```python
import torch

def _softmax(x, axis=-1):
    return torch.softmax(x, dim=axis)
def _gelu(x):
    return torch.nn.functional.gelu(x, approximate="tanh")
def _silu(x):
    return torch.nn.functional.silu(x)
def _sigmoid(x):
    return torch.sigmoid(x)
def _layernorm(x, axis=-1, eps=1e-5):
    m = x.mean(dim=axis, keepdim=True)
    v = x.var(dim=axis, keepdim=True, unbiased=False)
    return (x - m) / torch.sqrt(v + eps)
def _scatter_add(tgt, idx, src, axis=0):
    return tgt.clone().index_add_(axis, idx, src)
def _segment_sum(src, seg, n):
    out = torch.zeros((n,) + src.shape[1:], dtype=src.dtype)
    return out.index_add_(0, seg, src)
def _pad(x, pw):
    flat = tuple(v for pair in reversed(pw) for v in pair)
    return torch.nn.functional.pad(x, flat)

kernel_name = 'gather_scatter__molecular_angular_gemnet__graph'

def setup_inputs():

    _w = (lambda a: (lambda t: t.to(torch.bfloat16) if t.is_floating_point() else t)(torch.as_tensor(a)))
    N, deg, De, L = 10000, 64, 4, 1
    E = N * deg
    T = E * deg
    NR = 8
    dist = torch.rand(E).to(float)
    angle = (torch.rand(T) * torch.pi).to(float)
    centers = torch.linspace(0.0, 1.0, NR).to(float)
    ang_freq = torch.arange(1, L + 1).to(float)
    return {
        "m": _w((lambda *s: torch.randn(*s, dtype=torch.bfloat16) * 0.05)(E, De)),
        "idx_in": _w((lambda lo, hi, *s: torch.randint(lo, hi, s))(0, E, T).to(torch.int64)),
        "idx_out": _w((lambda lo, hi, *s: torch.randint(lo, hi, s))(0, E, T).to(torch.int64)),
        "dist": _w(dist),
        "angle": _w(angle),
        "centers": _w(centers),
        "ang_freq": _w(ang_freq),
        "w_rbf": _w((lambda *s: torch.randn(*s, dtype=torch.bfloat16) * 0.2)(NR, De)),
        "w_sbf": _w((lambda *s: torch.randn(*s, dtype=torch.bfloat16) * 0.2)(NR * L, De)),
        "w_down": _w((lambda *s: torch.randn(*s, dtype=torch.bfloat16) * 0.2)(De, De)),
        "w_up": _w((lambda *s: torch.randn(*s, dtype=torch.bfloat16) * 0.2)(De, De)),
    }

def reference(m, idx_in, idx_out, dist, angle, centers, ang_freq, w_rbf, w_sbf, w_down, w_up):
    E, De = m.shape[0], m.shape[1]
    NR = centers.shape[0]
    L = ang_freq.shape[0]
    rbf = torch.exp(-10.0 * (dist[:, None] - centers[None, :]) ** 2)
    cbf = torch.cos(ang_freq[None, :] * angle[:, None])
    rbf_t = rbf[idx_out]
    sbf = torch.reshape(rbf_t[:, :, None] * cbf[:, None, :], (-1, NR * L))
    x = (m[idx_in] @ w_down) * (sbf @ w_sbf)
    agg = _segment_sum(x, idx_out, E)
    return m + (agg @ w_up) * (rbf @ w_rbf)
```

```cpp
#include <cuda_runtime.h>
#include <cuda_bf16.h>
#include <stdint.h>

#define CFG_N1 56
#define CFG_NI 22
#define CFG_NW 28
#define CFG_P1W 14
#define CFG_GPW 2
#define CFG_KR 2
#define CFG_SMPAD 0
#define CFG_QPW 3
#define CFG_TG 2
#define CFG_PMASK 8
#define CFG_PSTREAK 1
#define CFG_NBT 1
#define CFG_SKEY 7
#define CFG_TBD 4
#define CFG_P0 500
#define CFG_NTK 16
#define CFG_CRE 0
#define CFG_TH 10
#define CFG_TS 300
#define CFG_POLL 64
#define CFG_HINT 20000
#define CFG_BSLEEP 100
#define CFG_CSLEEP 200
#define CFG_FSLEEP 100
#define CFG_PSLEEP 100
#define CFG_DRY 1
#define CFG_PROBES 4

namespace gs {

constexpr int E_MAX = 640000;
constexpr int N1 = CFG_N1, NI = CFG_NI, N2 = 2 * NI, N3 = 32, NCTA = N1 + N2 + N3;
constexpr int H2 = NI, H3 = N3 / 2;
constexpr int NB = NI * N3;
constexpr int NW = CFG_NW, NT = NW * 32;
constexpr int GPW = CFG_GPW, NF = NI / GPW;
constexpr int QPW = CFG_QPW, NBT = CFG_NBT;
constexpr int P1W = CFG_P1W, P2W = (N1 + QPW - 1) / QPW, P3W = NI;
constexpr int NQ1 = 32, NQ2 = 64;
constexpr int ROWS2_MAX = ((E_MAX + NI - 1) / NI + 31) / 8 * 8;
constexpr int ROWS3_MAX = (E_MAX / 32 + 31) / 32 * 32;
constexpr int NTAIL = N1 + N2;
constexpr int NPC = 5, WPP = 5, RPC = NTAIL * WPP * 8;
constexpr int GUARD = 1 << 26;
static_assert(NCTA % 4 == 0 && NCTA <= 192, "roles come in CTA pairs, per partition");
static_assert(NI % GPW == 0 && (GPW == 2 || GPW == 4) && QPW >= NBT && QPW <= 4 && NI <= 32 && N1 <= 62, "queue ownership");
static_assert(P1W + NF + 2 <= NW && P2W + 2 <= NW && P3W + 1 <= NW && P1W * 256 + 64 < 8192, "warp roles");
static_assert(ROWS2_MAX + 8 <= 32768 && ROWS3_MAX <= 32768, "index bits");

constexpr uint32_t SB = 1024;
constexpr int SM_DONE = 0;
constexpr int SM_MISC = 16;
constexpr int SM_FIN = 48;
constexpr int SM_STAT = 64;
constexpr int SM_CNT2 = 128;
constexpr int SM_W = 256;
constexpr int SM_PUB = SM_W + 384;
constexpr int SM_PROBE = SM_PUB + 768;
constexpr int SM_ZERO = 2048;
constexpr int SM_DATA = SM_ZERO + 4096;
constexpr int cmax(int a, int b) { return a > b ? a : b; }
constexpr int A_CNT = SM_DATA;
constexpr int A_LIST = A_CNT + NB * 4;
constexpr int KR = CFG_KR, LISTH = (GPW * 16 + 4 * KR + 31) / 32 * 128 + 16, LISTB = 2 * LISTH;
constexpr int A_ST = (A_LIST + NF * LISTB + 127) / 128 * 128;
constexpr int A_END = A_ST + NB * 256;
constexpr int B_TA = SM_DATA;
constexpr int B_TB = B_TA + (ROWS2_MAX + 8) * 4;
constexpr int B_END = B_TB + (ROWS2_MAX + 8) * 2;
constexpr int C_S = SM_DATA;
constexpr int C_END = C_S + ROWS3_MAX * 8;
constexpr int T_G = SM_DATA, T_END = T_G + NPC * WPP * 6144;
constexpr int ZEND = cmax(A_END, C_END);
constexpr int SMEM_BYTES = cmax(cmax(A_END, B_END), cmax(C_END, T_END)) + CFG_SMPAD;
static_assert(SMEM_BYTES <= 232448 && SM_PROBE + 128 <= SM_ZERO, "shared memory");
static_assert(NPC * RPC >= ROWS3_MAX && NPC * WPP + 2 <= NW, "tail");

constexpr uint32_t FIN = 0x80000000u;

constexpr uint32_t WIN = 524288;
constexpr int CWIN = N2 + N3, NWIN = CWIN + 2, CPAIRS = 31;
constexpr uint32_t PROBE_OFF = (uint32_t)NWIN * WIN;
constexpr int NPROBE = 16;
static_assert(NWIN <= NCTA && NPROBE <= NW, "windows");
constexpr size_t RING_BYTES = (size_t)PROBE_OFF + WIN;
__device__ __align__(128) unsigned char g_ring[2 * RING_BYTES + WIN];
__device__ __align__(128) uint32_t g_S[2][32][ROWS3_MAX];
__device__ __align__(128) float4 g_Sg[E_MAX];
__device__ uint32_t g_dirty[E_MAX / 32];
__device__ uint32_t g_epoch;

#define TR(ev, on)
#define ACC_DECL
#define ACC(i, n)
#define ACC_SAVE

struct Params {
    const uint2* m;
    const int* idx_in;
    const int* idx_out;
    const __nv_bfloat16* dist;
    const __nv_bfloat16* angle;
    const __nv_bfloat16* centers;
    const __nv_bfloat16* freq;
    const __nv_bfloat16* w_rbf;
    const __nv_bfloat16* w_sbf;
    const __nv_bfloat16* w_down;
    const __nv_bfloat16* w_up;
    uint2* out;
    unsigned char* ring;
    cudaTextureObject_t t_in, t_out, t_ang;
    int E, n4;
    uint32_t rows2, nrows2, magic2, rows3;
    uint32_t ring_lo, ring_hi, c1;
};

__device__ __forceinline__ float bflo(uint32_t w) { return __uint_as_float(w << 16); }
__device__ __forceinline__ float bfhi(uint32_t w) { return __uint_as_float(w & 0xffff0000u); }
__device__ __forceinline__ uint32_t pack_bf2(float lo, float hi) {
    uint32_t r;
    asm("cvt.rn.bf16x2.f32 %0, %1, %2;" : "=r"(r) : "f"(hi), "f"(lo));
    return r;
}
__device__ __forceinline__ uint32_t mul_bf2(uint32_t a, uint32_t b) {
    uint32_t r;
    asm("mul.rn.bf16x2 %0, %1, %2;" : "=r"(r) : "r"(a), "r"(b));
    return r;
}
__device__ __forceinline__ uint32_t sub_bf2(uint32_t a, uint32_t b) {
    uint32_t r;
    asm("sub.rn.bf16x2 %0, %1, %2;" : "=r"(r) : "r"(a), "r"(b));
    return r;
}
__device__ __forceinline__ uint32_t maxabs_bf2(uint32_t a, uint32_t b) {
    uint32_t r;
    asm("max.NaN.xorsign.abs.bf16x2 %0, %1, %2;" : "=r"(r) : "r"(a), "r"(b));
    return r;
}
__device__ __forceinline__ void mbar_init(uint32_t a, uint32_t n) {
    asm volatile("mbarrier.init.shared::cta.b64 [%0], %1;" ::"r"(a), "r"(n) : "memory");
}
__device__ __forceinline__ void mbar_arrive(uint32_t a) {
    asm volatile("mbarrier.arrive.shared::cta.b64 _, [%0];" ::"r"(a) : "memory");
}
__device__ __forceinline__ void mbar_arrive_n(uint32_t a, uint32_t n) {
    asm volatile("mbarrier.arrive.shared::cta.b64 _, [%0], %1;" ::"r"(a), "r"(n) : "memory");
}
__device__ __forceinline__ void mbar_arrive_if(uint32_t a, bool on) {
    asm volatile("{.reg .pred q; setp.ne.u32 q, %1, 0; @q mbarrier.arrive.shared::cta.b64 _, [%0];}" ::"r"(a), "r"((uint32_t)on) : "memory");
}
__device__ __forceinline__ void mbar_wait(uint32_t a, uint32_t parity) {
    uint32_t ok;
    int guard = 0;
    do {
        asm volatile("{.reg .pred p; mbarrier.try_wait.parity.shared::cta.b64 p, [%1], %2, %3; selp.u32 %0, 1, 0, p;}"
                     : "=r"(ok) : "r"(a), "r"(parity), "r"(CFG_HINT) : "memory");
        if (!ok) {
            if (++guard > GUARD) __trap();
        }
    } while (!ok);
}
__device__ __forceinline__ void cta_sync() { __syncwarp(); __syncthreads(); }
__device__ __forceinline__ void bar_sync(int id, int n) { asm volatile("bar.sync %0, %1;" ::"r"(id), "r"(n) : "memory"); }
__device__ __forceinline__ void bar_arrive(int id, int n) { asm volatile("bar.arrive %0, %1;" ::"r"(id), "r"(n) : "memory"); }
__device__ __forceinline__ bool mbar_test(uint32_t a, uint32_t parity) {
    uint32_t ok;
    asm volatile("{.reg .pred p; mbarrier.test_wait.parity.shared::cta.b64 p, [%1], %2; selp.u32 %0, 1, 0, p;}"
                 : "=r"(ok) : "r"(a), "r"(parity) : "memory");
    return ok;
}
__device__ __forceinline__ uint32_t ld_acq(const uint32_t* p) {
    uint32_t v;
    asm volatile("ld.acquire.gpu.global.u32 %0, [%1];" : "=r"(v) : "l"(p) : "memory");
    return v;
}
__device__ __forceinline__ uint32_t ld_rlx(const uint32_t* p) {
    uint32_t v;
    asm volatile("ld.relaxed.gpu.global.u32 %0, [%1];" : "=r"(v) : "l"(p) : "memory");
    return v;
}
__device__ __forceinline__ void st_rlx(uint32_t* p, uint32_t v) {
    asm volatile("st.relaxed.gpu.global.u32 [%0], %1;" ::"l"(p), "r"(v) : "memory");
}
__device__ __forceinline__ void red_rlx(uint32_t* p, uint32_t v) {
    asm volatile("red.relaxed.gpu.global.add.u32 [%0], %1;" ::"l"(p), "r"(v) : "memory");
}
__device__ __forceinline__ bool elect_one() {
    uint32_t p;
    asm volatile("{.reg .pred P; elect.sync _|P, 0xffffffff; selp.u32 %0, 1, 0, P;}" : "=r"(p));
    return p;
}
__device__ __forceinline__ uint32_t spin_ge(const uint32_t* p, uint32_t target) {
    int guard = 0;
    while (ld_rlx(p) < target) {
        __nanosleep(CFG_POLL);
        if (++guard > GUARD) __trap();
    }
    return ld_acq(p);
}
__device__ __forceinline__ void fence_gpu() { asm volatile("fence.acq_rel.gpu;" ::: "memory"); }
__device__ __forceinline__ void fence_async_smem() { asm volatile("fence.proxy.async.shared::cta;" ::: "memory"); }
__device__ __forceinline__ void fence_async_all() { asm volatile("fence.proxy.async;" ::: "memory"); }
__device__ __forceinline__ void bulk_store(void* g, uint32_t s, uint32_t bytes) {
    asm volatile("cp.async.bulk.global.shared::cta.bulk_group [%0], [%1], %2;" ::"l"(g), "r"(s), "r"(bytes) : "memory");
}
__device__ __forceinline__ void cp16(uint32_t s, const void* g, bool on) {
    asm volatile("{.reg .pred q; setp.ne.u32 q, %2, 0; @q cp.async.cg.shared.global [%0], [%1], 16;}" ::"r"(s), "l"(g), "r"((uint32_t)on) : "memory");
}
__device__ __forceinline__ void cp_commit() { asm volatile("cp.async.commit_group;" ::: "memory"); }
template <int N> __device__ __forceinline__ void cp_wait() { asm volatile("cp.async.wait_group %0;" ::"n"(N) : "memory"); }
__device__ __forceinline__ uint32_t atoms_add(uint32_t a, uint32_t v) {
    uint32_t o;
    asm volatile("atom.shared.add.u32 %0, [%1], %2;" : "=r"(o) : "r"(a), "r"(v) : "memory");
    return o;
}
__device__ __forceinline__ void sts32(uint32_t a, uint32_t v) { asm volatile("st.shared.u32 [%0], %1;" ::"r"(a), "r"(v) : "memory"); }
__device__ __forceinline__ void sts16(uint32_t a, uint32_t v) { asm volatile("st.shared.u16 [%0], %1;" ::"r"(a), "h"((uint16_t)v) : "memory"); }
__device__ __forceinline__ void sts64(uint32_t a, uint32_t x, uint32_t y) { asm volatile("st.shared.v2.u32 [%0], {%1,%2};" ::"r"(a), "r"(x), "r"(y) : "memory"); }
__device__ __forceinline__ uint32_t lds32(uint32_t a) {
    uint32_t v;
    asm volatile("ld.shared.u32 %0, [%1];" : "=r"(v) : "r"(a) : "memory");
    return v;
}
__device__ __forceinline__ uint2 lds64(uint32_t a) {
    uint2 v;
    asm volatile("ld.shared.v2.u32 {%0,%1}, [%2];" : "=r"(v.x), "=r"(v.y) : "r"(a));
    return v;
}
__device__ __forceinline__ uint2 lds64v(uint32_t a) {
    uint2 v;
    asm volatile("ld.volatile.shared.v2.u32 {%0,%1}, [%2];" : "=r"(v.x), "=r"(v.y) : "r"(a) : "memory");
    return v;
}
__device__ __forceinline__ uint32_t lds32v(uint32_t a) {
    uint32_t v;
    asm volatile("ld.volatile.shared.u32 %0, [%1];" : "=r"(v) : "r"(a) : "memory");
    return v;
}
__device__ __forceinline__ uint4 lds128(uint32_t a) {
    uint4 v;
    asm volatile("ld.shared.v4.u32 {%0,%1,%2,%3}, [%4];" : "=r"(v.x), "=r"(v.y), "=r"(v.z), "=r"(v.w) : "r"(a) : "memory");
    return v;
}
__device__ __forceinline__ void sts128(uint32_t a, uint4 v) {
    asm volatile("st.shared.v4.u32 [%0], {%1,%2,%3,%4};" ::"r"(a), "r"(v.x), "r"(v.y), "r"(v.z), "r"(v.w) : "memory");
}
#define LD_Q "ld.relaxed.gpu.global"
__device__ __forceinline__ uint4 ldg_q128(const void* p) {
    uint4 v;
    asm volatile(LD_Q ".v4.u32 {%0,%1,%2,%3}, [%4];"
                 : "=r"(v.x), "=r"(v.y), "=r"(v.z), "=r"(v.w) : "l"(p) : "memory");
    return v;
}
__device__ __forceinline__ uint2 ldg_q64(const void* p) {
    uint2 v;
    asm volatile(LD_Q ".v2.u32 {%0,%1}, [%2];" : "=r"(v.x), "=r"(v.y) : "l"(p) : "memory");
    return v;
}
__device__ __forceinline__ void red_v4(float4* p, float a, float b, float c, float d) {
    asm volatile("red.global.add.v4.f32 [%0], {%1,%2,%3,%4};" ::"l"(p), "f"(a), "f"(b), "f"(c), "f"(d) : "memory");
}
__device__ __forceinline__ uint2 down_row(uint2 r, const float* wd) {
    float x0 = bflo(r.x), x1 = bfhi(r.x), x2 = bflo(r.y), x3 = bfhi(r.y);
    float y[4];
#pragma unroll
    for (int j = 0; j < 4; j++) y[j] = x0 * wd[j] + x1 * wd[4 + j] + x2 * wd[8 + j] + x3 * wd[12 + j];
    return make_uint2(pack_bf2(y[0], y[1]), pack_bf2(y[2], y[3]));
}
__device__ __forceinline__ uint32_t prmt(uint32_t a, uint32_t b, uint32_t s) {
    uint32_t r;
    asm("prmt.b32 %0, %1, %2, %3;" : "=r"(r) : "r"(a), "r"(b), "r"(s));
    return r;
}
__device__ __forceinline__ uint32_t bitsel(uint32_t a, uint32_t b, uint32_t m) {
    uint32_t r;
    asm("lop3.b32 %0, %1, %2, %3, 0xE4;" : "=r"(r) : "r"(a), "r"(b), "r"(m));
    return r;
}
__device__ __forceinline__ uint32_t pack_h2(float lo, float hi) {
    uint32_t r;
    asm("cvt.rn.f16x2.f32 %0, %1, %2;" : "=r"(r) : "f"(hi), "f"(lo));
    return r;
}
__device__ __forceinline__ uint32_t mul_h2(uint32_t a, uint32_t b) {
    uint32_t r;
    asm("mul.rn.f16x2 %0, %1, %2;" : "=r"(r) : "r"(a), "r"(b));
    return r;
}
__device__ __forceinline__ uint32_t lds32nv(uint32_t a) {
    uint32_t v;
    asm volatile("ld.shared.u32 %0, [%1];" : "=r"(v) : "r"(a));
    return v;
}
__device__ __forceinline__ uint32_t lds16nv(uint32_t a) {
    uint32_t v;
    asm volatile("ld.shared.u16 %0, [%1];" : "=r"(v) : "r"(a));
    return v;
}
#define X_CR1
#define X_CR2
#define X_ST1
#define X_ST2
#define ST_Q "st.relaxed.gpu.global"
__device__ __forceinline__ void stg_q128(void* p, uint32_t a, uint32_t b, uint32_t c, uint32_t d, bool on) {
    asm volatile("{.reg .pred q; setp.ne.u32 q, %5, 0; @q " ST_Q ".v4.u32 [%0], {%1,%2,%3,%4};}"
                 ::"l"(p), "r"(a), "r"(b), "r"(c), "r"(d), "r"((uint32_t)on) : "memory");
}
__device__ __forceinline__ void stg_q64(void* p, uint32_t a, uint32_t b, bool on) {
    asm volatile("{.reg .pred q; setp.ne.u32 q, %3, 0; @q " ST_Q ".v2.u32 [%0], {%1,%2};}"
                 ::"l"(p), "r"(a), "r"(b), "r"((uint32_t)on) : "memory");
}
__device__ __forceinline__ void st_rlx_if(uint32_t* p, uint32_t v, bool on) {
    asm volatile("{.reg .pred q; setp.ne.u32 q, %2, 0; @q st.relaxed.gpu.global.u32 [%0], %1;}" ::"l"(p), "r"(v), "r"((uint32_t)on) : "memory");
}
__device__ __forceinline__ uint32_t ld_rlx_if(const uint32_t* p, bool on) {
    uint32_t v;
    asm volatile("{.reg .pred q; setp.ne.u32 q, %2, 0; mov.b32 %0, 0; @q ld.relaxed.gpu.global.u32 %0, [%1];}" : "=&r"(v) : "l"(p), "r"((uint32_t)on) : "memory");
    return v;
}
__device__ __forceinline__ void ldq128_keep(uint4& v, const void* p, bool on) {
    asm volatile("{.reg .pred q; setp.ne.u32 q, %5, 0; @q ld.relaxed.gpu.global.v4.u32 {%0,%1,%2,%3}, [%4];}"
                 : "+r"(v.x), "+r"(v.y), "+r"(v.z), "+r"(v.w) : "l"(p), "r"((uint32_t)on) : "memory");
}
__device__ __forceinline__ void ldq64_keep(uint2& v, const void* p, bool on) {
    asm volatile("{.reg .pred q; setp.ne.u32 q, %3, 0; @q ld.relaxed.gpu.global.v2.u32 {%0,%1}, [%2];}"
                 : "+r"(v.x), "+r"(v.y) : "l"(p), "r"((uint32_t)on) : "memory");
}
__device__ __forceinline__ void atoms_add_keep(uint32_t& o, uint32_t a, uint32_t v, bool on) {
    asm volatile("{.reg .pred q; setp.ne.u32 q, %3, 0; @q atom.shared.add.u32 %0, [%1], %2;}" : "+r"(o) : "r"(a), "r"(v), "r"((uint32_t)on) : "memory");
}
__device__ __forceinline__ void reds_add(uint32_t a, uint32_t v) { asm volatile("red.shared.add.u32 [%0], %1;" ::"r"(a), "r"(v) : "memory"); }
__device__ __forceinline__ void sts32_if(uint32_t a, uint32_t v, bool on) {
    asm volatile("{.reg .pred q; setp.ne.u32 q, %2, 0; @q st.shared.u32 [%0], %1;}" ::"r"(a), "r"(v), "r"((uint32_t)on) : "memory");
}
__device__ __forceinline__ void sts64_if(uint32_t a, uint32_t x, uint32_t y, bool on) {
    asm volatile("{.reg .pred q; setp.ne.u32 q, %3, 0; @q st.shared.v2.u32 [%0], {%1,%2};}" ::"r"(a), "r"(x), "r"(y), "r"((uint32_t)on) : "memory");
}
__device__ __forceinline__ void lds128_keep(uint4& v, uint32_t a, bool on) {
    asm volatile("{.reg .pred q; setp.ne.u32 q, %5, 0; @q ld.volatile.shared.v4.u32 {%0,%1,%2,%3}, [%4];}"
                 : "+r"(v.x), "+r"(v.y), "+r"(v.z), "+r"(v.w) : "r"(a), "r"((uint32_t)on) : "memory");
}
__device__ __forceinline__ void or3_if(uint32_t& x, uint32_t a, uint32_t b, bool on) {
    asm("{.reg .pred q; setp.ne.u32 q, %3, 0; @q lop3.b32 %0, %0, %1, %2, 0xfe;}" : "+r"(x) : "r"(a), "r"(b), "r"((uint32_t)on));
}
__device__ __forceinline__ uint32_t clk() {
    uint32_t t;
    asm volatile("mov.u32 %0, %%clock;" : "=r"(t) :: "memory");
    return t;
}
__device__ __forceinline__ void sg_add(int row, float a, float b, float c, float d) {
    red_v4(g_Sg + row, a, b, c, d);
    st_rlx(g_dirty + (row >> 5), 1u);
}
__device__ __forceinline__ void slow_add(const uint2* m, uint32_t sb, int in, int out, float c) {
    const uint2 r = __ldg(m + in);
    const float x[4] = {bflo(r.x), bfhi(r.x), bflo(r.y), bfhi(r.y)};
    float y[4] = {0.f, 0.f, 0.f, 0.f};
#pragma unroll
    for (int k = 0; k < 4; k++) {
        const uint4 q = lds128(sb + SM_W + 320 + k * 16);
        y[0] = k ? y[0] + x[k] * __uint_as_float(q.x) : x[k] * __uint_as_float(q.x);
        y[1] = k ? y[1] + x[k] * __uint_as_float(q.y) : x[k] * __uint_as_float(q.y);
        y[2] = k ? y[2] + x[k] * __uint_as_float(q.z) : x[k] * __uint_as_float(q.z);
        y[3] = k ? y[3] + x[k] * __uint_as_float(q.w) : x[k] * __uint_as_float(q.w);
    }
    const uint32_t lo = pack_bf2(y[0], y[1]), hi = pack_bf2(y[2], y[3]);
    sg_add(out, c * bflo(lo), c * bfhi(lo), c * bflo(hi), c * bfhi(hi));
}

struct Mat4 { uint32_t b[4]; };
__device__ __forceinline__ Mat4 load_mat4(const __nv_bfloat16* w, int lane) {
    const unsigned short* u = (const unsigned short*)w + (lane >> 2 & 1);
    const bool on = lane >> 3 == (lane & 3);
    Mat4 m;
#pragma unroll
    for (int k = 0; k < 4; k++) m.b[k] = on ? u[(k & 1) * 8 + (k & 2)] | (uint32_t)u[(k & 1) * 8 + 4 + (k & 2)] << 16 : 0u;
    return m;
}
__device__ __forceinline__ void mul4(const uint4& x, const Mat4& m, float (&y)[8]) {
#pragma unroll
    for (int h = 0; h < 2; h++)
        asm("mma.sync.aligned.m16n8k16.row.col.f32.bf16.bf16.f32 {%0,%1,%2,%3}, {%4,%5,%6,%7}, {%8,%9}, {%10,%10,%10,%10};"
            : "=f"(y[2 * h]), "=f"(y[2 * h + 1]), "=f"(y[4 + 2 * h]), "=f"(y[5 + 2 * h])
            : "r"(x.x), "r"(x.z), "r"(x.y), "r"(x.w), "r"(m.b[2 * h]), "r"(m.b[2 * h + 1]), "f"(0.f));
}

struct Scale { uint32_t eb[4]; bool allslow; };
__device__ __forceinline__ void md_stats(const uint4& in, const Mat4& wd, int lane) {
    float y[8];
    mul4(in, wd, y);
    uint32_t mx[4], se[4];
#pragma unroll
    for (int c = 0; c < 4; c++) {
        uint32_t a = __float_as_uint(y[c]) & 0x7fffffffu, b = __float_as_uint(y[4 + c]) & 0x7fffffffu;
        if (a >= 0x7f800000u) a = 0;
        if (b >= 0x7f800000u) b = 0;
        mx[c] = __reduce_max_sync(0xffffffffu, max(a, b));
        se[c] = __reduce_add_sync(0xffffffffu, (a >> 23) + (b >> 23) + (a ? 1u << 20 : 0u) + (b ? 1u << 20 : 0u));
    }
    if (lane < 4) {
        asm volatile("red.shared.max.u32 [%0], %1;" ::"r"(SB + SM_STAT + lane * 4), "r"(lane == 0 ? mx[0] : lane == 1 ? mx[1] : lane == 2 ? mx[2] : mx[3]) : "memory");
        reds_add(SB + SM_STAT + 16 + lane * 4, lane == 0 ? se[0] : lane == 1 ? se[1] : lane == 2 ? se[2] : se[3]);
    }
}
__device__ __forceinline__ Scale get_scale(uint32_t sb) {
    Scale s;
    s.allslow = false;
#pragma unroll
    for (int k = 0; k < 4; k++) {
        const uint32_t mx = lds32(sb + SM_STAT + 4 * k), se = lds32(sb + SM_STAT + 16 + 4 * k);
        const uint32_t mean = (uint32_t)__fdividef((float)(se & 0xfffffu), (float)max(se >> 20, 1u));
        uint32_t eb = min(min((mx + 0x6e0000u) >> 23, mean + 5u), 227u);
        if (eb < 27u) { s.allslow = s.allslow || mx != 0; eb = 27u; }
        s.eb[k] = eb;
    }
    return s;
}

__device__ __forceinline__ uint32_t probe_rt(uint32_t* p) {
    uint32_t best = 0xffffffffu;
#pragma unroll 1
    for (int r = 0; r < CFG_PROBES; r++) {
        const uint32_t t0 = clock();
        uint32_t v;
        asm volatile("atom.relaxed.gpu.global.add.u32 %0, [%1], 1;" : "=r"(v) : "l"(p) : "memory");
        if (v > 100000u) __trap();
        const uint32_t t1 = clock();
        best = min(best, t1 - t0);
    }
    return best;
}
__device__ __forceinline__ uint32_t* pub_ptr(const Params& p, int blk, uint32_t sel) {
    const int pr = blk / 44;
    return (uint32_t*)(p.ring + PROBE_OFF + (pr ? 4096u << pr : 0u) + (sel << 12) + 2176 + (blk - pr * 44) * 32);
}
__device__ __forceinline__ void probe(const Params& p, uint32_t sb, int w, int lane) {
    const int blk = blockIdx.x, pr = w >> 1;
    uint32_t off = PROBE_OFF + blk * 16 + (pr ? 4096u << pr : 0u);
    if (pr == 7) off = blk < NWIN ? blk * WIN + 4064 : PROBE_OFF + 3584 + blk % 16 * 32;
    off += (w & 1) * 4096;
    if (lane < 8) st_rlx((uint32_t*)(p.ring + (off & ~31u)) + lane, 0u);
    if (lane == 0) sts32(sb + SM_PROBE + w * 4, probe_rt((uint32_t*)(p.ring + off)));
}
__device__ __forceinline__ void assign_role(const Params& p, uint32_t sb, int lane) {
    {
        const bool x = lane < 8 && lds32(sb + SM_PROBE + lane * 8 + 4) < lds32(sb + SM_PROBE + lane * 8);
        const uint32_t near = __ballot_sync(0xffffffffu, x), bits = near & 1 ? ~near | 1u : near;
        const uint32_t tag = (lds32(sb + SM_MISC + 16) + 1) << 30;
        uint32_t smid;
        asm("mov.u32 %0, %%smid;" : "=r"(smid));
        if (lane < 16) st_rlx(pub_ptr(p, blockIdx.x, lane >> 3) + (lane & 7), tag | (smid & 0xffffu) << 8 | (bits & 0xffu));
        constexpr int K = (NCTA + 31) / 32;
        __nanosleep(CFG_P0);
        uint32_t v[K], bad;
        int guard = 0;
        do {
            bad = 0;
#pragma unroll
            for (int k = 0; k < K; k++) {
                const int b = min(lane + 32 * k, NCTA - 1);
                v[k] = ld_rlx(pub_ptr(p, b, near >> (b / 44) & 1));
                bad |= v[k] ^ tag;
            }
            bad = __any_sync(0xffffffffu, bad >> 30);
            if (bad) __nanosleep(CFG_PSLEEP);
            if (++guard > GUARD) __trap();
        } while (bad);
#pragma unroll
        for (int k = 0; k < K; k++) sts32(sb + SM_PUB + (lane + 32 * k) * 4, v[k]);
    }
    __syncwarp();
    constexpr int NP = NCTA / 2, NTAB = H2 + H3;
    const int me = blockIdx.x >> 1, odd = blockIdx.x & 1;
    uint32_t pp[3], st[5] = {0, 0, 0, 0, 0}, key[3];
    int n1 = 0;
#pragma unroll
    for (int k = 0; k < 3; k++) {
        const int i = lane + 32 * k;
        const uint32_t a = lds32(sb + SM_PUB + min(i, NP - 1) * 8), b = lds32(sb + SM_PUB + min(max(i - 1, 0), NP - 1) * 8);
        pp[k] = a & 1;
        st[k + 1] = __ballot_sync(0xffffffffu, i == 0 || i >= NP || (a >> 8) < (b >> 8));
        n1 += 2 * __popc(__ballot_sync(0xffffffffu, i < NP && pp[k]));
    }
    bool fixed = n1 < NTAB || NCTA - n1 < NTAB;
    if (fixed) n1 = NP / 2 * 2;
#pragma unroll
    for (int k = 0; k < 3; k++) {
        const uint32_t rank = __clz(__funnelshift_rc(st[k], st[k + 1], lane + 1)), len = rank + __ffs(__funnelshift_rc(st[k + 1], st[k + 2], lane + 1));
        if (fixed) pp[k] = lane & 1;
        key[k] = (len < 4 ? CFG_SKEY : min(rank, 15u) * 2) << 8 | (lane + 32 * k);
    }
    const uint32_t mine = __shfl_sync(0xffffffffu, (me < 32 ? key[0] : me < 64 ? key[1] : key[2]) * 2 + (me < 32 ? pp[0] : me < 64 ? pp[1] : pp[2]), me & 31);
    const int part = mine & 1;
    int pos = odd;
#pragma unroll
    for (int k = 0; k < 3; k++) pos += 2 * __popc(__ballot_sync(0xffffffffu, lane + 32 * k < NP && pp[k] == (uint32_t)part && key[k] < mine / 2));
    const int role = pos < H2 ? 1 : pos < NTAB ? 2 : 0;
    const int id = pos < H2 ? part * H2 + pos : pos < NTAB ? part * H3 + pos - H2 : (part ? NCTA - n1 - NTAB : 0) + pos - NTAB;
    const uint32_t v = lds32(sb + SM_PUB + lane * 4);
    uint32_t lin = 0;
#pragma unroll
    for (int b = 0; b < 6; b++) lin |= (__popc(__ballot_sync(0xffffffffu, (v >> (b + 1)) & 1)) > 16 ? 1u : 0u) << b;
    if (lane == 0) {
        sts32(sb + SM_MISC, role << 8 | id);
        sts32(sb + SM_MISC + 4, lin);
        sts32(sb + SM_MISC + 8, NCTA - n1 - NTAB);
        sts32(sb + SM_MISC + 20, part);
        sts32(sb + SM_MISC + 12, role == 0 ? id : role == 1 ? N1 + id : N1 + N2 + id);
    }
}
__device__ __forceinline__ uint32_t sel_of(uint32_t sb, int widx, uint32_t k, int part) {
    return (__popc(k & lds32(sb + SM_MISC + 4)) ^ (lds32(sb + SM_PUB + widx * 4) >> 7) ^ part) & 1;
}
__device__ __forceinline__ uint32_t gran_off(uint32_t sb, int widx, int k, int part) { return (2 * k + sel_of(sb, widx, k, part)) << 12; }
__device__ __forceinline__ uint32_t q1a_off(uint32_t sb, int src, int blk, int part) { return gran_off(sb, 2 * blk + part, src >> 1, part) + (src & 1) * 2048; }
__device__ __forceinline__ uint32_t q1h_off(uint32_t sb, int src, int blk, int part) { return gran_off(sb, 2 * blk + part, 32 + (src >> 2), part) + (src & 3) * 1024; }
__device__ __forceinline__ uint32_t* ctl_word(const Params& p, uint32_t sb, int k, int word, int part) {
    const int widx = CWIN + lds32(sb + SM_MISC + 16);
    return (uint32_t*)(p.ring + (widx * WIN + ((2 * k + sel_of(sb, widx, k, part)) << 12))) + word;
}
__device__ __forceinline__ uint32_t* cred1_of(const Params& p, uint32_t sb, int src) { return ctl_word(p, sb, src >> 3, (src & 7) * 128, src >= (int)lds32(sb + SM_MISC + 8)); }
__device__ __forceinline__ uint32_t* fin1_of(const Params& p, uint32_t sb, int dst) { return ctl_word(p, sb, 8 + (dst >> 3), (dst & 7) * 128, dst / H2); }
__device__ __forceinline__ uint32_t* cred2_of(const Params& p, uint32_t sb, int src) { return ctl_word(p, sb, 16 + (src >> 3), (src & 7) * 128, src / H2); }
__device__ __forceinline__ uint32_t* fin2_of(const Params& p, uint32_t sb, int dst) { return ctl_word(p, sb, 24 + (dst >> 3), (dst & 7) * 128, dst / H3); }
__device__ __forceinline__ uint32_t* rdy_of(const Params& p, uint32_t sb, int word, int part) { return ctl_word(p, sb, 28, word, part); }
__device__ __forceinline__ uint32_t q2_off(uint32_t sb, int blk, int dst) {
    return (N2 + dst) * WIN + gran_off(sb, N2 + dst, (blk >> 1) * 4 + (blk & 1), dst / H3);
}
template <bool IS1>
__device__ __forceinline__ void clear_queues(const Params& p, uint32_t sb, int id, int lane) {
    constexpr int NA = (N1 + 1) / 2, N = IS1 ? NA + (N1 + 3) / 4 : NI * 2;
    fence_async_smem();
    for (int k = lane; k < N; k += 32) {
        const int wi = 2 * (id % H2) + id / H2;
        const uint32_t off = IS1 ? wi * WIN + gran_off(sb, wi, k < NA ? k : 32 + k - NA, id / H2) : q2_off(sb, k >> 1, id) + (k & 1) * 16384;
        bulk_store(p.ring + off, sb + SM_ZERO, 4096);
    }
    asm volatile("cp.async.bulk.commit_group;" ::: "memory");
    asm volatile("cp.async.bulk.wait_group 0;" ::: "memory");
    if (!IS1) {
        fence_async_all();
        __syncwarp();
        fence_gpu();
        if (lane < NI) red_rlx(rdy_of(p, sb, id / H3 * H2 + lane, id / H3), 1u);
    }
    __syncwarp();
}

struct In8 { uint4 a[2], o[2]; uint2 g[2]; };
__device__ __forceinline__ void p1_load(const Params& p, In8& r, int i4) {
#pragma unroll
    for (int u = 0; u < 2; u++) {
        [[maybe_unused]] uint32_t x, y;
        asm volatile("tex.1d.v4.u32.s32 {%0,%1,%2,%3}, [%4, {%5}];" : "=r"(r.a[u].x), "=r"(r.a[u].y), "=r"(r.a[u].z), "=r"(r.a[u].w) : "l"(p.t_in), "r"(i4 + u * 32));
        asm volatile("tex.1d.v4.u32.s32 {%0,%1,%2,%3}, [%4, {%5}];" : "=r"(r.o[u].x), "=r"(r.o[u].y), "=r"(r.o[u].z), "=r"(r.o[u].w) : "l"(p.t_out), "r"(i4 + u * 32));
        asm volatile("tex.1d.v4.u32.s32 {%0,%1,%2,%3}, [%4, {%5}];" : "=r"(r.g[u].x), "=r"(r.g[u].y), "=r"(x), "=r"(y) : "l"(p.t_ang), "r"(i4 + u * 32));
    }
}
__device__ __forceinline__ uint32_t imad(uint32_t a, uint32_t b, uint32_t c) {
    uint32_t r;
    asm("mad.lo.u32 %0, %1, %2, %3;" : "=r"(r) : "r"(a), "r"(b), "r"(c));
    return r;
}
__device__ __forceinline__ unsigned char* ring_ptr(const Params& p, uint32_t lo) {
    uint64_t r;
    asm("mov.b64 %0, {%1, %2};" : "=l"(r) : "r"(lo), "r"(p.ring_hi));
    return (unsigned char*)r;
}
__device__ __forceinline__ uint32_t opaque32(uint32_t x) {
    asm volatile("" : "+r"(x));
    return x;
}
template <typename T> __device__ __forceinline__ T* opaque(T* p) {
    asm volatile("" : "+l"(p));
    return p;
}
template <int LUT> __device__ __forceinline__ uint32_t lop3(uint32_t a, uint32_t b, uint32_t c) {
    uint32_t r;
    asm("lop3.b32 %0, %1, %2, %3, %4;" : "=r"(r) : "r"(a), "r"(b), "r"(c), "n"(LUT));
    return r;
}
__device__ __forceinline__ uint32_t dp4(uint32_t a, uint32_t b, uint32_t c) {
    uint32_t r;
    asm("dp4a.u32.u32 %0, %1, %2, %3;" : "=r"(r) : "r"(a), "r"(b), "r"(c));
    return r;
}
__device__ __forceinline__ uint32_t dp2(uint32_t a, uint32_t b, uint32_t c) {
    uint32_t r;
    asm("dp2a.lo.u32.u32 %0, %1, %2, %3;" : "=r"(r) : "r"(a), "r"(b), "r"(c));
    return r;
}
__device__ __forceinline__ void p1_put(uint32_t sb, uint32_t wa, uint32_t wb, uint32_t old, bool on) {
    asm volatile("{.reg .pred q; setp.ne.u32 q, %3, 0; @q st.shared.v2.u32 [%0], {%1,%2};}"
                 ::"r"(sb + A_ST + prmt(old, wb, 0xf762)), "r"(wa), "r"(prmt(wb, old, 0x7210)), "r"((uint32_t)on) : "memory");
}
__device__ __forceinline__ void p1_slow_tile(const Params& p, uint32_t sb, int i4) {
    const float f = __bfloat162float(p.freq[0]);
#pragma unroll 1
    for (int u = 0; u < 8; u++) {
        const int k4 = i4 + (u >> 2) * 32;
        if (k4 < p.n4) {
            const size_t t = (size_t)k4 * 4 + (u & 3);
            const float x = __bfloat162float(__float2bfloat16(f * __bfloat162float(p.angle[t])));
            slow_add(p.m, sb, p.idx_in[t], p.idx_out[t], __bfloat162float(__float2bfloat16(cosf(x))));
        }
    }
}
__device__ __forceinline__ void role_p1(const Params& p, uint32_t sb, int id, int w, int lane) {
    const uint32_t f2 = (uint32_t)__bfloat16_as_ushort(p.freq[0]) * 0x10001u;
    constexpr int TG = CFG_TG, NTK = CFG_NTK;
    static_assert(N1 * P1W % NTK == 0 && (NTK == 16 || NTK == 8) && P1W % 2 == 0, "tickets");
    const int first = (N1 * P1W + (id * P1W + w) % NTK) * (TG * 64);
    uint32_t* const tickets = opaque(ctl_word(p, sb, 29 + (id * P1W + w) % NTK / 8, (id * P1W + w) % 8 * 128 + lane, w & 1));
    auto draw = [&]() {
        uint32_t t = 0;
        asm volatile("{.reg .pred q; setp.eq.u32 q, %2, 0; @q atom.relaxed.gpu.global.add.u32 %0, [%1], 1;}" : "+r"(t) : "l"(tickets), "r"(lane) : "memory");
        return t;
    };
    int i4 = (id * P1W + w) * (TG * 64);
    In8 r;
    ACC_DECL
    uint32_t tk = draw();
    p1_load(p, r, i4 + lane);
    while (i4 < p.n4) {
        const int cur = i4;
        i4 += 64;
        if (i4 % (TG * 64) == 0) {
            i4 = min(__shfl_sync(0xffffffffu, tk, 0), 0x7fffffffu / (NTK * TG * 64) - N1 * P1W / NTK - 2) * (NTK * TG * 64) + first;
            tk = draw();
        }
        uint32_t wa[8], wb[8], x2[4];
        x2[0] = mul_bf2(r.g[0].x, f2); x2[1] = mul_bf2(r.g[0].y, f2);
        x2[2] = mul_bf2(r.g[1].x, f2); x2[3] = mul_bf2(r.g[1].y, f2);
        const uint32_t mx = maxabs_bf2(maxabs_bf2(x2[0], x2[1]), maxabs_bf2(x2[2], x2[3]));
        const bool fast = __all_sync(0xffffffffu, cur + 64 <= p.n4 && ((mx & 0x7fffu) <= 0x4300u) && ((mx & 0x7fff0000u) <= 0x43000000u));
        {
            const uint32_t in[8] = {r.a[0].x, r.a[0].y, r.a[0].z, r.a[0].w, r.a[1].x, r.a[1].y, r.a[1].z, r.a[1].w};
            const uint32_t ou[8] = {r.o[0].x, r.o[0].y, r.o[0].z, r.o[0].w, r.o[1].x, r.o[1].y, r.o[1].z, r.o[1].w};
#pragma unroll
            for (int j = 0; j < 8; j += 2) {
                const uint32_t ch = mul_h2(pack_h2(__cosf(bflo(x2[j >> 1])), __cosf(bfhi(x2[j >> 1]))), 0x24002400u);
#pragma unroll
                for (int k = j; k < j + 2; k++) {
                    const uint32_t blk = __umulhi(in[k], p.magic2), il = imad(blk, p.nrows2, in[k]);
                    wa[k] = k & 1 ? bitsel(ch, il, 0xffff0000u) : imad(ch, 65536u, il);
                    wb[k] = imad(blk, 1u << 21, imad(ou[k] >> 5, 1u - (1u << 21), ou[k] << 16));
                }
            }
        }
        p1_load(p, r, i4 + lane);
        if (fast) {
            uint32_t old[8], any = 0;
#pragma unroll
            for (int j = 0; j < 8; j++) old[j] = atoms_add(dp2(wb[j], 0x400u, 0u) + (sb + A_CNT), 0x80001u);
#pragma unroll
            for (int j = 0; j < 8; j++) any |= old[j];
            if (!__any_sync(0xffffffffu, any & 0xffe0u)) {
#pragma unroll
                for (int j = 0; j < 8; j++) p1_put(sb, wa[j], wb[j], old[j], true);
            } else {
                uint32_t pend = 0;
#pragma unroll
                for (int j = 0; j < 8; j++) { p1_put(sb, wa[j], wb[j], old[j], !(old[j] & 0xffe0u)); if (old[j] & 0xffe0u) pend |= 1u << j; }
                ACC(0, 1)
                for (int guard = 0; __any_sync(0xffffffffu, pend); guard++) {
                    __nanosleep(CFG_BSLEEP);
                    ACC(1, 1)
#pragma unroll
                    for (int j = 0; j < 8; j++) {
                        if (__any_sync(0xffffffffu, pend >> j & 1)) {
                            const uint32_t c = lds32v(sb + A_CNT + (pend >> j & 1 ? wb[j] >> 16 : 0) * 4);
                            const bool go = (pend >> j & 1) && (((old[j] >> 19) - (c >> 19) + c) & 8191u) < 32u;
                            p1_put(sb, wa[j], wb[j], old[j], go);
                            if (go) pend &= ~(1u << j);
                        }
                    }
                    if (guard > GUARD) __trap();
                }
            }
        } else {
            p1_slow_tile(p, sb, cur + lane);
            __syncwarp();
        }
    }
    __syncwarp();
    mbar_arrive_if(sb + SM_DONE, lane == 0);
    ACC_SAVE
}

__device__ __forceinline__ void role_flush(const Params& p, uint32_t sb, int id, int f, int lane) {
    const int half = lane >> 4, o = lane >> 2, q = lane & 3;
    const uint32_t hm = half ? 0xffff0000u : 0xffffu, lth = ((1u << lane) - 1) & hm;
    const uint32_t list = sb + A_LIST + f * LISTB + half * LISTH, cnt = sb + A_CNT + (f * GPW * 32 + lane) * 4;
    const uint32_t* const cred = opaque(cred1_of(p, sb, id) + half * 32 + f * GPW);
    const uint32_t pa = opaque32(p.ring_lo + half * WIN + (id >> 1) * 8192 + (id & 1) * 2048 + q * 16);
    const uint32_t ph = opaque32(p.ring_lo + half * WIN + (32 + (id >> 2)) * 8192 + (id & 3) * 1024 + q * 8 - 2048);
    const uint32_t sa = q * 16 + (o & 1) * 64;
    uint32_t qo[GPW], hs[GPW], cr[4] = {0, 0, 0, 0};
#pragma unroll
    for (int g = 0; g < GPW; g++) {
        const int blk = f * GPW + g;
        qo[g] = 32u << 25;
        const uint32_t sa = sel_of(sb, 2 * blk + half, id >> 1, half), sh = sel_of(sb, 2 * blk + half, 32 + (id >> 2), half);
        hs[g] = sa << 31 | (2 * sh + 1 - sa) << 22 | 1u << 24 | (lane & 15) << 15 | (blk * 32 + lane) * 2;
    }
    uint4 x[KR] = {}, y[KR] = {};
    ACC_DECL
    int guard = 0;
    bool idle = false, done = false;
    while (true) {
        uint32_t c[GPW], fr[GPW], end = list, left = 0;
        if (idle && !done && __all_sync(0xffffffffu, mbar_test(sb + SM_DONE, 0))) {
            done = true;
            TR(17, f == 0 && lane == 0);
#pragma unroll
            for (int g = 0; g < GPW; g++) {
                const uint32_t u = lds32v(cnt + g * 128) & 31u, hd = hs[g] ^ (u & 16u ? imad(hs[g], 1u << 24, 1u) & 0x01000001u : 0u);
#pragma unroll 3
                for (uint32_t k = 1; k < 16; k++)
                    sts64_if(sb + A_ST + ((hd & 0x7ffu) << 7) + k * 8, p.rows2, (lane * 16 + k) | (hd & 0x1000000u), (u & 15u) && k >= (u & 15u));
                reds_add(cnt + g * 128, ((0u - u) & 15u) * 0x80001u);
            }
            __syncwarp();
        }
#pragma unroll
        for (int g = 0; g < GPW; g++) c[g] = lds32v(cnt + g * 128);
#pragma unroll
        for (int g = 0; g < GPW; g++) {
            const bool isfull = c[g] & 0xfff0u;
            const uint32_t m = __ballot_sync(0xffffffffu, isfull), rank = __popc(m & lth), r25 = rank << 25;
            const bool ok = isfull && (int)r25 < (int)(cr[g] - qo[g] + (63u << 25));
            const uint32_t n = __popc(__ballot_sync(0xffffffffu, ok) & hm);
            ACC(2, __popc(__ballot_sync(0xffffffffu, isfull && !ok)))
            sts32_if(imad(rank, 4u, end), bitsel(qo[g] + r25, hs[g], 0x7e000000u), ok);
            if (ok) hs[g] ^= imad(hs[g], 1u << 24, 1u) & 0x01000001u;
            fr[g] = ok ? 0u - 16u : 0u;
            left |= c[g] + fr[g];
            qo[g] = imad(n, 1u << 25, qo[g]);
            end = imad(n, 4u, end);
        }
        auto credits = [&]() {
            if (GPW == 4) { const uint4 v = ldg_q128(cred); cr[0] = v.x; cr[1] = v.y; cr[2] = v.z; cr[3] = v.w; }
            else { const uint2 v = ldg_q64(cred); cr[0] = v.x; cr[1] = v.y; }
        };
        if (CFG_CRE) credits();
        __syncwarp();
        ACC(0, 1) ACC(1, (end - list) / 2)
        if (__any_sync(0xffffffffu, end != list)) {
            uint32_t la = list + (o & 3) * 4;
            do {
                uint32_t d[KR];
#pragma unroll
                for (int k = 0; k < KR; k++) d[k] = lds32v(la + 16 * k);
                while (true) {
                    uint32_t bad = 0;
#pragma unroll
                    for (int k = 0; k < KR; k++) {
                        const uint32_t m = d[k] & 0x7ffu;
                        lds128_keep(x[k], imad(m, 128u, sa) + (sb + A_ST), la + 16 * k < end);
                        lds128_keep(y[k], imad(m, 128u, sa ^ 64) + (sb + A_ST), la + 16 * k < end);
                    }
#pragma unroll
                    for (int k = 0; k < KR; k++)
                        or3_if(bad, lop3<0x7e>(x[k].y, x[k].w, d[k]), lop3<0x7e>(y[k].y, y[k].w, d[k]), la + 16 * k < end);
                    if (!__any_sync(0xffffffffu, (int)imad(bad, 128u, 0u) < 0)) break;
                    if (++guard > GUARD) __trap();
                }
#pragma unroll
                for (int k = 0; k < KR; k++) {
                    const uint32_t mi = d[k] & 0x7c0u, dm = d[k] & 0xbec00000u;
                    x[k].x = bitsel(d[k], x[k].x, 0x40078000u);
                    x[k].y = prmt(x[k].y, x[k].w, 0x5410);
                    x[k].w = prmt(y[k].y, y[k].w, 0x5410);
                    y[k].x = bitsel(d[k], y[k].x, 0x40000000u);
                    y[k].y = y[k].z;
                    stg_q128(ring_ptr(p, dp4(dm, 0x20000000u, imad(mi, WIN / 32, pa))), x[k].x, x[k].y, x[k].z, x[k].w, X_ST1 la + 16 * k < end);
                    stg_q64(ring_ptr(p, dp4(dm, 0x10200000u, imad(mi, WIN / 32, ph))), y[k].x, y[k].y, X_ST1 la + 16 * k < end);
                }
                la += 16 * KR;
            } while (__any_sync(0xffffffffu, la < end));
            if (!CFG_CRE) credits();
#pragma unroll
            for (int g = 0; g < GPW; g++) reds_add(cnt + g * 128, fr[g]);
            idle = !__any_sync(0xffffffffu, end - list > 4 * CFG_TH);
            if (done && !__any_sync(0xffffffffu, left & 0xffffu)) break;
            if (idle) __nanosleep(CFG_TS);
        } else {
            if (done && !__any_sync(0xffffffffu, left & 0xffffu)) break;
            if (!CFG_CRE && __any_sync(0xffffffffu, left & 0xfff0u)) credits();
            idle = true;
            __nanosleep(CFG_FSLEEP);
            if (++guard > GUARD) __trap();
        }
    }
#pragma unroll
    for (int g = 0; g < GPW; g++) st_rlx_if(fin1_of(p, sb, half * H2 + f * GPW + g) + id, qo[g] - (32u << 25) + 1u, (lane & 15) == 0);
    TR(18, f == 0 && lane == 0);
    ACC_SAVE
}

__device__ __forceinline__ float h2f(uint32_t h) {
    float f;
    asm("{.reg .b16 t; cvt.u16.u32 t, %1; cvt.f32.f16 %0, t;}" : "=f"(f) : "r"(h));
    return f;
}
__device__ __forceinline__ void p2_slow(const Params& p, uint32_t sb, const uint32_t* tmp, int row0, uint32_t dst) {
#pragma unroll 1
    for (int j = 0; j < 4; j++)
        if (tmp[8 + j] & 0x40u) slow_add(p.m, sb, row0 + (tmp[j] & 0x7fffu), (tmp[4 + j] & 0x7fffu) * 32 + dst, h2f(tmp[j] >> 16) * 64.0f);
}
__device__ __forceinline__ uint32_t mul_h2_hi(uint32_t a, uint32_t b) {
    uint32_t r;
    asm("{.reg .b16 l, h; .reg .b32 t; mov.b32 {l, h}, %2; mov.b32 t, {h, h}; mul.rn.f16x2 %0, %1, t;}" : "=r"(r) : "r"(a), "r"(b));
    return r;
}
template <bool CHECK>
__device__ __forceinline__ void role_p2(const Params& p, uint32_t sb, int id, int w, int lane) {
    const int part = id / H2, blk = id - part * H2, row0 = blk * p.rows2;
    const int o = lane >> 2, q = lane & 3;
    uint32_t* const cbase = (uint32_t*)(p.ring + (CWIN + lds32(sb + SM_MISC + 16)) * WIN);
    const uint32_t cred = opaque32((uint32_t)(uintptr_t)(cbase + part * 32 + blk));
    const uint32_t pa = opaque32(p.ring_lo + (2 * blk + part) * WIN + q * 16), ph = opaque32(pa - q * 8);
    const uint32_t po = opaque32(p.ring_lo + (q2_off(sb, blk, part * H3) & ~4096u) + q * 16 + (o & 1) * 64);
    const uint32_t sel = __ballot_sync(0xffffffffu, q2_off(sb, blk, part * H3 + (lane & 15)) & 4096u) << 12;
    const uint32_t* const fins = fin1_of(p, sb, id);
    uint32_t st[QPW] = {}, sq[QPW] = {};
    uint4 qa[NBT];
    uint2 qh[NBT];
    auto load = [&](int k) {
        qa[k] = ldg_q128(ring_ptr(p, pa + (bitsel(sq[k], st[k] >> 19, 0x7f800u) & 0x7ffc0u)));
        qh[k] = ldg_q64(ring_ptr(p, ph + (bitsel(sq[k] >> 9, st[k] >> 20, 0x7fc00u) & 0x7ffe0u)));
    };
#pragma unroll
    for (int k = 0; k < QPW; k++) {
        const int src = w * QPW + k;
        st[k] = o << 25 | (src < N1 ? 1u : 5u);
        sq[k] = src < N1 ? q1h_off(sb, src, blk, part) << 9 | q1a_off(sb, src, blk, part) | (uint32_t)(cred1_of(p, sb, src) - cbase) / 8 : 0x7e000u * 513u;
    }
#pragma unroll
    for (int k = 0; k < NBT; k++) load(k);
    ACC_DECL
    int guard = 0;
    uint32_t streak = 0;
    while (true) {
        uint32_t nn[NBT], xx[NBT][4], hh[NBT][2], dd[NBT], any = 0;
        bool last = false;
#pragma unroll
        for (int k = 0; k < NBT; k++) {
            const uint4 a = qa[k];
            const uint2 h = qh[k];
            uint32_t n = 8;
            const uint32_t miss = __ballot_sync(0xffffffffu, (int)imad((a.x ^ st[k]) & (h.x ^ st[k]), 2u, 0u) >= 0);
            if (miss) {
                n = (__ffs(miss) - 1) >> 2;
                if (!__any_sync(0xffffffffu, st[k] & 8u)) { if (streak < CFG_PSTREAK) n &= CFG_PMASK; }
                else if (!__any_sync(0xffffffffu, ((st[k] >> 6) + ((n - o) << 19) ^ st[k]) & 0x1f80000u)) { st[k] |= 4u; last = true; }
            }
            ACC(1, n == 0) ACC(2, n != 0) ACC(3, n)
            st[k] = imad(n, 1u << 25, st[k]);
            st_rlx_if((uint32_t*)ring_ptr(p, imad(sq[k] & 0x7f0u, 32u, cred)), st[k], X_CR1 lane == 0 && n);
            xx[k][0] = bitsel(a.x, 0x00040000u, 0xbff87fffu); xx[k][1] = a.z; xx[k][2] = h.x & 0xbfffffffu; xx[k][3] = h.y;
            hh[k][0] = a.y; hh[k][1] = a.w; dd[k] = a.x >> 13 & 0x3cu; nn[k] = n;
            any |= n;
        }
        if (!any) {
#pragma unroll
            for (int k = 0; k < QPW; k++) {
                const uint32_t fin = ld_rlx(fins + ((sq[k] >> 12 & 62u) | (sq[k] >> 11 & 1u)));
                if (fin & 1u) st[k] |= (fin >> 6 & 0x1f80000u) | 8u;
            }
            if (++guard > GUARD) __trap();
            streak++;
        } else streak = 0;
        if (last) {
            uint32_t all = 4u;
#pragma unroll
            for (int k = 0; k < QPW; k++) all &= st[k];
            last = __all_sync(0xffffffffu, all);
        }
        {
            uint32_t t[QPW], u[QPW];
#pragma unroll
            for (int k = 0; k < QPW; k++) { t[k] = st[(k + NBT) % QPW]; u[k] = sq[(k + NBT) % QPW]; }
#pragma unroll
            for (int k = 0; k < QPW; k++) { st[k] = t[k]; sq[k] = u[k]; }
        }
#pragma unroll
        for (int k = 0; k < NBT; k++) load(k);
#pragma unroll
      for (int k = 0; k < NBT; k++) {
        if (nn[k]) {
            const uint32_t* const x = xx[k];
            const uint32_t h0 = hh[k][0], h1 = hh[k][1], d4 = dd[k];
            const bool v = o < nn[k];
            uint32_t old = 0, ta[4], tb[4], w0[4], w1[4];
            atoms_add_keep(old, sb + SM_CNT2 + d4, 0x10001u, q == 0 && v);
#pragma unroll
            for (int j = 0; j < 4; j++) {
                ta[j] = lds32nv(dp2(x[j], 4u, 0u) + (sb + B_TA));
                tb[j] = lds16nv(dp2(x[j], 2u, 0u) + (sb + B_TB));
            }
            old = __shfl_sync(0xffffffffu, old, lane & 28);
            const uint32_t tag = old << 8 & 0x40000000u;
#pragma unroll
            for (int j = 0; j < 4; j++) {
                const uint32_t z = prmt(j & 2 ? h1 : h0, 0, j & 1 ? 0x4342 : 0x4140);
                const uint32_t t23 = prmt((ta[j] & 0x60076007u) * 2050u, tb[j], 0x5341) & 0xfffcffffu;
                w0[j] = (imad(z, 128u, j & 1 ? 0u : tag) & 0x78007800u) | mul_h2_hi(ta[j] & 0x9ff89ff8u, x[j]);
                w1[j] = (imad(z, 2048u, 0u) & 0x78007800u) | mul_h2_hi(t23, x[j]);
            }
            if (CHECK && v && ((tb[0] | tb[1] | tb[2] | tb[3]) & 0x40u)) {
                uint32_t tmp[12];
#pragma unroll
                for (int j = 0; j < 4; j++) {
                    tmp[j] = x[j]; tmp[4 + j] = (j & 2 ? h1 : h0) >> (j & 1 ? 16 : 0); tmp[8 + j] = tb[j];
                    if (tb[j] & 0x40u) { w0[j] &= 0x78007800u; w1[j] &= 0x78007800u; }
                }
                p2_slow(p, sb, tmp, row0, part * H3 + d4 / 4);
            }
            const uint32_t off = (bitsel(old >> 9, old >> 7, 0x0f80u) & 0x4f80u) + imad(d4, WIN / 4, (sel >> (d4 / 4) & 4096u) + po);
            bool wait = old & (0x10000u - NQ2);
            if (!__any_sync(0xffffffffu, wait)) {
                stg_q128(ring_ptr(p, off), w0[0], w1[0], w0[1], w1[1], X_ST2 v);
                stg_q128(ring_ptr(p, off ^ 64u), w0[2], w1[2], w0[3], w1[3], X_ST2 v);
            } else {
                bool pend = v;
                ACC(0, 1)
                for (int g2 = 0;; g2++) {
                    stg_q128(ring_ptr(p, off), w0[0], w1[0], w0[1], w1[1], pend && !wait);
                    stg_q128(ring_ptr(p, off ^ 64u), w0[2], w1[2], w0[3], w1[3], pend && !wait);
                    pend = wait;
                    if (!__any_sync(0xffffffffu, pend)) break;
                    __nanosleep(CFG_BSLEEP);
                    const uint32_t c = lds32v(sb + SM_CNT2 + d4);
                    wait = pend && (((old >> 16) - (c >> 16) + c) & 0xffffu) >= NQ2;
                    if (g2 > GUARD) __trap();
                }
            }
        }
      }
        if (last) break;
    }
    TR(17, w == 0 && lane == 0);
    __syncwarp();
    uint32_t rank = 0;
    if (lane == 0) { __threadfence_block(); rank = atoms_add(sb + SM_FIN, 1u); __threadfence_block(); }
    if (__shfl_sync(0xffffffffu, rank, 0) == P2W - 1 && lane < 16)
        st_rlx(fin2_of(p, sb, part * H3 + lane) + blk, FIN | (((lds32v(sb + SM_CNT2 + lane * 4) >> 16) - NQ2) & 0xffffu));
    __syncwarp();
    mbar_arrive_if(sb + SM_DONE, lane == 0);
    ACC_SAVE
}
__device__ __forceinline__ void role_credit(const Params& p, uint32_t sb, int id, int lane) {
    const uint32_t* const cred = cred2_of(p, sb, id) + (lane & 15);
    uint32_t last = 0;
    for (int guard = 0;; guard++) {
        if (__all_sync(0xffffffffu, mbar_test(sb + SM_DONE, 0))) break;
        const uint32_t c = ld_rlx(cred);
        if (lane < 16 && c != last) reds_add(sb + SM_CNT2 + lane * 4, 0u - ((c - last) & 0xffffu));
        last = c;
        __nanosleep(CFG_CSLEEP);
        if (guard > GUARD) __trap();
    }
}

__device__ __forceinline__ void p3_wrap(uint32_t sb, int id, const uint32_t* tmp) {
    const Scale sc = get_scale(sb);
#pragma unroll 1
    for (int j = 0; j < 8; j++) {
        const uint32_t old = tmp[4 + j], v = tmp[12 + j], nw = old + v, t = (old ^ nw) & (v ^ nw);
        if (t & 0x80008000u) {
            const float k = (t & 0x8000u) ? ((v & 0x8000u) ? -1.0f : 1.0f) : 0.0f;
            const float q = (t & 0x80000000u) ? ((int)v < 0 ? -65536.0f : 65536.0f) : 0.0f;
            const uint32_t e0 = (j & 1) ? sc.eb[2] : sc.eb[0], e1 = (j & 1) ? sc.eb[3] : sc.eb[1];
            const float lo = k * 65536.0f * __uint_as_float((e0 - 10) << 23), hi = (q - k) * __uint_as_float((e1 - 10) << 23);
            if (j & 1) sg_add(tmp[j >> 1] * 32 + id, 0.f, 0.f, lo, hi);
            else sg_add(tmp[j >> 1] * 32 + id, lo, hi, 0.f, 0.f);
        }
    }
}
__device__ __forceinline__ uint32_t p3_val(uint32_t w) {
    const uint32_t mk = prmt(w, 0, 0xBB99);
    return ((w & 0x07ff07ffu) ^ mk) - mk;
}
__device__ __forceinline__ void role_p3(const Params& p, uint32_t sb, int id, int w, int lane) {
    uint32_t* const cred = opaque(cred2_of(p, sb, id / H3 * H2 + w) + id % H3);
    const uint32_t pq = opaque32(p.ring_lo + q2_off(sb, w, id) + lane * 16);
    auto off = [&](uint32_t n) { return (n & 1u) << 11 | (n & 2u) << 13; };
    const uint32_t pp = opaque32(pq - lane * 16 + 2032);
    auto tag_of = [&](uint32_t n) { return ~n << 28; };
    uint32_t n = 0, fin = 0, pr = 0;
    uint4 v[4] = {};
    bool have = false, last = false;
    ACC_DECL
    int guard = 0;
    while (true) {
        const uint32_t ex = tag_of(n);
        const bool ok = have && !__any_sync(0xffffffffu, ((v[0].x ^ ex) | (v[1].x ^ ex) | (v[2].x ^ ex) | (v[3].x ^ ex)) & 0x40000000u);
        if (ok) n++;
        const bool ready = __all_sync(0xffffffffu, (have && !ok) || !((pr ^ tag_of(n)) & 0x40000000u));
        st_rlx_if(cred, n * 16, X_CR2 lane == 0 && ok);
        if (!ok && !ready && __all_sync(0xffffffffu, fin & FIN)) {
            const uint32_t left = __shfl_sync(0xffffffffu, (fin - n * 16) & 0xffffu, 0);
            if (left - 1u > 0x8000u) break;
            if (left < 16u) {
#pragma unroll
                for (int u = 0; u < 4; u++) {
                    v[u] = make_uint4(ex & 0x40000000u, 0, 0, 0);
                    ldq128_keep(v[u], ring_ptr(p, pq + off(n)) + u * 512, u * 4 + (lane >> 3) < left);
                }
                have = last = !__any_sync(0xffffffffu, ((v[0].x ^ ex) | (v[1].x ^ ex) | (v[2].x ^ ex) | (v[3].x ^ ex)) & 0x40000000u);
                pr = ~tag_of(n + have);
                if (++guard > GUARD) __trap();
                continue;
            }
        }
        uint32_t row[8], val[16];
#pragma unroll
        for (int u = 0; u < 4; u++) {
            const uint4 x = v[u];
            row[2 * u] = prmt(bitsel(x.x << 1, x.y >> 3, 0x7000f000u), 0, 0x4431);
            row[2 * u + 1] = prmt(bitsel(x.z << 1, x.w >> 3, 0x7000f000u), 0, 0x4431);
            val[4 * u] = p3_val(x.x); val[4 * u + 1] = p3_val(x.y);
            val[4 * u + 2] = p3_val(x.z); val[4 * u + 3] = p3_val(x.w);
        }
#pragma unroll
        for (int u = 0; u < 4; u++) ldq128_keep(v[u], ring_ptr(p, pq + off(n)) + u * 512, ready);
        pr = ld_rlx((const uint32_t*)ring_ptr(p, pp + off(n + ready)));
        ACC(2, have && !ok)
        have = ready;
        if (!ok) {
            ACC(1, 1)
            fin = ld_rlx(fin2_of(p, sb, id) + w);
            if (++guard > GUARD) __trap();
        } else {
#pragma unroll
            for (int u = 0; u < 4; u += 2) {
                uint32_t old[8], chk = 0;
#pragma unroll
                for (int j = 0; j < 4; j++) {
                    old[2 * j] = atoms_add(sb + C_S + row[2 * u + j] * 4, val[4 * u + 2 * j]);
                    old[2 * j + 1] = atoms_add(sb + C_S + ROWS3_MAX * 4 + row[2 * u + j] * 4, val[4 * u + 2 * j + 1]);
                }
#pragma unroll
                for (int j = 0; j < 8; j++) {
                    const uint32_t nw = old[j] + val[4 * u + j];
                    chk |= (old[j] ^ nw) & (val[4 * u + j] ^ nw);
                }
                if (chk & 0x80008000u) {
                    uint32_t tmp[20];
#pragma unroll
                    for (int j = 0; j < 8; j++) { tmp[j >> 1] = row[2 * u + (j >> 1)]; tmp[4 + j] = old[j]; tmp[12 + j] = val[4 * u + j]; }
                    p3_wrap(sb, id, tmp);
                }
            }
            __syncwarp();
            if (last) break;
        }
    }
    ACC_SAVE
}

__device__ __forceinline__ void row_gates(const float* sw, const uint32_t* c2, uint32_t dbits, float4& gs, float4& gr) {
    const uint32_t d2 = dbits * 0x10001u;
    gs = gr = make_float4(0.f, 0.f, 0.f, 0.f);
#pragma unroll
    for (int r2 = 0; r2 < 4; r2++) {
        uint32_t df = sub_bf2(d2, c2[r2]);
        uint32_t ar = mul_bf2(mul_bf2(df, df), 0xC120C120u);
        uint32_t rb = pack_bf2(__expf(bflo(ar)), __expf(bfhi(ar)));
        const float r0 = bflo(rb), r1 = bfhi(rb);
        const float4 s0 = *(const float4*)(sw + r2 * 8), s1 = *(const float4*)(sw + r2 * 8 + 4);
        const float4 q0 = *(const float4*)(sw + 32 + r2 * 8), q1 = *(const float4*)(sw + 32 + r2 * 8 + 4);
        gs.x += r0 * s0.x + r1 * s1.x; gs.y += r0 * s0.y + r1 * s1.y;
        gs.z += r0 * s0.z + r1 * s1.z; gs.w += r0 * s0.w + r1 * s1.w;
        gr.x += r0 * q0.x + r1 * q1.x; gr.y += r0 * q0.y + r1 * q1.y;
        gr.z += r0 * q0.z + r1 * q1.z; gr.w += r0 * q0.w + r1 * q1.w;
    }
}
__device__ __forceinline__ uint2 finish_row(const float* wu, const float4& gs, const float4& gr, const float S[4], uint2 mrow) {
    const float a[4] = {S[0] * gs.x, S[1] * gs.y, S[2] * gs.z, S[3] * gs.w};
    float u[4] = {0, 0, 0, 0};
#pragma unroll
    for (int k = 0; k < 4; k++) {
        u[0] += a[k] * wu[4 * k]; u[1] += a[k] * wu[4 * k + 1]; u[2] += a[k] * wu[4 * k + 2]; u[3] += a[k] * wu[4 * k + 3];
    }
    return make_uint2(pack_bf2(bflo(mrow.x) + u[0] * gr.x, bfhi(mrow.x) + u[1] * gr.y),
                      pack_bf2(bflo(mrow.y) + u[2] * gr.z, bfhi(mrow.y) + u[3] * gr.w));
}
__device__ __forceinline__ void load_tail_weights(const Params& p, float* sw, int tid) {
    if (tid < 32) sw[tid] = __bfloat162float(p.w_sbf[tid]);
    else if (tid < 64) sw[tid] = __bfloat162float(p.w_rbf[tid - 32]);
    else if (tid < 80) sw[tid] = __bfloat162float(p.w_up[tid - 64]);
    else if (tid < 96) sw[tid] = __bfloat162float(p.w_down[tid - 80]);
}
__device__ __forceinline__ void tail_rows(const Params& p, int tidx, int w, int lane) {
    constexpr uint32_t sb = SB;
    if (w == NW - 1 && lane < 2) {
        fence_gpu();
        red_rlx(rdy_of(p, sb, 320, lane), 1u);
    }
    if (w >= NPC * WPP) return;
    const int pc = w / WPP, r0 = pc * RPC + (tidx * WPP + w - pc * WPP) * 8, e0 = r0 * 32;
    const uint32_t G = sb + T_G + w * 6144;
    {
        const int g = lane >> 2, t = lane & 3;
        uint32_t dv[16];
#pragma unroll
        for (int k = 0; k < 16; k++) dv[k] = __ldg((const uint32_t*)p.dist + min(e0 / 2 + k * 8 + g, p.E / 2 - 1));
        const uint32_t c2 = ((const uint32_t*)p.centers)[t];
        const unsigned short* wg = (const unsigned short*)(g < 4 ? p.w_sbf : p.w_rbf) + t * 8 + (g & 3);
        const uint32_t b = wg[0] | (uint32_t)wg[4] << 16;
#pragma unroll
        for (int k = 0; k < 16; k++) {
            uint32_t a[2];
#pragma unroll
            for (int h = 0; h < 2; h++) {
                const uint32_t df = sub_bf2(prmt(dv[k], 0, h ? 0x3232 : 0x1010), c2);
                const uint32_t ar = mul_bf2(mul_bf2(df, df), 0xC120C120u);
                a[h] = pack_bf2(__expf(bflo(ar)), __expf(bfhi(ar)));
            }
            float d[4];
            asm("mma.sync.aligned.m16n8k8.row.col.f32.bf16.bf16.f32 {%0,%1,%2,%3}, {%4,%5}, {%6}, {%7,%7,%7,%7};"
                : "=f"(d[0]), "=f"(d[1]), "=f"(d[2]), "=f"(d[3]) : "r"(a[0]), "r"(a[1]), "r"(b), "f"(0.f));
            const uint32_t at = G + (((k & 1) * 4 + (k >> 1 & 3)) * 32 + g * 4 + (k >> 3)) * 16 + t * 4;
            sts32(at, pack_bf2(d[0], d[1]));
            sts32(at + 32, pack_bf2(d[2], d[3]));
        }
    }
    __syncwarp();
    auto edge = [&](int k) { return e0 + (lane & 1) * 128 + (lane >> 1) + (k & 3) * 32 + (k >> 2) * 16; };
    {
        uint2 mv[8];
#pragma unroll
        for (int k = 0; k < 8; k++) mv[k] = __ldg(p.m + min(edge(k), p.E - 1));
#pragma unroll
        for (int k = 0; k < 8; k++) sts64(G + 4096 + (k * 32 + lane) * 8, mv[k].x, mv[k].y);
    }
    const Scale sc = get_scale(sb);
    const float lsb[4] = {__uint_as_float((sc.eb[0] - 10) << 23), __uint_as_float((sc.eb[1] - 10) << 23),
                          __uint_as_float((sc.eb[2] - 10) << 23), __uint_as_float((sc.eb[3] - 10) << 23)};
    TR(2, w == 0 && lane == 0);
    uint32_t dirty = 0;
    uint4 sx[2] = {}, sy[2] = {};
#pragma unroll 1
    for (int pass = CFG_DRY ? 0 : 1; pass < 2; pass++) {
        if (pass) {
            if (w == pc * WPP && lane < 2) spin_ge(rdy_of(p, sb, lane ? 320 : 160 + 32 * pc, lds32(sb + SM_MISC + 20)), lane ? NTAIL : N3);
            __syncwarp();
            bar_sync(1 + pc, WPP * 32);
            TR(3, w == 0 && lane == 0);
            TR(10, w == NPC * WPP - 1 && lane == 0);
            if (r0 >= (int)p.rows3) return;
            const uint32_t* const src = &g_S[0][lane >> 1][r0 + (lane & 1) * 4];
#pragma unroll
            for (int u = 0; u < 2; u++) {
                sx[u] = ldg_q128(src + u * 16 * ROWS3_MAX);
                sy[u] = ldg_q128(src + (u * 16 + 32) * ROWS3_MAX);
            }
            if (lane < 8 && (r0 + lane) * 32 < p.E && (dirty = ld_rlx(g_dirty + r0 + lane))) st_rlx(g_dirty + r0 + lane, 0u);
            dirty = __ballot_sync(0xffffffffu, dirty != 0);
        }
        asm volatile("" : "+r"(lane));
        float wu[16];
#pragma unroll
        for (int k = 0; k < 4; k++) *(uint4*)(wu + 4 * k) = lds128(sb + SM_W + 256 + 16 * k);
        auto finish = [&](int k, uint32_t x, uint32_t y, bool extra) {
            const int e = edge(k);
            float S[4];
            const uint32_t tx = x + 0x80008000u, ty = y + 0x80008000u;
            S[0] = (__uint_as_float(prmt(tx, 0x4b000000u, 0x7610)) - 8421376.0f) * lsb[0];
            S[1] = (__uint_as_float(prmt(tx, 0x4b000000u, 0x7632)) - 8421376.0f) * lsb[1];
            S[2] = (__uint_as_float(prmt(ty, 0x4b000000u, 0x7610)) - 8421376.0f) * lsb[2];
            S[3] = (__uint_as_float(prmt(ty, 0x4b000000u, 0x7632)) - 8421376.0f) * lsb[3];
            if (extra && e < p.E) {
                const float4 g = __ldcg(g_Sg + e);
                S[0] += g.x; S[1] += g.y; S[2] += g.z; S[3] += g.w;
                __stcg(g_Sg + e, make_float4(0.f, 0.f, 0.f, 0.f));
            }
            const uint4 g = lds128(G + (k * 32 + lane) * 16);
            const uint2 o = finish_row(wu, make_float4(bflo(g.x), bfhi(g.x), bflo(g.y), bfhi(g.y)), make_float4(bflo(g.z), bfhi(g.z), bflo(g.w), bfhi(g.w)), S,
                                       lds64v(G + 4096 + (k * 32 + lane) * 8));
            asm volatile("{.reg .pred q; setp.ne.u32 q, %3, 0; @q st.global.v2.u32 [%0], {%1,%2};}"
                         ::"l"(p.out + e), "r"(o.x), "r"(o.y), "r"((uint32_t)(pass && e < p.E)));
        };
        const uint32_t xs[8] = {sx[0].x, sx[0].y, sx[0].z, sx[0].w, sx[1].x, sx[1].y, sx[1].z, sx[1].w};
        const uint32_t ys[8] = {sy[0].x, sy[0].y, sy[0].z, sy[0].w, sy[1].x, sy[1].y, sy[1].z, sy[1].w};
        if (!dirty) {
#pragma unroll
            for (int k = 0; k < 8; k++) finish(k, xs[k], ys[k], false);
        } else {
            uint32_t tmp[16];
#pragma unroll
            for (int k = 0; k < 8; k++) { tmp[k] = xs[k]; tmp[8 + k] = ys[k]; }
#pragma unroll 1
            for (int k = 0; k < 8; k++) finish(k, tmp[k], tmp[8 + k], dirty >> ((lane & 1) * 4 + (k & 3)) & 1);
        }
    }
    TR(9, w == 0 && lane == 0);
    TR(11, w == NPC * WPP - 1 && lane == 0);
}

#define CFG_MAP1 1
__global__ void __launch_bounds__(NT, 1) k_main(const __grid_constant__ Params p) {
    extern __shared__ __align__(1024) unsigned char smem[];
    constexpr uint32_t sb = SB;
    if ((uint32_t)__cvta_generic_to_shared(smem) != SB) __trap();
    const int tid = threadIdx.x, w = __shfl_sync(0xffffffffu, tid >> 5, 0), lane = tid & 31;
    if (w < NPROBE) probe(p, sb, w, lane);
    else {
        if (tid == NT - 1) sts32(sb + SM_MISC + 16, ld_rlx(&g_epoch) & 1);
        if (tid >= NT - 32 && lane < 12) sts32(sb + SM_FIN + lane * 4, 0u);
        load_tail_weights(p, (float*)(smem + SM_W), tid - NPROBE * 32);
    }
    const Mat4 wd = load_mat4(p.w_down, lane);
    cta_sync();
    if (w) {
        const uint4 in = __ldg((const uint4*)p.m + (size_t)(tid - 32) * (p.E / 2) / (NT - 32));
        if (tid == 32) {
            const uint32_t n = (p.E / 2 + NCTA - 1) / NCTA, o = blockIdx.x * n;
            if (o < (uint32_t)p.E / 2) asm volatile("cp.async.bulk.prefetch.L2.global [%0], %1;" ::"l"((const uint4*)p.m + o), "r"(min(n, p.E / 2 - o) * 16) : "memory");
        }
        for (int i = SM_ZERO / 16 + tid - 32; i < ZEND / 16; i += NT - 32) ((uint4*)smem)[i] = make_uint4(0, 0, 0, 0);
        if (tid < 48) sts32(sb + SM_CNT2 + (tid - 32) * 4, NQ2 << 16);
        __syncwarp();
        md_stats(in, wd, lane);
    } else assign_role(p, sb, lane);
    if (tid == 0) {
        mbar_init(sb + SM_DONE, lds32(sb + SM_MISC) >> 8 ? P2W : P1W);
    }
    cta_sync();
    const uint32_t rid = __shfl_sync(0xffffffffu, lds32(sb + SM_MISC), 0);
    const int role = rid >> 8, id = rid & 255;
    TR(5, tid == 0);
    if (role == 0) {
        const int ww = CFG_MAP1 == 0 ? ((w & 3) == 3 ? NW : (w >> 2) * 3 + (w & 3)) : CFG_MAP1 == 1 ? (w & 2 ? NW : (w >> 2) * 2 + (w & 1)) : w;
        const int sw = CFG_MAP1 == 0 ? ((w & 3) == 3 ? w >> 2 : NW) : CFG_MAP1 == 1 ? (w & 2 ? (w >> 2) * 2 + (w & 1) : NW) : w - P1W;
        static_assert(CFG_MAP1 == 0 ? (P1W <= NW / 4 * 3 && NF + 2 <= NW / 4) : CFG_MAP1 == 1 ? (P1W <= NW / 2 && NF + 2 <= NW / 2) : true, "warp map");
        for (int i = tid; i < NB; i += NT) sts32(sb + A_CNT + i * 4, 1u << 24);
        cta_sync();
        TR(1, tid == 0);
        if (ww < P1W) role_p1(p, sb, id, ww, lane);
        else if (sw < NF) role_flush(p, sb, id, sw, lane);
        else if (w == NW - 1) {
            uint4* owin = (uint4*)(p.ring + (CWIN + (lds32(sb + SM_MISC + 16) ^ 1)) * WIN);
            for (int i = id * 32 + lane; i < CPAIRS * 512; i += N1 * 32) __stcg(owin + i, make_uint4(0, 0, 0, 0));
            __syncwarp();
        }
        cta_sync();
        tail_rows(p, id, w, lane);
    } else if (role == 1) {
        const int row0 = id % H2 * p.rows2;
        const int nrows = min((int)p.rows2, p.E - row0);
        constexpr int NTB = NT - 32, TBD = CFG_TBD;
        bool flagged = false;
        if (w < NW - 1) {
            const Scale sc = get_scale(sb);
            const float ts[4] = {__uint_as_float((246u - sc.eb[0]) << 23), __uint_as_float((246u - sc.eb[1]) << 23),
                                 __uint_as_float((246u - sc.eb[2]) << 23), __uint_as_float((246u - sc.eb[3]) << 23)};
            const uint4* const src = (const uint4*)(p.m + row0);
            uint4 r2[TBD], nx[TBD];
            auto fetch = [&](int i) {
#pragma unroll
                for (int k = 0; k < TBD; k++)
                    asm volatile("ld.global.nc.v4.u32 {%0,%1,%2,%3}, [%4];" : "=r"(nx[k].x), "=r"(nx[k].y), "=r"(nx[k].z), "=r"(nx[k].w) : "l"(src + min(i + k * NTB, nrows / 2 - 1)));
            };
            fetch(tid);
#pragma unroll 1
            for (int i0 = tid; 2 * (i0 - lane) < nrows; i0 += TBD * NTB) {
#pragma unroll
                for (int k = 0; k < TBD; k++) r2[k] = make_uint4(nx[k].x, nx[k].z, nx[k].y, nx[k].w);
                fetch(i0 + TBD * NTB);
#pragma unroll
                for (int k = 0; k < TBD; k++) {
                    const int i = i0 + k * NTB;
                    float y[8];
                    mul4(make_uint4(r2[k].x, r2[k].z, r2[k].y, r2[k].w), wd, y);
                    uint32_t ta[2], tb[2];
#pragma unroll
                    for (int h = 0; h < 2; h++) {
                        const uint32_t a01 = pack_h2(y[4 * h] * ts[0], y[4 * h + 1] * ts[1]), h01 = a01 + 0x00040004u;
                        const uint32_t a23 = pack_h2(y[4 * h + 2] * ts[2], y[4 * h + 3] * ts[3]), h23 = a23 + 0x00040004u;
                        ta[h] = (h01 & 0x9ff89ff8u) | ((h23 >> 3) & 0x00070007u) | ((h23 << 7) & 0x60006000u);
                        tb[h] = prmt(h23, 0, 0x4431);
                        if (((a01 | a23 | h01 | h23) & 0x60006000u) || sc.allslow) { ta[h] = 0; tb[h] = 0x40u; flagged = true; }
                    }
                    sts64_if(sb + B_TA + i * 8, ta[0], ta[1], 2 * i < nrows);
                    sts32_if(sb + B_TB + i * 4, prmt(tb[0], tb[1], 0x5410), 2 * i < nrows);
                }
            }
            if (tid == 0) {
                sts32(sb + B_TA + p.rows2 * 4, 0u);
                sts16(sb + B_TB + p.rows2 * 2, 0u);
            }
            TR(8, tid == 0);
        } else if (lane == 0) spin_ge(rdy_of(p, sb, id, id / H2), H3);
        __syncwarp();
        flagged = __any_sync(0xffffffffu, __syncthreads_or(flagged));
        TR(1, tid == 0);
        if (w < P2W) {
            if (flagged) role_p2<true>(p, sb, id, w, lane);
            else role_p2<false>(p, sb, id, w, lane);
        } else if (w == P2W) role_credit(p, sb, id, lane);
        cta_sync();
        TR(18, tid == 0);
        if (w == NW - 2) clear_queues<true>(p, sb, id, lane);
        tail_rows(p, N1 + id, w, lane);
    } else {
        if (w == 0) clear_queues<false>(p, sb, id, lane);
        if (tid >= 32 && tid < 33 + NPC) mbar_init(sb + SM_CNT2 + (tid - 32) * 8, 1);
        cta_sync();
        TR(1, tid == 0);
        if (w < P3W) role_p3(p, sb, id, w, lane);
        cta_sync();
        TR(2, tid == 0);
        if (w < NPC && lane == 0) {
            fence_async_smem();
            const int n = min(((int)p.rows3 + 7) / 8 * 8 - w * RPC, RPC);
            if (w) mbar_wait(sb + SM_CNT2 + w * 8, 0);
            if (n > 0) {
                bulk_store(g_S[0][id] + w * RPC, sb + C_S + w * RPC * 4, n * 4);
                bulk_store(g_S[1][id] + w * RPC, sb + C_S + (ROWS3_MAX + w * RPC) * 4, n * 4);
            }
            asm volatile("cp.async.bulk.commit_group;" ::: "memory");
            asm volatile("cp.async.bulk.wait_group.read 0;" ::: "memory");
            mbar_arrive(sb + SM_CNT2 + w * 8 + 8);
            asm volatile("cp.async.bulk.wait_group 0;" ::: "memory");
            fence_gpu();
            red_rlx(rdy_of(p, sb, 160 + 32 * w, 0), 1u);
            red_rlx(rdy_of(p, sb, 160 + 32 * w, 1), 1u);
            if (id == 0 && w == 0) red_rlx(&g_epoch, 1u);
            TR(12 + w, true);
        }
    }
    TR(4, tid == 0);
}

__global__ void k_direct(const Params p, long long T) {
    float wd[16];
#pragma unroll
    for (int i = 0; i < 16; i++) wd[i] = __bfloat162float(p.w_down[i]);
    const float f = __bfloat162float(p.freq[0]);
    for (long long t = blockIdx.x * (long long)blockDim.x + threadIdx.x; t < T; t += (long long)gridDim.x * blockDim.x) {
        float x = __bfloat162float(__float2bfloat16(f * __bfloat162float(p.angle[t])));
        float c = __bfloat162float(__float2bfloat16(cosf(x)));
        uint2 md = down_row(__ldg(p.m + p.idx_in[t]), wd);
        red_v4(g_Sg + p.idx_out[t], c * bflo(md.x), c * bfhi(md.x), c * bflo(md.y), c * bfhi(md.y));
    }
}
__global__ void k_direct_tail(const Params p) {
    __shared__ __align__(16) float sw[96];
    load_tail_weights(p, sw, threadIdx.x);
    __syncthreads();
    uint32_t c2[4];
#pragma unroll
    for (int i = 0; i < 4; i++) c2[i] = ((const uint32_t*)p.centers)[i];
    for (int e = blockIdx.x * blockDim.x + threadIdx.x; e < p.E; e += gridDim.x * blockDim.x) {
        float4 g = __ldcg(g_Sg + e);
        __stcg(g_Sg + e, make_float4(0.f, 0.f, 0.f, 0.f));
        const float Sv[4] = {g.x, g.y, g.z, g.w};
        float4 gs, gr;
        row_gates(sw, c2, __bfloat16_as_ushort(p.dist[e]), gs, gr);
        p.out[e] = finish_row(sw + 64, gs, gr, Sv, __ldg(p.m + e));
    }
}

static bool pick_rows(int E, int n, int rows_max, int mult, uint32_t* rows, uint32_t* magic) {
    for (uint32_t r = (E + n - 1) / n; r <= (uint32_t)rows_max; r++) {
        if (r < 2 || r % mult) continue;
        uint64_t mg = ((1ull << 32) + r - 1) / r;
        uint64_t err = mg * r - (1ull << 32);
        if (err * (uint64_t)n < mg) { *rows = r; *magic = (uint32_t)mg; return true; }
    }
    return false;
}

}

extern "C" void kernel_launch(void* const* d_in, const int* in_sizes, int n_in, void* d_out, int out_size) {
    using namespace gs;
    (void)n_in; (void)out_size;
    Params p;
    p.m = (const uint2*)d_in[0];
    p.idx_in = (const int*)d_in[1];
    p.idx_out = (const int*)d_in[2];
    p.dist = (const __nv_bfloat16*)d_in[3];
    p.angle = (const __nv_bfloat16*)d_in[4];
    p.centers = (const __nv_bfloat16*)d_in[5];
    p.freq = (const __nv_bfloat16*)d_in[6];
    p.w_rbf = (const __nv_bfloat16*)d_in[7];
    p.w_sbf = (const __nv_bfloat16*)d_in[8];
    p.w_down = (const __nv_bfloat16*)d_in[9];
    p.w_up = (const __nv_bfloat16*)d_in[10];
    p.out = (uint2*)d_out;
    p.E = in_sizes[3];
    const long long T = in_sizes[1];
    p.n4 = (int)(T / 4);
    p.rows2 = p.magic2 = 0;
    p.ring = nullptr;

    static int sms = 0, rsv = 0;
    if (!sms) {
        int dev = 0;
        cudaGetDevice(&dev);
        cudaDeviceGetAttribute(&rsv, cudaDevAttrReservedSharedMemoryPerBlock, dev);
        cudaDeviceGetAttribute(&sms, cudaDevAttrMultiProcessorCount, dev);
        cudaFuncSetAttribute(k_main, cudaFuncAttributeMaxDynamicSharedMemorySize, SMEM_BYTES);
    }
    cudaStream_t st = cudaStreamPerThread;
    bool fast = (T % 4 == 0) && T > 0 && sms >= NCTA && rsv == (int)SB && p.E >= 65536 && p.E <= E_MAX &&
                p.E % 4 == 0 && (((uintptr_t)p.m | (uintptr_t)p.idx_in | (uintptr_t)p.idx_out | (uintptr_t)p.angle) & 15) == 0 &&
                pick_rows(p.E, NI, ROWS2_MAX, 2, &p.rows2, &p.magic2);
    p.c1 = 1;
    p.nrows2 = 0u - p.rows2;
    p.rows3 = (p.E + 31) / 32;
    fast = fast && (p.rows2 * (NI - 1) + 2 <= (uint32_t)p.E);
    static const void* tkey[3] = {nullptr, nullptr, nullptr};
    static cudaTextureObject_t tex[3] = {0, 0, 0};
    static long long tlen = -1;
    const void* tptr[3] = {p.idx_in, p.idx_out, p.angle};
    for (int k = 0; fast && k < 3; k++) {
        if (tkey[k] == tptr[k] && tlen == T) continue;
        if (tkey[k]) cudaDestroyTextureObject(tex[k]);
        tkey[k] = nullptr;
        cudaResourceDesc rd = {};
        rd.resType = cudaResourceTypeLinear;
        rd.res.linear.devPtr = (void*)tptr[k];
        rd.res.linear.desc = cudaCreateChannelDesc(32, 32, k < 2 ? 32 : 0, k < 2 ? 32 : 0, cudaChannelFormatKindUnsigned);
        rd.res.linear.sizeInBytes = (size_t)T * (k < 2 ? 4 : 2);
        cudaTextureDesc td = {};
        td.readMode = cudaReadModeElementType;
        if (cudaCreateTextureObject(&tex[k], &rd, &td, nullptr) == cudaSuccess) tkey[k] = tptr[k];
        else { (void)cudaGetLastError(); fast = false; }
    }
    if (fast) tlen = T;
    p.t_in = tex[0]; p.t_out = tex[1]; p.t_ang = tex[2];
    if (fast) {
        void* ring = nullptr;
        cudaGetSymbolAddress(&ring, g_ring);
        uintptr_t a = ((uintptr_t)ring + WIN - 1) & ~(uintptr_t)(WIN - 1);
        if (a >> 32 != (a + RING_BYTES - 1) >> 32) a += RING_BYTES;
        p.ring = (unsigned char*)a;
        p.ring_lo = (uint32_t)a;
        p.ring_hi = (uint32_t)(a >> 32);
        k_main<<<NCTA, NT, SMEM_BYTES, st>>>(p);
    } else {
        k_direct<<<sms * 8, 256, 0, st>>>(p, T);
        k_direct_tail<<<sms * 4, 256, 0, st>>>(p);
    }
}
```

```cpp
#include <cuda_runtime.h>
#include <cuda_bf16.h>
#include <stdint.h>

#define CFG_N1 56
#define CFG_NI 22
#define CFG_NW 28
#define CFG_P1W 14
#define CFG_GPW 2
#define CFG_KR 1
#define CFG_SMPAD 0
#define CFG_QPW 3
#define CFG_TG 2
#define CFG_PMASK 8
#define CFG_PSTREAK 1
#define CFG_NBT 1
#define CFG_SKEY 7
#define CFG_TBD 4
#define CFG_P0 500
#define CFG_NTK 16
#define CFG_PFD 200
#define CFG_CRE 0
#define CFG_TH 10
#define CFG_TS 300
#define CFG_POLL 64
#define CFG_HINT 20000
#define CFG_BSLEEP 100
#define CFG_CSLEEP 200
#define CFG_FSLEEP 100
#define CFG_PSLEEP 100
#define CFG_DRY 1
#define CFG_PROBES 4

namespace gs {

constexpr int E_MAX = 640000;
constexpr int N1 = CFG_N1, NI = CFG_NI, N2 = 2 * NI, N3 = 32, NCTA = N1 + N2 + N3;
constexpr int H2 = NI, H3 = N3 / 2;
constexpr int NB = NI * N3;
constexpr int NW = CFG_NW, NT = NW * 32;
constexpr int GPW = CFG_GPW, NF = NI / GPW;
constexpr int QPW = CFG_QPW, NBT = CFG_NBT;
constexpr int P1W = CFG_P1W, P2W = (N1 + QPW - 1) / QPW, P3W = NI;
constexpr int NQ1 = 32, NQ2 = 64;
constexpr int ROWS2_MAX = ((E_MAX + NI - 1) / NI + 31) / 8 * 8;
constexpr int ROWS3_MAX = (E_MAX / 32 + 31) / 32 * 32;
constexpr int NTAIL = N1 + N2;
constexpr int NPC = 5, WPP = 5, RPC = NTAIL * WPP * 8;
constexpr int GUARD = 1 << 26;
static_assert(NCTA % 4 == 0 && NCTA <= 192, "roles come in CTA pairs, per partition");
static_assert(NI % GPW == 0 && (GPW == 2 || GPW == 4) && QPW >= NBT && QPW <= 4 && NI <= 32 && N1 <= 62, "queue ownership");
static_assert(P1W + NF + 2 <= NW && P2W + 2 <= NW && P3W + 1 <= NW && P1W * 256 + 64 < 8192, "warp roles");
static_assert(ROWS2_MAX + 8 <= 32768 && ROWS3_MAX <= 32768, "index bits");

constexpr uint32_t SB = 1024;
constexpr int SM_DONE = 0;
constexpr int SM_MISC = 16;
constexpr int SM_FIN = 48;
constexpr int SM_STAT = 64;
constexpr int SM_CNT2 = 128;
constexpr int SM_W = 256;
constexpr int SM_PUB = SM_W + 384;
constexpr int SM_PROBE = SM_PUB + 768;
constexpr int SM_DATA = 2048;
constexpr int cmax(int a, int b) { return a > b ? a : b; }
constexpr int A_CNT = SM_DATA;
constexpr int A_LIST = A_CNT + NB * 4;
constexpr int KR = CFG_KR, LISTH = (GPW * 16 + 4 * KR + 31) / 32 * 128 + 16, LISTB = 2 * LISTH;
constexpr int A_ST = (A_LIST + NF * LISTB + 127) / 128 * 128;
constexpr int A_END = A_ST + NB * 256;
constexpr int B_TA = SM_DATA;
constexpr int B_TB = B_TA + (ROWS2_MAX + 8) * 4;
constexpr int B_END = B_TB + (ROWS2_MAX + 8) * 2;
constexpr int C_S = SM_DATA;
constexpr int C_END = C_S + ROWS3_MAX * 8;
constexpr int T_G = SM_DATA, T_END = T_G + NPC * WPP * 6144;
constexpr int ZEND = cmax(A_END, C_END);
constexpr int SM_ZERO = (cmax(cmax(A_END, B_END), cmax(C_END, T_END)) + 127) / 128 * 128;
constexpr int SMEM_BYTES = SM_ZERO + 4096 + CFG_SMPAD;
static_assert(SMEM_BYTES <= 232448 && SM_PROBE + 128 <= SM_DATA, "shared memory");
static_assert(NPC * RPC >= ROWS3_MAX && NPC * WPP + 2 <= NW, "tail");

constexpr uint32_t FIN = 0x80000000u;

constexpr uint32_t WIN = 524288;
constexpr int CWIN = N2 + N3, NWIN = CWIN + 2, CPAIRS = 31;
constexpr uint32_t PROBE_OFF = (uint32_t)NWIN * WIN;
constexpr int NPROBE = 16;
static_assert(NWIN <= NCTA && NPROBE <= NW, "windows");
constexpr size_t RING_BYTES = (size_t)PROBE_OFF + WIN;
__device__ __align__(128) unsigned char g_ring[2 * RING_BYTES + WIN];
__device__ __align__(128) uint32_t g_S[2][32][ROWS3_MAX];
__device__ __align__(128) float4 g_Sg[E_MAX];
__device__ uint32_t g_dirty[E_MAX / 32];
__device__ uint32_t g_epoch;

#define TR(ev, on)
#define ACC_DECL
#define ACC(i, n)
#define ACC_SAVE

struct Params {
    const uint2* m;
    const int* idx_in;
    const int* idx_out;
    const __nv_bfloat16* dist;
    const __nv_bfloat16* angle;
    const __nv_bfloat16* centers;
    const __nv_bfloat16* freq;
    const __nv_bfloat16* w_rbf;
    const __nv_bfloat16* w_sbf;
    const __nv_bfloat16* w_down;
    const __nv_bfloat16* w_up;
    uint2* out;
    unsigned char* ring;
    cudaTextureObject_t t_in, t_out, t_ang;
    int E, n4;
    uint32_t rows2, nrows2, magic2, rows3;
    uint32_t ring_lo, ring_hi, c1;
};

__device__ __forceinline__ float bflo(uint32_t w) { return __uint_as_float(w << 16); }
__device__ __forceinline__ float bfhi(uint32_t w) { return __uint_as_float(w & 0xffff0000u); }
__device__ __forceinline__ uint32_t pack_bf2(float lo, float hi) {
    uint32_t r;
    asm("cvt.rn.bf16x2.f32 %0, %1, %2;" : "=r"(r) : "f"(hi), "f"(lo));
    return r;
}
__device__ __forceinline__ uint32_t mul_bf2(uint32_t a, uint32_t b) {
    uint32_t r;
    asm("mul.rn.bf16x2 %0, %1, %2;" : "=r"(r) : "r"(a), "r"(b));
    return r;
}
__device__ __forceinline__ uint32_t sub_bf2(uint32_t a, uint32_t b) {
    uint32_t r;
    asm("sub.rn.bf16x2 %0, %1, %2;" : "=r"(r) : "r"(a), "r"(b));
    return r;
}
__device__ __forceinline__ uint32_t maxabs_bf2(uint32_t a, uint32_t b) {
    uint32_t r;
    asm("max.NaN.xorsign.abs.bf16x2 %0, %1, %2;" : "=r"(r) : "r"(a), "r"(b));
    return r;
}
__device__ __forceinline__ void mbar_init(uint32_t a, uint32_t n) {
    asm volatile("mbarrier.init.shared::cta.b64 [%0], %1;" ::"r"(a), "r"(n) : "memory");
}
__device__ __forceinline__ void mbar_arrive(uint32_t a) {
    asm volatile("mbarrier.arrive.shared::cta.b64 _, [%0];" ::"r"(a) : "memory");
}
__device__ __forceinline__ void mbar_arrive_n(uint32_t a, uint32_t n) {
    asm volatile("mbarrier.arrive.shared::cta.b64 _, [%0], %1;" ::"r"(a), "r"(n) : "memory");
}
__device__ __forceinline__ void mbar_arrive_if(uint32_t a, bool on) {
    asm volatile("{.reg .pred q; setp.ne.u32 q, %1, 0; @q mbarrier.arrive.shared::cta.b64 _, [%0];}" ::"r"(a), "r"((uint32_t)on) : "memory");
}
__device__ __forceinline__ void mbar_wait(uint32_t a, uint32_t parity) {
    uint32_t ok;
    int guard = 0;
    do {
        asm volatile("{.reg .pred p; mbarrier.try_wait.parity.shared::cta.b64 p, [%1], %2, %3; selp.u32 %0, 1, 0, p;}"
                     : "=r"(ok) : "r"(a), "r"(parity), "r"(CFG_HINT) : "memory");
        if (!ok) {
            if (++guard > GUARD) __trap();
        }
    } while (!ok);
}
__device__ __forceinline__ void cta_sync() { __syncwarp(); __syncthreads(); }
__device__ __forceinline__ void bar_sync(int id, int n) { asm volatile("bar.sync %0, %1;" ::"r"(id), "r"(n) : "memory"); }
__device__ __forceinline__ void bar_arrive(int id, int n) { asm volatile("bar.arrive %0, %1;" ::"r"(id), "r"(n) : "memory"); }
__device__ __forceinline__ bool mbar_test(uint32_t a, uint32_t parity) {
    uint32_t ok;
    asm volatile("{.reg .pred p; mbarrier.test_wait.parity.shared::cta.b64 p, [%1], %2; selp.u32 %0, 1, 0, p;}"
                 : "=r"(ok) : "r"(a), "r"(parity) : "memory");
    return ok;
}
__device__ __forceinline__ uint32_t ld_acq(const uint32_t* p) {
    uint32_t v;
    asm volatile("ld.acquire.gpu.global.u32 %0, [%1];" : "=r"(v) : "l"(p) : "memory");
    return v;
}
__device__ __forceinline__ uint32_t ld_rlx(const uint32_t* p) {
    uint32_t v;
    asm volatile("ld.relaxed.gpu.global.u32 %0, [%1];" : "=r"(v) : "l"(p) : "memory");
    return v;
}
__device__ __forceinline__ void st_rlx(uint32_t* p, uint32_t v) {
    asm volatile("st.relaxed.gpu.global.u32 [%0], %1;" ::"l"(p), "r"(v) : "memory");
}
__device__ __forceinline__ void red_rlx(uint32_t* p, uint32_t v) {
    asm volatile("red.relaxed.gpu.global.add.u32 [%0], %1;" ::"l"(p), "r"(v) : "memory");
}
__device__ __forceinline__ bool elect_one() {
    uint32_t p;
    asm volatile("{.reg .pred P; elect.sync _|P, 0xffffffff; selp.u32 %0, 1, 0, P;}" : "=r"(p));
    return p;
}
__device__ __forceinline__ uint32_t spin_ge(const uint32_t* p, uint32_t target) {
    int guard = 0;
    while (ld_rlx(p) < target) {
        __nanosleep(CFG_POLL);
        if (++guard > GUARD) __trap();
    }
    return ld_acq(p);
}
__device__ __forceinline__ void fence_gpu() { asm volatile("fence.acq_rel.gpu;" ::: "memory"); }
__device__ __forceinline__ void fence_async_smem() { asm volatile("fence.proxy.async.shared::cta;" ::: "memory"); }
__device__ __forceinline__ void fence_async_all() { asm volatile("fence.proxy.async;" ::: "memory"); }
__device__ __forceinline__ void bulk_store(void* g, uint32_t s, uint32_t bytes) {
    asm volatile("cp.async.bulk.global.shared::cta.bulk_group [%0], [%1], %2;" ::"l"(g), "r"(s), "r"(bytes) : "memory");
}
__device__ __forceinline__ void cp16(uint32_t s, const void* g, bool on) {
    asm volatile("{.reg .pred q; setp.ne.u32 q, %2, 0; @q cp.async.cg.shared.global [%0], [%1], 16;}" ::"r"(s), "l"(g), "r"((uint32_t)on) : "memory");
}
__device__ __forceinline__ void cp_commit() { asm volatile("cp.async.commit_group;" ::: "memory"); }
template <int N> __device__ __forceinline__ void cp_wait() { asm volatile("cp.async.wait_group %0;" ::"n"(N) : "memory"); }
__device__ __forceinline__ uint32_t atoms_add(uint32_t a, uint32_t v) {
    uint32_t o;
    asm volatile("atom.shared.add.u32 %0, [%1], %2;" : "=r"(o) : "r"(a), "r"(v) : "memory");
    return o;
}
__device__ __forceinline__ void sts32(uint32_t a, uint32_t v) { asm volatile("st.shared.u32 [%0], %1;" ::"r"(a), "r"(v) : "memory"); }
__device__ __forceinline__ void sts16(uint32_t a, uint32_t v) { asm volatile("st.shared.u16 [%0], %1;" ::"r"(a), "h"((uint16_t)v) : "memory"); }
__device__ __forceinline__ void sts64(uint32_t a, uint32_t x, uint32_t y) { asm volatile("st.shared.v2.u32 [%0], {%1,%2};" ::"r"(a), "r"(x), "r"(y) : "memory"); }
__device__ __forceinline__ uint32_t lds32(uint32_t a) {
    uint32_t v;
    asm volatile("ld.shared.u32 %0, [%1];" : "=r"(v) : "r"(a) : "memory");
    return v;
}
__device__ __forceinline__ uint2 lds64(uint32_t a) {
    uint2 v;
    asm volatile("ld.shared.v2.u32 {%0,%1}, [%2];" : "=r"(v.x), "=r"(v.y) : "r"(a));
    return v;
}
__device__ __forceinline__ uint2 lds64v(uint32_t a) {
    uint2 v;
    asm volatile("ld.volatile.shared.v2.u32 {%0,%1}, [%2];" : "=r"(v.x), "=r"(v.y) : "r"(a) : "memory");
    return v;
}
__device__ __forceinline__ uint32_t lds32v(uint32_t a) {
    uint32_t v;
    asm volatile("ld.volatile.shared.u32 %0, [%1];" : "=r"(v) : "r"(a) : "memory");
    return v;
}
__device__ __forceinline__ uint4 lds128(uint32_t a) {
    uint4 v;
    asm volatile("ld.shared.v4.u32 {%0,%1,%2,%3}, [%4];" : "=r"(v.x), "=r"(v.y), "=r"(v.z), "=r"(v.w) : "r"(a) : "memory");
    return v;
}
__device__ __forceinline__ void sts128(uint32_t a, uint4 v) {
    asm volatile("st.shared.v4.u32 [%0], {%1,%2,%3,%4};" ::"r"(a), "r"(v.x), "r"(v.y), "r"(v.z), "r"(v.w) : "memory");
}
#define LD_Q "ld.relaxed.gpu.global"
__device__ __forceinline__ uint4 ldg_q128(const void* p) {
    uint4 v;
    asm volatile(LD_Q ".v4.u32 {%0,%1,%2,%3}, [%4];"
                 : "=r"(v.x), "=r"(v.y), "=r"(v.z), "=r"(v.w) : "l"(p) : "memory");
    return v;
}
__device__ __forceinline__ uint2 ldg_q64(const void* p) {
    uint2 v;
    asm volatile(LD_Q ".v2.u32 {%0,%1}, [%2];" : "=r"(v.x), "=r"(v.y) : "l"(p) : "memory");
    return v;
}
__device__ __forceinline__ void red_v4(float4* p, float a, float b, float c, float d) {
    asm volatile("red.global.add.v4.f32 [%0], {%1,%2,%3,%4};" ::"l"(p), "f"(a), "f"(b), "f"(c), "f"(d) : "memory");
}
__device__ __forceinline__ uint2 down_row(uint2 r, const float* wd) {
    float x0 = bflo(r.x), x1 = bfhi(r.x), x2 = bflo(r.y), x3 = bfhi(r.y);
    float y[4];
#pragma unroll
    for (int j = 0; j < 4; j++) y[j] = x0 * wd[j] + x1 * wd[4 + j] + x2 * wd[8 + j] + x3 * wd[12 + j];
    return make_uint2(pack_bf2(y[0], y[1]), pack_bf2(y[2], y[3]));
}
__device__ __forceinline__ uint32_t prmt(uint32_t a, uint32_t b, uint32_t s) {
    uint32_t r;
    asm("prmt.b32 %0, %1, %2, %3;" : "=r"(r) : "r"(a), "r"(b), "r"(s));
    return r;
}
__device__ __forceinline__ uint32_t bitsel(uint32_t a, uint32_t b, uint32_t m) {
    uint32_t r;
    asm("lop3.b32 %0, %1, %2, %3, 0xE4;" : "=r"(r) : "r"(a), "r"(b), "r"(m));
    return r;
}
__device__ __forceinline__ uint32_t pack_h2(float lo, float hi) {
    uint32_t r;
    asm("cvt.rn.f16x2.f32 %0, %1, %2;" : "=r"(r) : "f"(hi), "f"(lo));
    return r;
}
__device__ __forceinline__ uint32_t mul_h2(uint32_t a, uint32_t b) {
    uint32_t r;
    asm("mul.rn.f16x2 %0, %1, %2;" : "=r"(r) : "r"(a), "r"(b));
    return r;
}
__device__ __forceinline__ uint32_t lds32nv(uint32_t a) {
    uint32_t v;
    asm volatile("ld.shared.u32 %0, [%1];" : "=r"(v) : "r"(a));
    return v;
}
__device__ __forceinline__ uint32_t lds16nv(uint32_t a) {
    uint32_t v;
    asm volatile("ld.shared.u16 %0, [%1];" : "=r"(v) : "r"(a));
    return v;
}
#define X_CR1
#define X_CR2
#define X_ST1
#define X_ST2
#define ST_Q "st.relaxed.gpu.global"
__device__ __forceinline__ void stg_q128(void* p, uint32_t a, uint32_t b, uint32_t c, uint32_t d, bool on) {
    asm volatile("{.reg .pred q; setp.ne.u32 q, %5, 0; @q " ST_Q ".v4.u32 [%0], {%1,%2,%3,%4};}"
                 ::"l"(p), "r"(a), "r"(b), "r"(c), "r"(d), "r"((uint32_t)on) : "memory");
}
__device__ __forceinline__ void stg_q64(void* p, uint32_t a, uint32_t b, bool on) {
    asm volatile("{.reg .pred q; setp.ne.u32 q, %3, 0; @q " ST_Q ".v2.u32 [%0], {%1,%2};}"
                 ::"l"(p), "r"(a), "r"(b), "r"((uint32_t)on) : "memory");
}
__device__ __forceinline__ void st_rlx_if(uint32_t* p, uint32_t v, bool on) {
    asm volatile("{.reg .pred q; setp.ne.u32 q, %2, 0; @q st.relaxed.gpu.global.u32 [%0], %1;}" ::"l"(p), "r"(v), "r"((uint32_t)on) : "memory");
}
__device__ __forceinline__ uint32_t ld_rlx_if(const uint32_t* p, bool on) {
    uint32_t v;
    asm volatile("{.reg .pred q; setp.ne.u32 q, %2, 0; mov.b32 %0, 0; @q ld.relaxed.gpu.global.u32 %0, [%1];}" : "=&r"(v) : "l"(p), "r"((uint32_t)on) : "memory");
    return v;
}
__device__ __forceinline__ void ldq128_keep(uint4& v, const void* p, bool on) {
    asm volatile("{.reg .pred q; setp.ne.u32 q, %5, 0; @q ld.relaxed.gpu.global.v4.u32 {%0,%1,%2,%3}, [%4];}"
                 : "+r"(v.x), "+r"(v.y), "+r"(v.z), "+r"(v.w) : "l"(p), "r"((uint32_t)on) : "memory");
}
__device__ __forceinline__ void ldq64_keep(uint2& v, const void* p, bool on) {
    asm volatile("{.reg .pred q; setp.ne.u32 q, %3, 0; @q ld.relaxed.gpu.global.v2.u32 {%0,%1}, [%2];}"
                 : "+r"(v.x), "+r"(v.y) : "l"(p), "r"((uint32_t)on) : "memory");
}
__device__ __forceinline__ void atoms_add_keep(uint32_t& o, uint32_t a, uint32_t v, bool on) {
    asm volatile("{.reg .pred q; setp.ne.u32 q, %3, 0; @q atom.shared.add.u32 %0, [%1], %2;}" : "+r"(o) : "r"(a), "r"(v), "r"((uint32_t)on) : "memory");
}
__device__ __forceinline__ void reds_add(uint32_t a, uint32_t v) { asm volatile("red.shared.add.u32 [%0], %1;" ::"r"(a), "r"(v) : "memory"); }
__device__ __forceinline__ void sts32_if(uint32_t a, uint32_t v, bool on) {
    asm volatile("{.reg .pred q; setp.ne.u32 q, %2, 0; @q st.shared.u32 [%0], %1;}" ::"r"(a), "r"(v), "r"((uint32_t)on) : "memory");
}
__device__ __forceinline__ void sts64_if(uint32_t a, uint32_t x, uint32_t y, bool on) {
    asm volatile("{.reg .pred q; setp.ne.u32 q, %3, 0; @q st.shared.v2.u32 [%0], {%1,%2};}" ::"r"(a), "r"(x), "r"(y), "r"((uint32_t)on) : "memory");
}
__device__ __forceinline__ void lds128_keep(uint4& v, uint32_t a, bool on) {
    asm volatile("{.reg .pred q; setp.ne.u32 q, %5, 0; @q ld.volatile.shared.v4.u32 {%0,%1,%2,%3}, [%4];}"
                 : "+r"(v.x), "+r"(v.y), "+r"(v.z), "+r"(v.w) : "r"(a), "r"((uint32_t)on) : "memory");
}
__device__ __forceinline__ void or3_if(uint32_t& x, uint32_t a, uint32_t b, bool on) {
    asm("{.reg .pred q; setp.ne.u32 q, %3, 0; @q lop3.b32 %0, %0, %1, %2, 0xfe;}" : "+r"(x) : "r"(a), "r"(b), "r"((uint32_t)on));
}
__device__ __forceinline__ uint32_t clk() {
    uint32_t t;
    asm volatile("mov.u32 %0, %%clock;" : "=r"(t) :: "memory");
    return t;
}
__device__ __forceinline__ void sg_add(int row, float a, float b, float c, float d) {
    red_v4(g_Sg + row, a, b, c, d);
    st_rlx(g_dirty + (row >> 5), 1u);
}
__device__ __forceinline__ void slow_add(const uint2* m, uint32_t sb, int in, int out, float c) {
    const uint2 r = __ldg(m + in);
    const float x[4] = {bflo(r.x), bfhi(r.x), bflo(r.y), bfhi(r.y)};
    float y[4] = {0.f, 0.f, 0.f, 0.f};
#pragma unroll
    for (int k = 0; k < 4; k++) {
        const uint4 q = lds128(sb + SM_W + 320 + k * 16);
        y[0] = k ? y[0] + x[k] * __uint_as_float(q.x) : x[k] * __uint_as_float(q.x);
        y[1] = k ? y[1] + x[k] * __uint_as_float(q.y) : x[k] * __uint_as_float(q.y);
        y[2] = k ? y[2] + x[k] * __uint_as_float(q.z) : x[k] * __uint_as_float(q.z);
        y[3] = k ? y[3] + x[k] * __uint_as_float(q.w) : x[k] * __uint_as_float(q.w);
    }
    const uint32_t lo = pack_bf2(y[0], y[1]), hi = pack_bf2(y[2], y[3]);
    sg_add(out, c * bflo(lo), c * bfhi(lo), c * bflo(hi), c * bfhi(hi));
}

struct Mat4 { uint32_t b[4]; };
__device__ __forceinline__ Mat4 load_mat4(const __nv_bfloat16* w, int lane) {
    const unsigned short* u = (const unsigned short*)w + (lane >> 2 & 1);
    const bool on = lane >> 3 == (lane & 3);
    Mat4 m;
#pragma unroll
    for (int k = 0; k < 4; k++) m.b[k] = on ? u[(k & 1) * 8 + (k & 2)] | (uint32_t)u[(k & 1) * 8 + 4 + (k & 2)] << 16 : 0u;
    return m;
}
__device__ __forceinline__ void mul4(const uint4& x, const Mat4& m, float (&y)[8]) {
#pragma unroll
    for (int h = 0; h < 2; h++)
        asm("mma.sync.aligned.m16n8k16.row.col.f32.bf16.bf16.f32 {%0,%1,%2,%3}, {%4,%5,%6,%7}, {%8,%9}, {%10,%10,%10,%10};"
            : "=f"(y[2 * h]), "=f"(y[2 * h + 1]), "=f"(y[4 + 2 * h]), "=f"(y[5 + 2 * h])
            : "r"(x.x), "r"(x.z), "r"(x.y), "r"(x.w), "r"(m.b[2 * h]), "r"(m.b[2 * h + 1]), "f"(0.f));
}

struct Scale { uint32_t eb[4]; bool allslow; };
__device__ __forceinline__ void md_stats(const uint4& in, const Mat4& wd, int lane) {
    float y[8];
    mul4(in, wd, y);
    uint32_t mx[4], se[4];
#pragma unroll
    for (int c = 0; c < 4; c++) {
        uint32_t a = __float_as_uint(y[c]) & 0x7fffffffu, b = __float_as_uint(y[4 + c]) & 0x7fffffffu;
        if (a >= 0x7f800000u) a = 0;
        if (b >= 0x7f800000u) b = 0;
        mx[c] = __reduce_max_sync(0xffffffffu, max(a, b));
        se[c] = __reduce_add_sync(0xffffffffu, (a >> 23) + (b >> 23) + (a ? 1u << 20 : 0u) + (b ? 1u << 20 : 0u));
    }
    if (lane < 4) {
        asm volatile("red.shared.max.u32 [%0], %1;" ::"r"(SB + SM_STAT + lane * 4), "r"(lane == 0 ? mx[0] : lane == 1 ? mx[1] : lane == 2 ? mx[2] : mx[3]) : "memory");
        reds_add(SB + SM_STAT + 16 + lane * 4, lane == 0 ? se[0] : lane == 1 ? se[1] : lane == 2 ? se[2] : se[3]);
    }
}
__device__ __forceinline__ Scale get_scale(uint32_t sb) {
    Scale s;
    s.allslow = false;
#pragma unroll
    for (int k = 0; k < 4; k++) {
        const uint32_t mx = lds32(sb + SM_STAT + 4 * k), se = lds32(sb + SM_STAT + 16 + 4 * k);
        const uint32_t mean = (uint32_t)__fdividef((float)(se & 0xfffffu), (float)max(se >> 20, 1u));
        uint32_t eb = min(min((mx + 0x6e0000u) >> 23, mean + 5u), 227u);
        if (eb < 27u) { s.allslow = s.allslow || mx != 0; eb = 27u; }
        if (eb > 170u) s.allslow = true;
        s.eb[k] = eb;
    }
    return s;
}

__device__ __forceinline__ uint32_t probe_rt(uint32_t* p) {
    uint32_t best = 0xffffffffu;
#pragma unroll 1
    for (int r = 0; r < CFG_PROBES; r++) {
        const uint32_t t0 = clock();
        uint32_t v;
        asm volatile("atom.relaxed.gpu.global.add.u32 %0, [%1], 1;" : "=r"(v) : "l"(p) : "memory");
        if (v > 100000u) __trap();
        const uint32_t t1 = clock();
        best = min(best, t1 - t0);
    }
    return best;
}
__device__ __forceinline__ uint32_t* pub_ptr(const Params& p, int blk, uint32_t sel) {
    const int pr = blk / 44;
    return (uint32_t*)(p.ring + PROBE_OFF + (pr ? 4096u << pr : 0u) + (sel << 12) + 2176 + (blk - pr * 44) * 32);
}
__device__ __forceinline__ void probe(const Params& p, uint32_t sb, int w, int lane) {
    const int blk = blockIdx.x, pr = w >> 1;
    uint32_t off = PROBE_OFF + blk * 16 + (pr ? 4096u << pr : 0u);
    if (pr == 7) off = blk < NWIN ? blk * WIN + 4064 : PROBE_OFF + 3584 + blk % 16 * 32;
    off += (w & 1) * 4096;
    if (lane < 8) st_rlx((uint32_t*)(p.ring + (off & ~31u)) + lane, 0u);
    if (lane == 0) sts32(sb + SM_PROBE + w * 4, probe_rt((uint32_t*)(p.ring + off)));
}
__device__ __forceinline__ void assign_role(const Params& p, uint32_t sb, int lane) {
    {
        const bool x = lane < 8 && lds32(sb + SM_PROBE + lane * 8 + 4) < lds32(sb + SM_PROBE + lane * 8);
        const uint32_t near = __ballot_sync(0xffffffffu, x), bits = near & 1 ? ~near | 1u : near;
        const uint32_t tag = (lds32(sb + SM_MISC + 16) + 1) << 30;
        uint32_t smid;
        asm("mov.u32 %0, %%smid;" : "=r"(smid));
        if (lane < 16) st_rlx(pub_ptr(p, blockIdx.x, lane >> 3) + (lane & 7), tag | (smid & 0xffffu) << 8 | (bits & 0xffu));
        constexpr int K = (NCTA + 31) / 32;
        __nanosleep(CFG_P0);
        uint32_t v[K], bad;
        int guard = 0;
        do {
            bad = 0;
#pragma unroll
            for (int k = 0; k < K; k++) {
                const int b = min(lane + 32 * k, NCTA - 1);
                v[k] = ld_rlx(pub_ptr(p, b, near >> (b / 44) & 1));
                bad |= v[k] ^ tag;
            }
            bad = __any_sync(0xffffffffu, bad >> 30);
            if (bad) __nanosleep(CFG_PSLEEP);
            if (++guard > GUARD) __trap();
        } while (bad);
#pragma unroll
        for (int k = 0; k < K; k++) sts32(sb + SM_PUB + (lane + 32 * k) * 4, v[k]);
    }
    __syncwarp();
    constexpr int NP = NCTA / 2, NTAB = H2 + H3;
    const int me = blockIdx.x >> 1, odd = blockIdx.x & 1;
    uint32_t pp[3], st[5] = {0, 0, 0, 0, 0}, key[3];
    int n1 = 0;
#pragma unroll
    for (int k = 0; k < 3; k++) {
        const int i = lane + 32 * k;
        const uint32_t a = lds32(sb + SM_PUB + min(i, NP - 1) * 8), b = lds32(sb + SM_PUB + min(max(i - 1, 0), NP - 1) * 8);
        pp[k] = a & 1;
        st[k + 1] = __ballot_sync(0xffffffffu, i == 0 || i >= NP || (a >> 8) < (b >> 8));
        n1 += 2 * __popc(__ballot_sync(0xffffffffu, i < NP && pp[k]));
    }
    bool fixed = n1 < NTAB || NCTA - n1 < NTAB;
    if (fixed) n1 = NP / 2 * 2;
#pragma unroll
    for (int k = 0; k < 3; k++) {
        const uint32_t rank = __clz(__funnelshift_rc(st[k], st[k + 1], lane + 1)), len = rank + __ffs(__funnelshift_rc(st[k + 1], st[k + 2], lane + 1));
        if (fixed) pp[k] = lane & 1;
        key[k] = (len < 4 ? CFG_SKEY : min(rank, 15u) * 2) << 8 | (lane + 32 * k);
    }
    const uint32_t mine = __shfl_sync(0xffffffffu, (me < 32 ? key[0] : me < 64 ? key[1] : key[2]) * 2 + (me < 32 ? pp[0] : me < 64 ? pp[1] : pp[2]), me & 31);
    const int part = mine & 1;
    int pos = odd;
#pragma unroll
    for (int k = 0; k < 3; k++) pos += 2 * __popc(__ballot_sync(0xffffffffu, lane + 32 * k < NP && pp[k] == (uint32_t)part && key[k] < mine / 2));
    const int role = pos < H2 ? 1 : pos < NTAB ? 2 : 0;
    const int id = pos < H2 ? part * H2 + pos : pos < NTAB ? part * H3 + pos - H2 : (part ? NCTA - n1 - NTAB : 0) + pos - NTAB;
    const uint32_t v = lds32(sb + SM_PUB + lane * 4);
    uint32_t lin = 0;
#pragma unroll
    for (int b = 0; b < 6; b++) lin |= (__popc(__ballot_sync(0xffffffffu, (v >> (b + 1)) & 1)) > 16 ? 1u : 0u) << b;
    if (lane == 0) {
        sts32(sb + SM_MISC, role << 8 | id);
        sts32(sb + SM_MISC + 4, lin);
        sts32(sb + SM_MISC + 8, NCTA - n1 - NTAB);
        sts32(sb + SM_MISC + 20, part);
        sts32(sb + SM_MISC + 12, role == 0 ? id : role == 1 ? N1 + id : N1 + N2 + id);
    }
}
__device__ __forceinline__ uint32_t sel_of(uint32_t sb, int widx, uint32_t k, int part) {
    return (__popc(k & lds32(sb + SM_MISC + 4)) ^ (lds32(sb + SM_PUB + widx * 4) >> 7) ^ part) & 1;
}
__device__ __forceinline__ uint32_t gran_off(uint32_t sb, int widx, int k, int part) { return (2 * k + sel_of(sb, widx, k, part)) << 12; }
__device__ __forceinline__ uint32_t q1a_off(uint32_t sb, int src, int blk, int part) { return gran_off(sb, 2 * blk + part, src >> 1, part) + (src & 1) * 2048; }
__device__ __forceinline__ uint32_t q1h_off(uint32_t sb, int src, int blk, int part) { return gran_off(sb, 2 * blk + part, 32 + (src >> 2), part) + (src & 3) * 1024; }
__device__ __forceinline__ uint32_t* ctl_word(const Params& p, uint32_t sb, int k, int word, int part) {
    const int widx = CWIN + lds32(sb + SM_MISC + 16);
    return (uint32_t*)(p.ring + (widx * WIN + ((2 * k + sel_of(sb, widx, k, part)) << 12))) + word;
}
__device__ __forceinline__ uint32_t* cred1_of(const Params& p, uint32_t sb, int src) { return ctl_word(p, sb, src >> 3, (src & 7) * 128, src >= (int)lds32(sb + SM_MISC + 8)); }
__device__ __forceinline__ uint32_t* fin1_of(const Params& p, uint32_t sb, int dst) { return ctl_word(p, sb, 8 + (dst >> 3), (dst & 7) * 128, dst / H2); }
__device__ __forceinline__ uint32_t* cred2_of(const Params& p, uint32_t sb, int src) { return ctl_word(p, sb, 16 + (src >> 3), (src & 7) * 128, src / H2); }
__device__ __forceinline__ uint32_t* fin2_of(const Params& p, uint32_t sb, int dst) { return ctl_word(p, sb, 24 + (dst >> 3), (dst & 7) * 128, dst / H3); }
__device__ __forceinline__ uint32_t* rdy_of(const Params& p, uint32_t sb, int word, int part) { return ctl_word(p, sb, 28, word, part); }
__device__ __forceinline__ uint32_t q2_off(uint32_t sb, int blk, int dst) {
    return (N2 + dst) * WIN + gran_off(sb, N2 + dst, (blk >> 1) * 4 + (blk & 1), dst / H3);
}
template <bool IS1>
__device__ __forceinline__ void clear_queues(const Params& p, uint32_t sb, int id, int lane) {
    constexpr int NA = (N1 + 1) / 2, NG = NA + (N1 + 3) / 4, N = IS1 ? NG * N2 : NI * 2;
    if (IS1 && lane == 0) spin_ge(rdy_of(p, sb, 320, lds32(sb + SM_MISC + 20)), NTAIL);
    __syncwarp();
    fence_async_smem();
    for (int k = IS1 ? id + lane * N1 : lane; k < N; k += IS1 ? 32 * N1 : 32) {
        const int wi = k / NG, g = k - wi * NG;
        const uint32_t off = IS1 ? wi * WIN + gran_off(sb, wi, g < NA ? g : 32 + g - NA, wi & 1) : q2_off(sb, k >> 1, id) + (k & 1) * 16384;
        bulk_store(p.ring + off, sb + SM_ZERO, 4096);
    }
    asm volatile("cp.async.bulk.commit_group;" ::: "memory");
    asm volatile("cp.async.bulk.wait_group 0;" ::: "memory");
    if (!IS1) {
        fence_async_all();
        __syncwarp();
        fence_gpu();
        if (lane < NI) red_rlx(rdy_of(p, sb, id / H3 * H2 + lane, id / H3), 1u);
    }
    __syncwarp();
}

struct In8 { uint4 a[2], o[2]; uint2 g[2]; };
__device__ __forceinline__ void p1_load(const Params& p, In8& r, int i4) {
#pragma unroll
    for (int u = 0; u < 2; u++) {
        [[maybe_unused]] uint32_t x, y;
        asm volatile("tex.1d.v4.u32.s32 {%0,%1,%2,%3}, [%4, {%5}];" : "=r"(r.a[u].x), "=r"(r.a[u].y), "=r"(r.a[u].z), "=r"(r.a[u].w) : "l"(p.t_in), "r"(i4 + u * 32));
        asm volatile("tex.1d.v4.u32.s32 {%0,%1,%2,%3}, [%4, {%5}];" : "=r"(r.o[u].x), "=r"(r.o[u].y), "=r"(r.o[u].z), "=r"(r.o[u].w) : "l"(p.t_out), "r"(i4 + u * 32));
        asm volatile("tex.1d.v4.u32.s32 {%0,%1,%2,%3}, [%4, {%5}];" : "=r"(r.g[u].x), "=r"(r.g[u].y), "=r"(x), "=r"(y) : "l"(p.t_ang), "r"(i4 + u * 32));
    }
}
__device__ __forceinline__ uint32_t imad(uint32_t a, uint32_t b, uint32_t c) {
    uint32_t r;
    asm("mad.lo.u32 %0, %1, %2, %3;" : "=r"(r) : "r"(a), "r"(b), "r"(c));
    return r;
}
__device__ __forceinline__ unsigned char* ring_ptr(const Params& p, uint32_t lo) {
    uint64_t r;
    asm("mov.b64 %0, {%1, %2};" : "=l"(r) : "r"(lo), "r"(p.ring_hi));
    return (unsigned char*)r;
}
__device__ __forceinline__ uint32_t opaque32(uint32_t x) {
    asm volatile("" : "+r"(x));
    return x;
}
template <typename T> __device__ __forceinline__ T* opaque(T* p) {
    asm volatile("" : "+l"(p));
    return p;
}
template <int LUT> __device__ __forceinline__ uint32_t lop3(uint32_t a, uint32_t b, uint32_t c) {
    uint32_t r;
    asm("lop3.b32 %0, %1, %2, %3, %4;" : "=r"(r) : "r"(a), "r"(b), "r"(c), "n"(LUT));
    return r;
}
__device__ __forceinline__ uint32_t dp4(uint32_t a, uint32_t b, uint32_t c) {
    uint32_t r;
    asm("dp4a.u32.u32 %0, %1, %2, %3;" : "=r"(r) : "r"(a), "r"(b), "r"(c));
    return r;
}
__device__ __forceinline__ uint32_t dp2(uint32_t a, uint32_t b, uint32_t c) {
    uint32_t r;
    asm("dp2a.lo.u32.u32 %0, %1, %2, %3;" : "=r"(r) : "r"(a), "r"(b), "r"(c));
    return r;
}
__device__ __forceinline__ void p1_put(uint32_t sb, uint32_t wa, uint32_t wb, uint32_t old, bool on) {
    asm volatile("{.reg .pred q; setp.ne.u32 q, %3, 0; @q st.shared.v2.u32 [%0], {%1,%2};}"
                 ::"r"(sb + A_ST + prmt(old, wb, 0xf762)), "r"(wa), "r"(prmt(wb, old, 0x7210)), "r"((uint32_t)on) : "memory");
}
__device__ __forceinline__ void p1_slow_tile(const Params& p, uint32_t sb, int i4) {
    const float f = __bfloat162float(p.freq[0]);
#pragma unroll 1
    for (int u = 0; u < 8; u++) {
        const int k4 = i4 + (u >> 2) * 32;
        if (k4 < p.n4) {
            const size_t t = (size_t)k4 * 4 + (u & 3);
            const float x = __bfloat162float(__float2bfloat16(f * __bfloat162float(p.angle[t])));
            slow_add(p.m, sb, p.idx_in[t], p.idx_out[t], __bfloat162float(__float2bfloat16(cosf(x))));
        }
    }
}
__device__ __forceinline__ void role_p1(const Params& p, uint32_t sb, int id, int w, int lane) {
    lane = __shfl_sync(0xffffffffu, lane, lane);
    const uint32_t f2 = (uint32_t)__bfloat16_as_ushort(p.freq[0]) * 0x10001u;
    constexpr int TG = CFG_TG, NTK = CFG_NTK;
    static_assert(N1 * P1W % NTK == 0 && (NTK == 16 || NTK == 8) && P1W % 2 == 0, "tickets");
    const int first = (N1 * P1W + (id * P1W + w) % NTK) * (TG * 64);
    uint32_t* const tickets = opaque(ctl_word(p, sb, 29 + (id * P1W + w) % NTK / 8, (id * P1W + w) % 8 * 128 + lane, w & 1));
    auto draw = [&]() {
        uint32_t t = 0;
        asm volatile("{.reg .pred q; setp.eq.u32 q, %2, 0; @q atom.relaxed.gpu.global.add.u32 %0, [%1], 1;}" : "+r"(t) : "l"(tickets), "r"(lane) : "memory");
        return t;
    };
    int i4 = (id * P1W + w) * (TG * 64);
    In8 r;
    ACC_DECL
    uint32_t tk = draw();
    p1_load(p, r, i4 + lane);
    while (i4 < p.n4) {
        const int cur = i4;
        i4 += 64;
        if (i4 % (TG * 64) == 0) {
            i4 = min(__shfl_sync(0xffffffffu, tk, 0), 0x7fffffffu / (NTK * TG * 64) - N1 * P1W / NTK - 2) * (NTK * TG * 64) + first;
            tk = draw();
        }
        uint32_t wa[8], wb[8], x2[4];
        x2[0] = mul_bf2(r.g[0].x, f2); x2[1] = mul_bf2(r.g[0].y, f2);
        x2[2] = mul_bf2(r.g[1].x, f2); x2[3] = mul_bf2(r.g[1].y, f2);
        const uint32_t mx = maxabs_bf2(maxabs_bf2(x2[0], x2[1]), maxabs_bf2(x2[2], x2[3]));
        const bool fast = __all_sync(0xffffffffu, cur + 64 <= p.n4 && ((mx & 0x7fffu) <= 0x4300u) && ((mx & 0x7fff0000u) <= 0x43000000u));
        {
            const uint32_t in[8] = {r.a[0].x, r.a[0].y, r.a[0].z, r.a[0].w, r.a[1].x, r.a[1].y, r.a[1].z, r.a[1].w};
            const uint32_t ou[8] = {r.o[0].x, r.o[0].y, r.o[0].z, r.o[0].w, r.o[1].x, r.o[1].y, r.o[1].z, r.o[1].w};
#pragma unroll
            for (int j = 0; j < 8; j += 2) {
                const uint32_t ch = mul_h2(pack_h2(__cosf(bflo(x2[j >> 1])), __cosf(bfhi(x2[j >> 1]))), 0x24002400u);
#pragma unroll
                for (int k = j; k < j + 2; k++) {
                    const uint32_t blk = __umulhi(in[k], p.magic2), il = imad(blk, p.nrows2, in[k]);
                    wa[k] = k & 1 ? bitsel(ch, il, 0xffff0000u) : imad(ch, 65536u, il);
                    wb[k] = imad(blk, 1u << 21, imad(ou[k] >> 5, 1u - (1u << 21), ou[k] << 16));
                }
            }
        }
        p1_load(p, r, i4 + lane);
        if (fast) {
            uint32_t old[8], any = 0;
#pragma unroll
            for (int j = 0; j < 8; j++) old[j] = atoms_add(dp2(wb[j], 0x400u, 0u) + (sb + A_CNT), 0x80001u);
#pragma unroll
            for (int j = 0; j < 8; j++) any |= old[j];
            if (!__any_sync(0xffffffffu, any & 0xffe0u)) {
#pragma unroll
                for (int j = 0; j < 8; j++) p1_put(sb, wa[j], wb[j], old[j], true);
            } else {
                uint32_t pend = 0;
#pragma unroll
                for (int j = 0; j < 8; j++) { p1_put(sb, wa[j], wb[j], old[j], !(old[j] & 0xffe0u)); if (old[j] & 0xffe0u) pend |= 1u << j; }
                ACC(0, 1)
                for (int guard = 0; __any_sync(0xffffffffu, pend); guard++) {
                    __nanosleep(CFG_BSLEEP);
                    ACC(1, 1)
#pragma unroll
                    for (int j = 0; j < 8; j++) {
                        if (__any_sync(0xffffffffu, pend >> j & 1)) {
                            const uint32_t c = lds32v(sb + A_CNT + (pend >> j & 1 ? wb[j] >> 16 : 0) * 4);
                            const bool go = (pend >> j & 1) && (((old[j] >> 19) - (c >> 19) + c) & 8191u) < 32u;
                            p1_put(sb, wa[j], wb[j], old[j], go);
                            if (go) pend &= ~(1u << j);
                        }
                    }
                    if (guard > GUARD) __trap();
                }
            }
        } else {
            p1_slow_tile(p, sb, cur + lane);
            __syncwarp();
        }
    }
    __syncwarp();
    mbar_arrive_if(sb + SM_DONE, lane == 0);
    ACC_SAVE
}

__device__ __forceinline__ void role_flush(const Params& p, uint32_t sb, int id, int f, int lane) {
    lane = __shfl_sync(0xffffffffu, lane, lane);
    const int half = lane >> 4, o = lane >> 2, q = lane & 3;
    const uint32_t hm = half ? 0xffff0000u : 0xffffu, lth = ((1u << lane) - 1) & hm;
    const uint32_t list = sb + A_LIST + f * LISTB + half * LISTH, cnt = sb + A_CNT + (f * GPW * 32 + lane) * 4;
    const uint32_t* const cred = opaque(cred1_of(p, sb, id) + half * 32 + f * GPW);
    const uint32_t pa = opaque32(p.ring_lo + half * WIN + (id >> 1) * 8192 + (id & 1) * 2048 + q * 16);
    const uint32_t ph = opaque32(p.ring_lo + half * WIN + (32 + (id >> 2)) * 8192 + (id & 3) * 1024 + q * 8 - 2048);
    const uint32_t sa = q * 16 + (o & 1) * 64;
    uint32_t qo[GPW], hs[GPW], cr[4] = {0, 0, 0, 0};
#pragma unroll
    for (int g = 0; g < GPW; g++) {
        const int blk = f * GPW + g;
        qo[g] = 32u << 25;
        const uint32_t sa = sel_of(sb, 2 * blk + half, id >> 1, half), sh = sel_of(sb, 2 * blk + half, 32 + (id >> 2), half);
        hs[g] = sa << 31 | (2 * sh + 1 - sa) << 22 | 1u << 24 | (lane & 15) << 15 | (blk * 32 + lane) * 2;
    }
    uint4 x[KR] = {}, y[KR] = {};
    ACC_DECL
    int guard = 0;
    bool idle = false, done = false;
    while (true) {
        uint32_t c[GPW], fr[GPW], end = list, left = 0;
        if (idle && !done && __all_sync(0xffffffffu, mbar_test(sb + SM_DONE, 0))) {
            done = true;
            TR(17, f == 0 && lane == 0);
#pragma unroll
            for (int g = 0; g < GPW; g++) {
                const uint32_t u = lds32v(cnt + g * 128) & 31u, hd = hs[g] ^ (u & 16u ? imad(hs[g], 1u << 24, 1u) & 0x01000001u : 0u);
#pragma unroll 3
                for (uint32_t k = 1; k < 16; k++)
                    sts64_if(sb + A_ST + ((hd & 0x7ffu) << 7) + k * 8, p.rows2, (lane * 16 + k) | (hd & 0x1000000u), (u & 15u) && k >= (u & 15u));
                reds_add(cnt + g * 128, ((0u - u) & 15u) * 0x80001u);
            }
            __syncwarp();
        }
#pragma unroll
        for (int g = 0; g < GPW; g++) c[g] = lds32v(cnt + g * 128);
#pragma unroll
        for (int g = 0; g < GPW; g++) {
            const bool isfull = c[g] & 0xfff0u;
            const uint32_t m = __ballot_sync(0xffffffffu, isfull), rank = __popc(m & lth), r25 = rank << 25;
            const bool ok = isfull && (int)r25 < (int)(cr[g] - qo[g] + (63u << 25));
            const uint32_t n = __popc(__ballot_sync(0xffffffffu, ok) & hm);
            ACC(2, __popc(__ballot_sync(0xffffffffu, isfull && !ok)))
            sts32_if(imad(rank, 4u, end), bitsel(qo[g] + r25, hs[g], 0x7e000000u), ok);
            if (ok) hs[g] ^= imad(hs[g], 1u << 24, 1u) & 0x01000001u;
            fr[g] = ok ? 0u - 16u : 0u;
            left |= c[g] + fr[g];
            qo[g] = imad(n, 1u << 25, qo[g]);
            end = imad(n, 4u, end);
        }
        auto credits = [&]() {
            if (GPW == 4) { const uint4 v = ldg_q128(cred); cr[0] = v.x; cr[1] = v.y; cr[2] = v.z; cr[3] = v.w; }
            else { const uint2 v = ldg_q64(cred); cr[0] = v.x; cr[1] = v.y; }
        };
        if (CFG_CRE) credits();
        __syncwarp();
        ACC(0, 1) ACC(1, (end - list) / 2)
        if (__any_sync(0xffffffffu, end != list)) {
            uint32_t la = list + (o & 3) * 4;
            do {
                uint32_t d[KR];
#pragma unroll
                for (int k = 0; k < KR; k++) d[k] = lds32v(la + 16 * k);
                while (true) {
                    uint32_t bad = 0;
#pragma unroll
                    for (int k = 0; k < KR; k++) {
                        const uint32_t m = d[k] & 0x7ffu;
                        lds128_keep(x[k], imad(m, 128u, sa) + (sb + A_ST), la + 16 * k < end);
                        lds128_keep(y[k], imad(m, 128u, sa ^ 64) + (sb + A_ST), la + 16 * k < end);
                    }
#pragma unroll
                    for (int k = 0; k < KR; k++)
                        or3_if(bad, lop3<0x7e>(x[k].y, x[k].w, d[k]), lop3<0x7e>(y[k].y, y[k].w, d[k]), la + 16 * k < end);
                    if (!__any_sync(0xffffffffu, (int)imad(bad, 128u, 0u) < 0)) break;
                    if (++guard > GUARD) __trap();
                }
#pragma unroll
                for (int k = 0; k < KR; k++) {
                    const uint32_t mi = d[k] & 0x7c0u, dm = d[k] & 0xbec00000u;
                    x[k].x = bitsel(d[k], x[k].x, 0x40078000u);
                    x[k].y = prmt(x[k].y, x[k].w, 0x5410);
                    x[k].w = prmt(y[k].y, y[k].w, 0x5410);
                    y[k].x = bitsel(d[k], y[k].x, 0x40000000u);
                    y[k].y = y[k].z;
                    stg_q128(ring_ptr(p, dp4(dm, 0x20000000u, imad(mi, WIN / 32, pa))), x[k].x, x[k].y, x[k].z, x[k].w, X_ST1 la + 16 * k < end);
                    stg_q64(ring_ptr(p, dp4(dm, 0x10200000u, imad(mi, WIN / 32, ph))), y[k].x, y[k].y, X_ST1 la + 16 * k < end);
                }
                la += 16 * KR;
            } while (__any_sync(0xffffffffu, la < end));
            if (!CFG_CRE) credits();
#pragma unroll
            for (int g = 0; g < GPW; g++) reds_add(cnt + g * 128, fr[g]);
            idle = !__any_sync(0xffffffffu, end - list > 4 * CFG_TH);
            if (done && !__any_sync(0xffffffffu, left & 0xffffu)) break;
            if (idle) __nanosleep(CFG_TS);
        } else {
            if (done && !__any_sync(0xffffffffu, left & 0xffffu)) break;
            if (!CFG_CRE && __any_sync(0xffffffffu, left & 0xfff0u)) credits();
            idle = true;
            __nanosleep(CFG_FSLEEP);
            if (++guard > GUARD) __trap();
        }
    }
#pragma unroll
    for (int g = 0; g < GPW; g++) st_rlx_if(fin1_of(p, sb, half * H2 + f * GPW + g) + id, qo[g] - (32u << 25) + 1u, (lane & 15) == 0);
    TR(18, f == 0 && lane == 0);
    ACC_SAVE
}

__device__ __forceinline__ float h2f(uint32_t h) {
    float f;
    asm("{.reg .b16 t; cvt.u16.u32 t, %1; cvt.f32.f16 %0, t;}" : "=f"(f) : "r"(h));
    return f;
}
__device__ __forceinline__ void p2_slow(const Params& p, uint32_t sb, const uint32_t* tmp, int row0, uint32_t dst) {
#pragma unroll 1
    for (int j = 0; j < 4; j++)
        if (tmp[8 + j] & 0x40u) slow_add(p.m, sb, row0 + (tmp[j] & 0x7fffu), (tmp[4 + j] & 0x7fffu) * 32 + dst, h2f(tmp[j] >> 16) * 64.0f);
}
__device__ __forceinline__ uint32_t mul_h2_hi(uint32_t a, uint32_t b) {
    uint32_t r;
    asm("{.reg .b16 l, h; .reg .b32 t; mov.b32 {l, h}, %2; mov.b32 t, {h, h}; mul.rn.f16x2 %0, %1, t;}" : "=r"(r) : "r"(a), "r"(b));
    return r;
}
template <bool CHECK>
__device__ __forceinline__ void role_p2(const Params& p, uint32_t sb, int id, int w, int lane) {
    lane = __shfl_sync(0xffffffffu, lane, lane);
    const int part = id / H2, blk = id - part * H2, row0 = blk * p.rows2;
    const int o = lane >> 2, q = lane & 3;
    uint32_t* const cbase = (uint32_t*)(p.ring + (CWIN + lds32(sb + SM_MISC + 16)) * WIN);
    const uint32_t cred = opaque32((uint32_t)(uintptr_t)(cbase + part * 32 + blk));
    const uint32_t pa = opaque32(p.ring_lo + (2 * blk + part) * WIN + q * 16), ph = opaque32(pa - q * 8);
    const uint32_t po = opaque32(p.ring_lo + (q2_off(sb, blk, part * H3) & ~4096u) + q * 16 + (o & 1) * 64);
    const uint32_t sel = __ballot_sync(0xffffffffu, q2_off(sb, blk, part * H3 + (lane & 15)) & 4096u) << 12;
    const uint32_t* const fins = fin1_of(p, sb, id);
    uint32_t st[QPW] = {}, sq[QPW] = {};
    uint4 qa[NBT];
    uint2 qh[NBT];
    auto load = [&](int k) {
        qa[k] = ldg_q128(ring_ptr(p, pa + (bitsel(sq[k], st[k] >> 19, 0x7f800u) & 0x7ffc0u)));
        qh[k] = ldg_q64(ring_ptr(p, ph + (bitsel(sq[k] >> 9, st[k] >> 20, 0x7fc00u) & 0x7ffe0u)));
    };
#pragma unroll
    for (int k = 0; k < QPW; k++) {
        const int src = w * QPW + k;
        st[k] = o << 25 | (src < N1 ? 1u : 5u);
        sq[k] = src < N1 ? q1h_off(sb, src, blk, part) << 9 | q1a_off(sb, src, blk, part) | (uint32_t)(cred1_of(p, sb, src) - cbase) / 8 : 0x7e000u * 513u;
    }
#pragma unroll
    for (int k = 0; k < NBT; k++) load(k);
    ACC_DECL
    int guard = 0;
    uint32_t streak = 0;
    while (true) {
        uint32_t nn[NBT], xx[NBT][4], hh[NBT][2], dd[NBT], any = 0;
        bool last = false;
#pragma unroll
        for (int k = 0; k < NBT; k++) {
            const uint4 a = qa[k];
            const uint2 h = qh[k];
            uint32_t n = 8;
            const uint32_t miss = __ballot_sync(0xffffffffu, (int)imad((a.x ^ st[k]) & (h.x ^ st[k]), 2u, 0u) >= 0);
            if (miss) {
                n = (__ffs(miss) - 1) >> 2;
                if (!__any_sync(0xffffffffu, st[k] & 8u)) { if (streak < CFG_PSTREAK) n &= CFG_PMASK; }
                else if (!__any_sync(0xffffffffu, ((st[k] >> 6) + ((n - o) << 19) ^ st[k]) & 0x1f80000u)) { st[k] |= 4u; last = true; }
            }
            ACC(1, n == 0) ACC(2, n != 0) ACC(3, n)
            st[k] = imad(n, 1u << 25, st[k]);
            st_rlx_if((uint32_t*)ring_ptr(p, imad(sq[k] & 0x7f0u, 32u, cred)), st[k], X_CR1 lane == 0 && n);
            xx[k][0] = bitsel(a.x, 0x00040000u, 0xbff87fffu); xx[k][1] = a.z; xx[k][2] = h.x & 0xbfffffffu; xx[k][3] = h.y;
            hh[k][0] = a.y; hh[k][1] = a.w; dd[k] = a.x >> 13 & 0x3cu; nn[k] = n;
            any |= n;
        }
        if (!any) {
#pragma unroll
            for (int k = 0; k < QPW; k++) {
                const uint32_t fin = ld_rlx(fins + ((sq[k] >> 12 & 62u) | (sq[k] >> 11 & 1u)));
                if (fin & 1u) st[k] |= (fin >> 6 & 0x1f80000u) | 8u;
            }
            if (++guard > GUARD) __trap();
            streak++;
        } else streak = 0;
        if (last) {
            uint32_t all = 4u;
#pragma unroll
            for (int k = 0; k < QPW; k++) all &= st[k];
            last = __all_sync(0xffffffffu, all);
        }
        {
            uint32_t t[QPW], u[QPW];
#pragma unroll
            for (int k = 0; k < QPW; k++) { t[k] = st[(k + NBT) % QPW]; u[k] = sq[(k + NBT) % QPW]; }
#pragma unroll
            for (int k = 0; k < QPW; k++) { st[k] = t[k]; sq[k] = u[k]; }
        }
#pragma unroll
        for (int k = 0; k < NBT; k++) load(k);
#pragma unroll
      for (int k = 0; k < NBT; k++) {
        if (nn[k]) {
            const uint32_t* const x = xx[k];
            const uint32_t h0 = hh[k][0], h1 = hh[k][1], d4 = dd[k];
            const bool v = o < nn[k];
            uint32_t old = 0, ta[4], tb[4], w0[4], w1[4];
            atoms_add_keep(old, sb + SM_CNT2 + d4, 0x10001u, q == 0 && v);
#pragma unroll
            for (int j = 0; j < 4; j++) {
                ta[j] = lds32nv(dp2(x[j], 4u, 0u) + (sb + B_TA));
                tb[j] = lds16nv(dp2(x[j], 2u, 0u) + (sb + B_TB));
            }
            old = __shfl_sync(0xffffffffu, old, lane & 28);
            const uint32_t tag = old << 8 & 0x40000000u;
#pragma unroll
            for (int j = 0; j < 4; j++) {
                const uint32_t z = prmt(j & 2 ? h1 : h0, 0, j & 1 ? 0x4342 : 0x4140);
                const uint32_t t23 = prmt((ta[j] & 0x60076007u) * 2050u, tb[j], 0x5341) & 0xfffcffffu;
                w0[j] = (imad(z, 128u, j & 1 ? 0u : tag) & 0x78007800u) | mul_h2_hi(ta[j] & 0x9ff89ff8u, x[j]);
                w1[j] = (imad(z, 2048u, 0u) & 0x78007800u) | mul_h2_hi(t23, x[j]);
            }
            if (CHECK && v && ((tb[0] | tb[1] | tb[2] | tb[3]) & 0x40u)) {
                uint32_t tmp[12];
#pragma unroll
                for (int j = 0; j < 4; j++) {
                    tmp[j] = x[j]; tmp[4 + j] = (j & 2 ? h1 : h0) >> (j & 1 ? 16 : 0); tmp[8 + j] = tb[j];
                    if (tb[j] & 0x40u) { w0[j] &= 0x78007800u; w1[j] &= 0x78007800u; }
                }
                p2_slow(p, sb, tmp, row0, part * H3 + d4 / 4);
            }
            const uint32_t off = (bitsel(old >> 9, old >> 7, 0x0f80u) & 0x4f80u) + imad(d4, WIN / 4, (sel >> (d4 / 4) & 4096u) + po);
            bool wait = old & (0x10000u - NQ2);
            if (!__any_sync(0xffffffffu, wait)) {
                stg_q128(ring_ptr(p, off), w0[0], w1[0], w0[1], w1[1], X_ST2 v);
                stg_q128(ring_ptr(p, off ^ 64u), w0[2], w1[2], w0[3], w1[3], X_ST2 v);
            } else {
                bool pend = v;
                ACC(0, 1)
                for (int g2 = 0;; g2++) {
                    stg_q128(ring_ptr(p, off), w0[0], w1[0], w0[1], w1[1], pend && !wait);
                    stg_q128(ring_ptr(p, off ^ 64u), w0[2], w1[2], w0[3], w1[3], pend && !wait);
                    pend = wait;
                    if (!__any_sync(0xffffffffu, pend)) break;
                    __nanosleep(CFG_BSLEEP);
                    const uint32_t c = lds32v(sb + SM_CNT2 + d4);
                    wait = pend && (((old >> 16) - (c >> 16) + c) & 0xffffu) >= NQ2;
                    if (g2 > GUARD) __trap();
                }
            }
        }
      }
        if (last) break;
    }
    TR(17, w == 0 && lane == 0);
    __syncwarp();
    uint32_t rank = 0;
    if (lane == 0) { __threadfence_block(); rank = atoms_add(sb + SM_FIN, 1u); __threadfence_block(); }
    if (__shfl_sync(0xffffffffu, rank, 0) == P2W - 1 && lane < 16)
        st_rlx(fin2_of(p, sb, part * H3 + lane) + blk, FIN | (((lds32v(sb + SM_CNT2 + lane * 4) >> 16) - NQ2) & 0xffffu));
    __syncwarp();
    mbar_arrive_if(sb + SM_DONE, lane == 0);
    ACC_SAVE
}
__device__ __forceinline__ void role_credit(const Params& p, uint32_t sb, int id, int lane) {
    const uint32_t* const cred = cred2_of(p, sb, id) + (lane & 15);
    uint32_t last = 0;
    for (int guard = 0;; guard++) {
        if (__all_sync(0xffffffffu, mbar_test(sb + SM_DONE, 0))) break;
        const uint32_t c = ld_rlx(cred);
        if (lane < 16 && c != last) reds_add(sb + SM_CNT2 + lane * 4, 0u - ((c - last) & 0xffffu));
        last = c;
        __nanosleep(CFG_CSLEEP);
        if (guard > GUARD) __trap();
    }
}

__device__ __forceinline__ void p3_wrap(uint32_t sb, int id, const uint32_t* tmp) {
    const Scale sc = get_scale(sb);
#pragma unroll 1
    for (int j = 0; j < 8; j++) {
        const uint32_t old = tmp[4 + j], v = tmp[12 + j], nw = old + v, t = (old ^ nw) & (v ^ nw);
        if (t & 0x80008000u) {
            const float k = (t & 0x8000u) ? ((v & 0x8000u) ? -1.0f : 1.0f) : 0.0f;
            const float q = (t & 0x80000000u) ? ((int)v < 0 ? -65536.0f : 65536.0f) : 0.0f;
            const uint32_t e0 = (j & 1) ? sc.eb[2] : sc.eb[0], e1 = (j & 1) ? sc.eb[3] : sc.eb[1];
            const float lo = k * 65536.0f * __uint_as_float((e0 - 10) << 23), hi = (q - k) * __uint_as_float((e1 - 10) << 23);
            if (j & 1) sg_add(tmp[j >> 1] * 32 + id, 0.f, 0.f, lo, hi);
            else sg_add(tmp[j >> 1] * 32 + id, lo, hi, 0.f, 0.f);
        }
    }
}
__device__ __forceinline__ uint32_t p3_val(uint32_t w) {
    const uint32_t mk = prmt(w, 0, 0xBB99);
    return ((w & 0x07ff07ffu) ^ mk) - mk;
}
__device__ __forceinline__ void role_p3(const Params& p, uint32_t sb, int id, int w, int lane) {
    lane = __shfl_sync(0xffffffffu, lane, lane);
    uint32_t* const cred = opaque(cred2_of(p, sb, id / H3 * H2 + w) + id % H3);
    const uint32_t pq = opaque32(p.ring_lo + q2_off(sb, w, id) + lane * 16);
    auto off = [&](uint32_t n) { return (n & 1u) << 11 | (n & 2u) << 13; };
    const uint32_t pp = opaque32(pq - lane * 16 + 2032);
    auto tag_of = [&](uint32_t n) { return ~n << 28; };
    uint32_t n = 0, fin = 0, pr = 0;
    uint4 v[4] = {};
    bool have = false, last = false;
    ACC_DECL
    int guard = 0;
    while (true) {
        const uint32_t ex = tag_of(n);
        const bool ok = have && !__any_sync(0xffffffffu, ((v[0].x ^ ex) | (v[1].x ^ ex) | (v[2].x ^ ex) | (v[3].x ^ ex)) & 0x40000000u);
        if (ok) n++;
        const bool ready = __all_sync(0xffffffffu, (have && !ok) || !((pr ^ tag_of(n)) & 0x40000000u));
        st_rlx_if(cred, n * 16, X_CR2 lane == 0 && ok);
        if (!ok && !ready && __all_sync(0xffffffffu, fin & FIN)) {
            const uint32_t left = __shfl_sync(0xffffffffu, (fin - n * 16) & 0xffffu, 0);
            if (left - 1u > 0x8000u) break;
            if (left < 16u) {
#pragma unroll
                for (int u = 0; u < 4; u++) {
                    v[u] = make_uint4(ex & 0x40000000u, 0, 0, 0);
                    ldq128_keep(v[u], ring_ptr(p, pq + off(n)) + u * 512, u * 4 + (lane >> 3) < left);
                }
                have = last = !__any_sync(0xffffffffu, ((v[0].x ^ ex) | (v[1].x ^ ex) | (v[2].x ^ ex) | (v[3].x ^ ex)) & 0x40000000u);
                pr = ~tag_of(n + have);
                if (++guard > GUARD) __trap();
                continue;
            }
        }
        uint32_t row[8], val[16];
#pragma unroll
        for (int u = 0; u < 4; u++) {
            const uint4 x = v[u];
            row[2 * u] = prmt(bitsel(x.x << 1, x.y >> 3, 0x7000f000u), 0, 0x4431);
            row[2 * u + 1] = prmt(bitsel(x.z << 1, x.w >> 3, 0x7000f000u), 0, 0x4431);
            val[4 * u] = p3_val(x.x); val[4 * u + 1] = p3_val(x.y);
            val[4 * u + 2] = p3_val(x.z); val[4 * u + 3] = p3_val(x.w);
        }
#pragma unroll
        for (int u = 0; u < 4; u++) ldq128_keep(v[u], ring_ptr(p, pq + off(n)) + u * 512, ready);
        pr = ld_rlx((const uint32_t*)ring_ptr(p, pp + off(n + ready)));
        ACC(2, have && !ok)
        have = ready;
        if (!ok) {
            ACC(1, 1)
            fin = ld_rlx(fin2_of(p, sb, id) + w);
            if (++guard > GUARD) __trap();
        } else {
#pragma unroll
            for (int u = 0; u < 4; u += 2) {
                uint32_t old[8], chk = 0;
#pragma unroll
                for (int j = 0; j < 4; j++) {
                    old[2 * j] = atoms_add(sb + C_S + row[2 * u + j] * 4, val[4 * u + 2 * j]);
                    old[2 * j + 1] = atoms_add(sb + C_S + ROWS3_MAX * 4 + row[2 * u + j] * 4, val[4 * u + 2 * j + 1]);
                }
#pragma unroll
                for (int j = 0; j < 8; j++) {
                    const uint32_t nw = old[j] + val[4 * u + j];
                    chk |= (old[j] ^ nw) & (val[4 * u + j] ^ nw);
                }
                if (chk & 0x80008000u) {
                    uint32_t tmp[20];
#pragma unroll
                    for (int j = 0; j < 8; j++) { tmp[j >> 1] = row[2 * u + (j >> 1)]; tmp[4 + j] = old[j]; tmp[12 + j] = val[4 * u + j]; }
                    p3_wrap(sb, id, tmp);
                }
            }
            __syncwarp();
            if (last) break;
        }
    }
    ACC_SAVE
}

__device__ __forceinline__ void row_gates(const float* sw, const uint32_t* c2, uint32_t dbits, float4& gs, float4& gr) {
    const uint32_t d2 = dbits * 0x10001u;
    gs = gr = make_float4(0.f, 0.f, 0.f, 0.f);
#pragma unroll
    for (int r2 = 0; r2 < 4; r2++) {
        uint32_t df = sub_bf2(d2, c2[r2]);
        uint32_t ar = mul_bf2(mul_bf2(df, df), 0xC120C120u);
        uint32_t rb = pack_bf2(__expf(bflo(ar)), __expf(bfhi(ar)));
        const float r0 = bflo(rb), r1 = bfhi(rb);
        const float4 s0 = *(const float4*)(sw + r2 * 8), s1 = *(const float4*)(sw + r2 * 8 + 4);
        const float4 q0 = *(const float4*)(sw + 32 + r2 * 8), q1 = *(const float4*)(sw + 32 + r2 * 8 + 4);
        gs.x += r0 * s0.x + r1 * s1.x; gs.y += r0 * s0.y + r1 * s1.y;
        gs.z += r0 * s0.z + r1 * s1.z; gs.w += r0 * s0.w + r1 * s1.w;
        gr.x += r0 * q0.x + r1 * q1.x; gr.y += r0 * q0.y + r1 * q1.y;
        gr.z += r0 * q0.z + r1 * q1.z; gr.w += r0 * q0.w + r1 * q1.w;
    }
}
__device__ __forceinline__ uint2 finish_row(const float* wu, const float4& gs, const float4& gr, const float S[4], uint2 mrow) {
    const float a[4] = {S[0] * gs.x, S[1] * gs.y, S[2] * gs.z, S[3] * gs.w};
    float u[4] = {0, 0, 0, 0};
#pragma unroll
    for (int k = 0; k < 4; k++) {
        u[0] += a[k] * wu[4 * k]; u[1] += a[k] * wu[4 * k + 1]; u[2] += a[k] * wu[4 * k + 2]; u[3] += a[k] * wu[4 * k + 3];
    }
    return make_uint2(pack_bf2(bflo(mrow.x) + u[0] * gr.x, bfhi(mrow.x) + u[1] * gr.y),
                      pack_bf2(bflo(mrow.y) + u[2] * gr.z, bfhi(mrow.y) + u[3] * gr.w));
}
__device__ __forceinline__ void load_tail_weights(const Params& p, float* sw, int tid) {
    if (tid < 32) sw[tid] = __bfloat162float(p.w_sbf[tid]);
    else if (tid < 64) sw[tid] = __bfloat162float(p.w_rbf[tid - 32]);
    else if (tid < 80) sw[tid] = __bfloat162float(p.w_up[tid - 64]);
    else if (tid < 96) sw[tid] = __bfloat162float(p.w_down[tid - 80]);
}
__device__ __forceinline__ float exp_ftz(float x) {
    float r;
    asm("ex2.approx.ftz.f32 %0, %1;" : "=f"(r) : "f"(x * 1.4426950408889634f));
    return r;
}
__device__ __forceinline__ void tail_rows(const Params& p, int tidx, int w, int lane) {
    constexpr uint32_t sb = SB;
    if (w == NW - 1 && lane < 2) {
        fence_gpu();
        red_rlx(rdy_of(p, sb, 320, lane), 1u);
    }
    if (w >= NPC * WPP) return;
    const int pc = w / WPP, r0 = pc * RPC + (tidx * WPP + w - pc * WPP) * 8, e0 = r0 * 32;
    const uint32_t G = sb + T_G + w * 6144;
    auto edge = [&](int k) { return e0 + (lane & 1) * 128 + (lane >> 1) + (k & 3) * 32 + (k >> 2) * 16; };
    {
        const int g = lane >> 2, t = lane & 3;
        uint32_t dv[16];
#pragma unroll
        for (int k = 0; k < 16; k++) dv[k] = __ldg((const uint32_t*)p.dist + min(e0 / 2 + k * 8 + g, p.E / 2 - 1));
        uint2 mv[8];
#pragma unroll
        for (int k = 0; k < 8; k++) mv[k] = __ldg(p.m + min(edge(k), p.E - 1));
        const uint32_t c2 = ((const uint32_t*)p.centers)[t];
        const unsigned short* wg = (const unsigned short*)(g < 4 ? p.w_sbf : p.w_rbf) + t * 8 + (g & 3);
        const uint32_t b = wg[0] | (uint32_t)wg[4] << 16;
#pragma unroll
        for (int k = 0; k < 8; k++) sts64(G + 4096 + (k * 32 + lane) * 8, mv[k].x, mv[k].y);
        TR(19, w == 0 && lane == 0 && dv[15] + b + c2 != 0x12345);
#pragma unroll
        for (int k = 0; k < 16; k++) {
            uint32_t a[2];
#pragma unroll
            for (int h = 0; h < 2; h++) {
                const uint32_t df = sub_bf2(prmt(dv[k], 0, h ? 0x3232 : 0x1010), c2);
                const uint32_t ar = mul_bf2(mul_bf2(df, df), 0xC120C120u);
                a[h] = pack_bf2(exp_ftz(bflo(ar)), exp_ftz(bfhi(ar)));
            }
            float d[4];
            asm("mma.sync.aligned.m16n8k8.row.col.f32.bf16.bf16.f32 {%0,%1,%2,%3}, {%4,%5}, {%6}, {%7,%7,%7,%7};"
                : "=f"(d[0]), "=f"(d[1]), "=f"(d[2]), "=f"(d[3]) : "r"(a[0]), "r"(a[1]), "r"(b), "f"(0.f));
            const uint32_t at = G + (((k & 1) * 4 + (k >> 1 & 3)) * 32 + g * 4 + (k >> 3)) * 16 + t * 4;
            sts32(at, pack_bf2(d[0], d[1]));
            sts32(at + 32, pack_bf2(d[2], d[3]));
        }
    }
    __syncwarp();
    TR(20, w == 0 && lane == 0);
    const Scale sc = get_scale(sb);
    const float lsb[4] = {__uint_as_float((sc.eb[0] - 10) << 23), __uint_as_float((sc.eb[1] - 10) << 23),
                          __uint_as_float((sc.eb[2] - 10) << 23), __uint_as_float((sc.eb[3] - 10) << 23)};
    TR(2, w == 0 && lane == 0);
    uint32_t dirty = 0;
    uint4 sx[2] = {}, sy[2] = {};
#pragma unroll 1
    for (int pass = CFG_DRY ? 0 : 1; pass < 2; pass++) {
        if (pass) {
            if (w == pc * WPP && lane < 2) spin_ge(rdy_of(p, sb, lane ? 320 : 160 + 32 * pc, lds32(sb + SM_MISC + 20)), lane ? NTAIL : N3);
            __syncwarp();
            bar_sync(1 + pc, WPP * 32);
            TR(3, w == 0 && lane == 0);
            TR(10, w == NPC * WPP - 1 && lane == 0);
            if (r0 >= (int)p.rows3) return;
            const uint32_t* const src = &g_S[0][lane >> 1][r0 + (lane & 1) * 4];
#pragma unroll
            for (int u = 0; u < 2; u++) {
                sx[u] = ldg_q128(src + u * 16 * ROWS3_MAX);
                sy[u] = ldg_q128(src + (u * 16 + 32) * ROWS3_MAX);
            }
            if (lane < 8 && (r0 + lane) * 32 < p.E && (dirty = ld_rlx(g_dirty + r0 + lane))) st_rlx(g_dirty + r0 + lane, 0u);
            dirty = __ballot_sync(0xffffffffu, dirty != 0);
        }
        asm volatile("" : "+r"(lane));
        float wu[16];
#pragma unroll
        for (int k = 0; k < 4; k++) *(uint4*)(wu + 4 * k) = lds128(sb + SM_W + 256 + 16 * k);
        auto finish = [&](int k, uint32_t x, uint32_t y, bool extra) {
            const int e = edge(k);
            float S[4];
            const uint32_t tx = x + 0x80008000u, ty = y + 0x80008000u;
            S[0] = (__uint_as_float(prmt(tx, 0x4b000000u, 0x7610)) - 8421376.0f) * lsb[0];
            S[1] = (__uint_as_float(prmt(tx, 0x4b000000u, 0x7632)) - 8421376.0f) * lsb[1];
            S[2] = (__uint_as_float(prmt(ty, 0x4b000000u, 0x7610)) - 8421376.0f) * lsb[2];
            S[3] = (__uint_as_float(prmt(ty, 0x4b000000u, 0x7632)) - 8421376.0f) * lsb[3];
            if (extra && e < p.E) {
                const float4 g = __ldcg(g_Sg + e);
                S[0] += g.x; S[1] += g.y; S[2] += g.z; S[3] += g.w;
                __stcg(g_Sg + e, make_float4(0.f, 0.f, 0.f, 0.f));
            }
            const uint4 g = lds128(G + (k * 32 + lane) * 16);
            const uint2 o = finish_row(wu, make_float4(bflo(g.x), bfhi(g.x), bflo(g.y), bfhi(g.y)), make_float4(bflo(g.z), bfhi(g.z), bflo(g.w), bfhi(g.w)), S,
                                       lds64v(G + 4096 + (k * 32 + lane) * 8));
            asm volatile("{.reg .pred q; setp.ne.u32 q, %3, 0; @q st.global.v2.u32 [%0], {%1,%2};}"
                         ::"l"(p.out + e), "r"(o.x), "r"(o.y), "r"((uint32_t)(pass && e < p.E)));
        };
        const uint32_t xs[8] = {sx[0].x, sx[0].y, sx[0].z, sx[0].w, sx[1].x, sx[1].y, sx[1].z, sx[1].w};
        const uint32_t ys[8] = {sy[0].x, sy[0].y, sy[0].z, sy[0].w, sy[1].x, sy[1].y, sy[1].z, sy[1].w};
        if (!dirty) {
#pragma unroll
            for (int k = 0; k < 8; k++) finish(k, xs[k], ys[k], false);
        } else {
            uint32_t tmp[16];
#pragma unroll
            for (int k = 0; k < 8; k++) { tmp[k] = xs[k]; tmp[8 + k] = ys[k]; }
#pragma unroll 1
            for (int k = 0; k < 8; k++) finish(k, tmp[k], tmp[8 + k], dirty >> ((lane & 1) * 4 + (k & 3)) & 1);
        }
    }
    TR(9, w == 0 && lane == 0);
    TR(11, w == NPC * WPP - 1 && lane == 0);
}

#define CFG_MAP1 1
__global__ void __launch_bounds__(NT, 1) k_main(const __grid_constant__ Params p) {
    extern __shared__ __align__(1024) unsigned char smem[];
    constexpr uint32_t sb = SB;
    if ((uint32_t)__cvta_generic_to_shared(smem) != SB) __trap();
    const int tid = threadIdx.x, w = __shfl_sync(0xffffffffu, tid >> 5, 0), lane = tid & 31;
    if (w < NPROBE) probe(p, sb, w, lane);
    else {
        if (tid == NT - 1) sts32(sb + SM_MISC + 16, ld_rlx(&g_epoch) & 1);
        if (tid >= NT - 32 && lane < 12) sts32(sb + SM_FIN + lane * 4, 0u);
        load_tail_weights(p, (float*)(smem + SM_W), tid - NPROBE * 32);
    }
    const Mat4 wd = load_mat4(p.w_down, lane);
    cta_sync();
    if (w) {
        const uint4 in = __ldg((const uint4*)p.m + (size_t)(tid - 32) * (p.E / 2) / (NT - 32));
        for (int i = SM_DATA / 16 + tid - 32; i < ZEND / 16; i += NT - 32) ((uint4*)smem)[i] = make_uint4(0, 0, 0, 0);
        if (tid - 32 < 256) ((uint4*)(smem + SM_ZERO))[tid - 32] = make_uint4(0, 0, 0, 0);
        if (tid < 48) sts32(sb + SM_CNT2 + (tid - 32) * 4, NQ2 << 16);
        __syncwarp();
        if (CFG_PFD && tid == NT - 1) {
            __nanosleep(CFG_PFD);
            const uint32_t n = (p.E / 2 + NCTA - 1) / NCTA, o = blockIdx.x * n;
            if (o < (uint32_t)p.E / 2) asm volatile("cp.async.bulk.prefetch.L2.global [%0], %1;" ::"l"((const uint4*)p.m + o), "r"(min(n, p.E / 2 - o) * 16) : "memory");
        }
        __syncwarp();
        md_stats(in, wd, lane);
    } else assign_role(p, sb, lane);
    if (tid == 0) {
        mbar_init(sb + SM_DONE, lds32(sb + SM_MISC) >> 8 ? P2W : P1W);
    }
    cta_sync();
    const uint32_t rid = __shfl_sync(0xffffffffu, lds32(sb + SM_MISC), 0);
    const int role = rid >> 8, id = rid & 255;
    TR(5, tid == 0);
    if (role == 0) {
        const int ww = CFG_MAP1 == 0 ? ((w & 3) == 3 ? NW : (w >> 2) * 3 + (w & 3)) : CFG_MAP1 == 1 ? (w & 2 ? NW : (w >> 2) * 2 + (w & 1)) : w;
        const int sw = CFG_MAP1 == 0 ? ((w & 3) == 3 ? w >> 2 : NW) : CFG_MAP1 == 1 ? (w & 2 ? (w >> 2) * 2 + (w & 1) : NW) : w - P1W;
        static_assert(CFG_MAP1 == 0 ? (P1W <= NW / 4 * 3 && NF + 2 <= NW / 4) : CFG_MAP1 == 1 ? (P1W <= NW / 2 && NF + 2 <= NW / 2) : true, "warp map");
        for (int i = tid; i < NB; i += NT) sts32(sb + A_CNT + i * 4, 1u << 24);
        cta_sync();
        TR(1, tid == 0);
        if (ww < P1W) role_p1(p, sb, id, ww, lane);
        else if (sw < NF) role_flush(p, sb, id, sw, lane);
        else if (w == NW - 1) {
            uint4* owin = (uint4*)(p.ring + (CWIN + (lds32(sb + SM_MISC + 16) ^ 1)) * WIN);
            for (int i = id * 32 + lane; i < CPAIRS * 512; i += N1 * 32) __stcg(owin + i, make_uint4(0, 0, 0, 0));
            __syncwarp();
        }
    } else if (role == 1) {
        const int row0 = id % H2 * p.rows2;
        const int nrows = min((int)p.rows2, p.E - row0);
        constexpr int NTB = NT - 32, TBD = CFG_TBD;
        bool flagged = false;
        if (w < NW - 1) {
            const Scale sc = get_scale(sb);
            Mat4 ws;
#pragma unroll
            for (int k = 0; k < 4; k++) ws.b[k] = mul_bf2(wd.b[k], ((246u - (lane & 4 ? sc.eb[(k & 2) + 1] : sc.eb[k & 2])) << 7) * 0x10001u);
            const uint4* const src = (const uint4*)(p.m + row0);
            uint4 r2[TBD], nx[TBD];
            auto fetch = [&](int i) {
#pragma unroll
                for (int k = 0; k < TBD; k++)
                    asm volatile("ld.global.nc.v4.u32 {%0,%1,%2,%3}, [%4];" : "=r"(nx[k].x), "=r"(nx[k].y), "=r"(nx[k].z), "=r"(nx[k].w) : "l"(src + min(i + k * NTB, nrows / 2 - 1)));
            };
            fetch(tid);
#pragma unroll 1
            for (int i0 = tid; 2 * (i0 - lane) < nrows; i0 += TBD * NTB) {
#pragma unroll
                for (int k = 0; k < TBD; k++) r2[k] = make_uint4(nx[k].x, nx[k].z, nx[k].y, nx[k].w);
                fetch(i0 + TBD * NTB);
#pragma unroll
                for (int k = 0; k < TBD; k++) {
                    const int i = i0 + k * NTB;
                    float y[8];
                    mul4(make_uint4(r2[k].x, r2[k].z, r2[k].y, r2[k].w), ws, y);
                    uint32_t a[4], h[4], ta[2];
#pragma unroll
                    for (int j = 0; j < 4; j++) { a[j] = pack_h2(y[2 * j], y[2 * j + 1]); h[j] = a[j] + 0x00040004u; }
#pragma unroll
                    for (int j = 0; j < 2; j++) ta[j] = bitsel(h[2 * j], bitsel(h[2 * j + 1] >> 3, h[2 * j + 1] << 7, 0x00070007u), 0x9ff89ff8u);
                    uint32_t tb = prmt(h[1], h[3], 0x7531);
                    const uint32_t b0 = a[0] | a[1] | h[0] | h[1], b1 = a[2] | a[3] | h[2] | h[3];
                    if (__any_sync(0xffffffffu, ((b0 | b1) & 0x60006000u) || sc.allslow)) {
                        if ((b0 & 0x60006000u) || sc.allslow) { ta[0] = 0; tb = (tb & 0xffff0000u) | 0x40u; }
                        if ((b1 & 0x60006000u) || sc.allslow) { ta[1] = 0; tb = (tb & 0xffffu) | 0x400000u; }
                        flagged = true;
                    }
                    sts64_if(sb + B_TA + i * 8, ta[0], ta[1], 2 * i < nrows);
                    sts32_if(sb + B_TB + i * 4, tb, 2 * i < nrows);
                }
            }
            if (tid == 0) {
                sts32(sb + B_TA + p.rows2 * 4, 0u);
                sts16(sb + B_TB + p.rows2 * 2, 0u);
            }
            TR(8, tid == 0);
        } else if (lane == 0) spin_ge(rdy_of(p, sb, id, id / H2), H3);
        __syncwarp();
        flagged = __any_sync(0xffffffffu, __syncthreads_or(flagged));
        TR(1, tid == 0);
        if (w < P2W) {
            if (flagged) role_p2<true>(p, sb, id, w, lane);
            else role_p2<false>(p, sb, id, w, lane);
        } else if (w == P2W) role_credit(p, sb, id, lane);
    } else {
        if (w == 0) clear_queues<false>(p, sb, id, lane);
        if (tid >= 32 && tid < 33 + NPC) mbar_init(sb + SM_CNT2 + (tid - 32) * 8, 1);
        cta_sync();
        TR(1, tid == 0);
        if (w < P3W) role_p3(p, sb, id, w, lane);
        cta_sync();
        TR(2, tid == 0);
        if (w < NPC && lane == 0) {
            fence_async_smem();
            const int n = min(((int)p.rows3 + 7) / 8 * 8 - w * RPC, RPC);
            if (w) mbar_wait(sb + SM_CNT2 + w * 8, 0);
            if (n > 0) {
                bulk_store(g_S[0][id] + w * RPC, sb + C_S + w * RPC * 4, n * 4);
                bulk_store(g_S[1][id] + w * RPC, sb + C_S + (ROWS3_MAX + w * RPC) * 4, n * 4);
            }
            asm volatile("cp.async.bulk.commit_group;" ::: "memory");
            asm volatile("cp.async.bulk.wait_group.read 0;" ::: "memory");
            mbar_arrive(sb + SM_CNT2 + w * 8 + 8);
            asm volatile("cp.async.bulk.wait_group 0;" ::: "memory");
            fence_gpu();
            red_rlx(rdy_of(p, sb, 160 + 32 * w, 0), 1u);
            red_rlx(rdy_of(p, sb, 160 + 32 * w, 1), 1u);
            if (id == 0 && w == 0) red_rlx(&g_epoch, 1u);
            TR(12 + w, true);
        }
        return;
    }
    cta_sync();
    TR(18, tid == 0 && role == 1);
    if (role == 0 && w == NW - 2) clear_queues<true>(p, sb, id, lane);
    tail_rows(p, role * N1 + id, w, lane);
}

__global__ void k_direct(const Params p, long long T) {
    float wd[16];
#pragma unroll
    for (int i = 0; i < 16; i++) wd[i] = __bfloat162float(p.w_down[i]);
    const float f = __bfloat162float(p.freq[0]);
    for (long long t = blockIdx.x * (long long)blockDim.x + threadIdx.x; t < T; t += (long long)gridDim.x * blockDim.x) {
        float x = __bfloat162float(__float2bfloat16(f * __bfloat162float(p.angle[t])));
        float c = __bfloat162float(__float2bfloat16(cosf(x)));
        uint2 md = down_row(__ldg(p.m + p.idx_in[t]), wd);
        red_v4(g_Sg + p.idx_out[t], c * bflo(md.x), c * bfhi(md.x), c * bflo(md.y), c * bfhi(md.y));
    }
}
__global__ void k_direct_tail(const Params p) {
    __shared__ __align__(16) float sw[96];
    load_tail_weights(p, sw, threadIdx.x);
    __syncthreads();
    uint32_t c2[4];
#pragma unroll
    for (int i = 0; i < 4; i++) c2[i] = ((const uint32_t*)p.centers)[i];
    for (int e = blockIdx.x * blockDim.x + threadIdx.x; e < p.E; e += gridDim.x * blockDim.x) {
        float4 g = __ldcg(g_Sg + e);
        __stcg(g_Sg + e, make_float4(0.f, 0.f, 0.f, 0.f));
        const float Sv[4] = {g.x, g.y, g.z, g.w};
        float4 gs, gr;
        row_gates(sw, c2, __bfloat16_as_ushort(p.dist[e]), gs, gr);
        p.out[e] = finish_row(sw + 64, gs, gr, Sv, __ldg(p.m + e));
    }
}

static bool pick_rows(int E, int n, int rows_max, int mult, uint32_t* rows, uint32_t* magic) {
    for (uint32_t r = (E + n - 1) / n; r <= (uint32_t)rows_max; r++) {
        if (r < 2 || r % mult) continue;
        uint64_t mg = ((1ull << 32) + r - 1) / r;
        uint64_t err = mg * r - (1ull << 32);
        if (err * (uint64_t)n < mg) { *rows = r; *magic = (uint32_t)mg; return true; }
    }
    return false;
}

}

extern "C" void kernel_launch(void* const* d_in, const int* in_sizes, int n_in, void* d_out, int out_size) {
    using namespace gs;
    (void)n_in; (void)out_size;
    Params p;
    p.m = (const uint2*)d_in[0];
    p.idx_in = (const int*)d_in[1];
    p.idx_out = (const int*)d_in[2];
    p.dist = (const __nv_bfloat16*)d_in[3];
    p.angle = (const __nv_bfloat16*)d_in[4];
    p.centers = (const __nv_bfloat16*)d_in[5];
    p.freq = (const __nv_bfloat16*)d_in[6];
    p.w_rbf = (const __nv_bfloat16*)d_in[7];
    p.w_sbf = (const __nv_bfloat16*)d_in[8];
    p.w_down = (const __nv_bfloat16*)d_in[9];
    p.w_up = (const __nv_bfloat16*)d_in[10];
    p.out = (uint2*)d_out;
    p.E = in_sizes[3];
    const long long T = in_sizes[1];
    p.n4 = (int)(T / 4);
    p.rows2 = p.magic2 = 0;
    p.ring = nullptr;

    static int sms = 0, rsv = 0;
    if (!sms) {
        int dev = 0;
        cudaGetDevice(&dev);
        cudaDeviceGetAttribute(&rsv, cudaDevAttrReservedSharedMemoryPerBlock, dev);
        cudaDeviceGetAttribute(&sms, cudaDevAttrMultiProcessorCount, dev);
        cudaFuncSetAttribute(k_main, cudaFuncAttributeMaxDynamicSharedMemorySize, SMEM_BYTES);
    }
    cudaStream_t st = cudaStreamPerThread;
    bool fast = (T % 4 == 0) && T > 0 && sms >= NCTA && rsv == (int)SB && p.E >= 65536 && p.E <= E_MAX &&
                p.E % 4 == 0 && (((uintptr_t)p.m | (uintptr_t)p.idx_in | (uintptr_t)p.idx_out | (uintptr_t)p.angle) & 15) == 0 &&
                pick_rows(p.E, NI, ROWS2_MAX, 2, &p.rows2, &p.magic2);
    p.c1 = 1;
    p.nrows2 = 0u - p.rows2;
    p.rows3 = (p.E + 31) / 32;
    fast = fast && (p.rows2 * (NI - 1) + 2 <= (uint32_t)p.E);
    static const void* tkey[3] = {nullptr, nullptr, nullptr};
    static cudaTextureObject_t tex[3] = {0, 0, 0};
    static long long tlen = -1;
    const void* tptr[3] = {p.idx_in, p.idx_out, p.angle};
    for (int k = 0; fast && k < 3; k++) {
        if (tkey[k] == tptr[k] && tlen == T) continue;
        if (tkey[k]) cudaDestroyTextureObject(tex[k]);
        tkey[k] = nullptr;
        cudaResourceDesc rd = {};
        rd.resType = cudaResourceTypeLinear;
        rd.res.linear.devPtr = (void*)tptr[k];
        rd.res.linear.desc = cudaCreateChannelDesc(32, 32, k < 2 ? 32 : 0, k < 2 ? 32 : 0, cudaChannelFormatKindUnsigned);
        rd.res.linear.sizeInBytes = (size_t)T * (k < 2 ? 4 : 2);
        cudaTextureDesc td = {};
        td.readMode = cudaReadModeElementType;
        if (cudaCreateTextureObject(&tex[k], &rd, &td, nullptr) == cudaSuccess) tkey[k] = tptr[k];
        else { (void)cudaGetLastError(); fast = false; }
    }
    if (fast) tlen = T;
    p.t_in = tex[0]; p.t_out = tex[1]; p.t_ang = tex[2];
    if (fast) {
        void* ring = nullptr;
        cudaGetSymbolAddress(&ring, g_ring);
        uintptr_t a = ((uintptr_t)ring + WIN - 1) & ~(uintptr_t)(WIN - 1);
        if (a >> 32 != (a + RING_BYTES - 1) >> 32) a += RING_BYTES;
        p.ring = (unsigned char*)a;
        p.ring_lo = (uint32_t)a;
        p.ring_hi = (uint32_t)(a >> 32);
        k_main<<<NCTA, NT, SMEM_BYTES, st>>>(p);
    } else {
        k_direct<<<sms * 8, 256, 0, st>>>(p, T);
        k_direct_tail<<<sms * 4, 256, 0, st>>>(p);
    }
}
```

```cpp
#include <cuda_runtime.h>
#include <cuda_bf16.h>
#include <stdint.h>

#define CFG_N1 56
#define CFG_NI 22
#define CFG_NW 28
#define CFG_P1W 14
#define CFG_GPW 2
#define CFG_KR 1
#define CFG_SMPAD 0
#define CFG_QPW 3
#define CFG_TG 2
#define CFG_PMASK 8
#define CFG_PSTREAK 1
#define CFG_NBT 1
#define CFG_KM 5
#define CFG_KN 9
#define CFG_TBD 4
#define CFG_P0 500
#define CFG_NTK 16
#define CFG_PFD 200
#define CFG_CRE 0
#define CFG_TH 10
#define CFG_TS 300
#define CFG_POLL 64
#define CFG_HINT 20000
#define CFG_BSLEEP 100
#define CFG_CSLEEP 200
#define CFG_FSLEEP 100
#define CFG_PSLEEP 100
#define CFG_DRY 1
#define CFG_PROBES 4

namespace gs {

constexpr int E_MAX = 640000;
constexpr int N1 = CFG_N1, NI = CFG_NI, N2 = 2 * NI, N3 = 32, NCTA = N1 + N2 + N3;
constexpr int H2 = NI, H3 = N3 / 2;
constexpr int NB = NI * N3;
constexpr int NW = CFG_NW, NT = NW * 32;
constexpr int GPW = CFG_GPW, NF = NI / GPW;
constexpr int QPW = CFG_QPW, NBT = CFG_NBT;
constexpr int P1W = CFG_P1W, P2W = (N1 + QPW - 1) / QPW, P3W = NI;
constexpr int NQ1 = 32, NQ2 = 64;
constexpr int ROWS2_MAX = ((E_MAX + NI - 1) / NI + 31) / 8 * 8;
constexpr int ROWS3_MAX = (E_MAX / 32 + 31) / 32 * 32;
constexpr int NTAIL = N1 + N2;
constexpr int NPC = 5, WPP = 5, RPC = NTAIL * WPP * 8;
constexpr int GUARD = 1 << 26;
static_assert(NCTA % 4 == 0 && NCTA <= 192, "roles come in CTA pairs, per partition");
static_assert(NI % GPW == 0 && (GPW == 2 || GPW == 4) && QPW >= NBT && QPW <= 4 && NI <= 32 && N1 <= 62, "queue ownership");
static_assert(P1W + NF + 2 <= NW && P2W + 2 <= NW && P3W + 1 <= NW && P1W * 256 + 64 < 8192, "warp roles");
static_assert(ROWS2_MAX + 8 <= 32768 && ROWS3_MAX <= 32768, "index bits");

constexpr uint32_t SB = 1024;
constexpr int SM_DONE = 0;
constexpr int SM_MISC = 16;
constexpr int SM_FIN = 48;
constexpr int SM_STAT = 64;
constexpr int SM_CNT2 = 128;
constexpr int SM_W = 256;
constexpr int SM_PUB = SM_W + 384;
constexpr int SM_PROBE = SM_PUB + 768;
constexpr int SM_DATA = 2048;
constexpr int cmax(int a, int b) { return a > b ? a : b; }
constexpr int A_CNT = SM_DATA;
constexpr int A_LIST = A_CNT + NB * 4;
constexpr int KR = CFG_KR, LISTH = (GPW * 16 + 4 * KR + 31) / 32 * 128 + 16, LISTB = 2 * LISTH;
constexpr int A_ST = (A_LIST + NF * LISTB + 127) / 128 * 128;
constexpr int A_END = A_ST + NB * 256;
constexpr int B_TA = SM_DATA;
constexpr int B_TB = B_TA + (ROWS2_MAX + 8) * 4;
constexpr int B_END = B_TB + (ROWS2_MAX + 8) * 2;
constexpr int C_S = SM_DATA;
constexpr int C_END = C_S + ROWS3_MAX * 8;
constexpr int T_G = SM_DATA, T_END = T_G + NPC * WPP * 6144;
constexpr int ZEND = cmax(A_END, C_END);
constexpr int SM_ZERO = (cmax(cmax(A_END, B_END), cmax(C_END, T_END)) + 127) / 128 * 128;
constexpr int SMEM_BYTES = SM_ZERO + 4096 + CFG_SMPAD;
static_assert(SMEM_BYTES <= 232448 && SM_PROBE + 128 <= SM_DATA, "shared memory");
static_assert(NPC * RPC >= ROWS3_MAX && NPC * WPP + 2 <= NW, "tail");

constexpr uint32_t FIN = 0x80000000u;

constexpr uint32_t WIN = 524288;
constexpr int CWIN = N2 + N3, NWIN = CWIN + 2, CPAIRS = 31;
constexpr uint32_t PROBE_OFF = (uint32_t)NWIN * WIN;
constexpr int NPROBE = 16;
static_assert(NWIN <= NCTA && NPROBE <= NW, "windows");
constexpr size_t RING_BYTES = (size_t)PROBE_OFF + WIN;
__device__ __align__(128) unsigned char g_ring[2 * RING_BYTES + WIN];
__device__ __align__(128) uint32_t g_S[2][32][ROWS3_MAX];
__device__ __align__(128) float4 g_Sg[E_MAX];
__device__ uint32_t g_dirty[E_MAX / 32];
__device__ uint32_t g_epoch;

#define TR(ev, on)
#define ACC_DECL
#define ACC(i, n)
#define ACC_SAVE

struct Params {
    const uint2* m;
    const int* idx_in;
    const int* idx_out;
    const __nv_bfloat16* dist;
    const __nv_bfloat16* angle;
    const __nv_bfloat16* centers;
    const __nv_bfloat16* freq;
    const __nv_bfloat16* w_rbf;
    const __nv_bfloat16* w_sbf;
    const __nv_bfloat16* w_down;
    const __nv_bfloat16* w_up;
    uint2* out;
    unsigned char* ring;
    cudaTextureObject_t t_in, t_out, t_ang;
    int E, n4;
    uint32_t rows2, nrows2, magic2, rows3;
    uint32_t ring_lo, ring_hi, c1;
};

__device__ __forceinline__ float bflo(uint32_t w) { return __uint_as_float(w << 16); }
__device__ __forceinline__ float bfhi(uint32_t w) { return __uint_as_float(w & 0xffff0000u); }
__device__ __forceinline__ uint32_t pack_bf2(float lo, float hi) {
    uint32_t r;
    asm("cvt.rn.bf16x2.f32 %0, %1, %2;" : "=r"(r) : "f"(hi), "f"(lo));
    return r;
}
__device__ __forceinline__ uint32_t mul_bf2(uint32_t a, uint32_t b) {
    uint32_t r;
    asm("mul.rn.bf16x2 %0, %1, %2;" : "=r"(r) : "r"(a), "r"(b));
    return r;
}
__device__ __forceinline__ uint32_t sub_bf2(uint32_t a, uint32_t b) {
    uint32_t r;
    asm("sub.rn.bf16x2 %0, %1, %2;" : "=r"(r) : "r"(a), "r"(b));
    return r;
}
__device__ __forceinline__ uint32_t maxabs_bf2(uint32_t a, uint32_t b) {
    uint32_t r;
    asm("max.NaN.xorsign.abs.bf16x2 %0, %1, %2;" : "=r"(r) : "r"(a), "r"(b));
    return r;
}
__device__ __forceinline__ void mbar_init(uint32_t a, uint32_t n) {
    asm volatile("mbarrier.init.shared::cta.b64 [%0], %1;" ::"r"(a), "r"(n) : "memory");
}
__device__ __forceinline__ void mbar_arrive(uint32_t a) {
    asm volatile("mbarrier.arrive.shared::cta.b64 _, [%0];" ::"r"(a) : "memory");
}
__device__ __forceinline__ void mbar_arrive_n(uint32_t a, uint32_t n) {
    asm volatile("mbarrier.arrive.shared::cta.b64 _, [%0], %1;" ::"r"(a), "r"(n) : "memory");
}
__device__ __forceinline__ void mbar_arrive_if(uint32_t a, bool on) {
    asm volatile("{.reg .pred q; setp.ne.u32 q, %1, 0; @q mbarrier.arrive.shared::cta.b64 _, [%0];}" ::"r"(a), "r"((uint32_t)on) : "memory");
}
__device__ __forceinline__ void mbar_wait(uint32_t a, uint32_t parity) {
    uint32_t ok;
    int guard = 0;
    do {
        asm volatile("{.reg .pred p; mbarrier.try_wait.parity.shared::cta.b64 p, [%1], %2, %3; selp.u32 %0, 1, 0, p;}"
                     : "=r"(ok) : "r"(a), "r"(parity), "r"(CFG_HINT) : "memory");
        if (!ok) {
            if (++guard > GUARD) __trap();
        }
    } while (!ok);
}
__device__ __forceinline__ void cta_sync() { __syncwarp(); __syncthreads(); }
__device__ __forceinline__ void bar_sync(int id, int n) { asm volatile("bar.sync %0, %1;" ::"r"(id), "r"(n) : "memory"); }
__device__ __forceinline__ void bar_arrive(int id, int n) { asm volatile("bar.arrive %0, %1;" ::"r"(id), "r"(n) : "memory"); }
__device__ __forceinline__ bool mbar_test(uint32_t a, uint32_t parity) {
    uint32_t ok;
    asm volatile("{.reg .pred p; mbarrier.test_wait.parity.shared::cta.b64 p, [%1], %2; selp.u32 %0, 1, 0, p;}"
                 : "=r"(ok) : "r"(a), "r"(parity) : "memory");
    return ok;
}
__device__ __forceinline__ uint32_t ld_acq(const uint32_t* p) {
    uint32_t v;
    asm volatile("ld.acquire.gpu.global.u32 %0, [%1];" : "=r"(v) : "l"(p) : "memory");
    return v;
}
__device__ __forceinline__ uint32_t ld_rlx(const uint32_t* p) {
    uint32_t v;
    asm volatile("ld.relaxed.gpu.global.u32 %0, [%1];" : "=r"(v) : "l"(p) : "memory");
    return v;
}
__device__ __forceinline__ void st_rlx(uint32_t* p, uint32_t v) {
    asm volatile("st.relaxed.gpu.global.u32 [%0], %1;" ::"l"(p), "r"(v) : "memory");
}
__device__ __forceinline__ void red_rlx(uint32_t* p, uint32_t v) {
    asm volatile("red.relaxed.gpu.global.add.u32 [%0], %1;" ::"l"(p), "r"(v) : "memory");
}
__device__ __forceinline__ bool elect_one() {
    uint32_t p;
    asm volatile("{.reg .pred P; elect.sync _|P, 0xffffffff; selp.u32 %0, 1, 0, P;}" : "=r"(p));
    return p;
}
__device__ __forceinline__ uint32_t spin_ge(const uint32_t* p, uint32_t target) {
    int guard = 0;
    while (ld_rlx(p) < target) {
        __nanosleep(CFG_POLL);
        if (++guard > GUARD) __trap();
    }
    return ld_acq(p);
}
__device__ __forceinline__ void fence_gpu() { asm volatile("fence.acq_rel.gpu;" ::: "memory"); }
__device__ __forceinline__ void fence_async_smem() { asm volatile("fence.proxy.async.shared::cta;" ::: "memory"); }
__device__ __forceinline__ void fence_async_all() { asm volatile("fence.proxy.async;" ::: "memory"); }
__device__ __forceinline__ void bulk_store(void* g, uint32_t s, uint32_t bytes) {
    asm volatile("cp.async.bulk.global.shared::cta.bulk_group [%0], [%1], %2;" ::"l"(g), "r"(s), "r"(bytes) : "memory");
}
__device__ __forceinline__ void cp16(uint32_t s, const void* g, bool on) {
    asm volatile("{.reg .pred q; setp.ne.u32 q, %2, 0; @q cp.async.cg.shared.global [%0], [%1], 16;}" ::"r"(s), "l"(g), "r"((uint32_t)on) : "memory");
}
__device__ __forceinline__ void cp_commit() { asm volatile("cp.async.commit_group;" ::: "memory"); }
template <int N> __device__ __forceinline__ void cp_wait() { asm volatile("cp.async.wait_group %0;" ::"n"(N) : "memory"); }
__device__ __forceinline__ uint32_t atoms_add(uint32_t a, uint32_t v) {
    uint32_t o;
    asm volatile("atom.shared.add.u32 %0, [%1], %2;" : "=r"(o) : "r"(a), "r"(v) : "memory");
    return o;
}
__device__ __forceinline__ void sts32(uint32_t a, uint32_t v) { asm volatile("st.shared.u32 [%0], %1;" ::"r"(a), "r"(v) : "memory"); }
__device__ __forceinline__ void sts16(uint32_t a, uint32_t v) { asm volatile("st.shared.u16 [%0], %1;" ::"r"(a), "h"((uint16_t)v) : "memory"); }
__device__ __forceinline__ void sts64(uint32_t a, uint32_t x, uint32_t y) { asm volatile("st.shared.v2.u32 [%0], {%1,%2};" ::"r"(a), "r"(x), "r"(y) : "memory"); }
__device__ __forceinline__ uint32_t lds32(uint32_t a) {
    uint32_t v;
    asm volatile("ld.shared.u32 %0, [%1];" : "=r"(v) : "r"(a) : "memory");
    return v;
}
__device__ __forceinline__ uint2 lds64(uint32_t a) {
    uint2 v;
    asm volatile("ld.shared.v2.u32 {%0,%1}, [%2];" : "=r"(v.x), "=r"(v.y) : "r"(a));
    return v;
}
__device__ __forceinline__ uint2 lds64v(uint32_t a) {
    uint2 v;
    asm volatile("ld.volatile.shared.v2.u32 {%0,%1}, [%2];" : "=r"(v.x), "=r"(v.y) : "r"(a) : "memory");
    return v;
}
__device__ __forceinline__ uint32_t lds32v(uint32_t a) {
    uint32_t v;
    asm volatile("ld.volatile.shared.u32 %0, [%1];" : "=r"(v) : "r"(a) : "memory");
    return v;
}
__device__ __forceinline__ uint4 lds128(uint32_t a) {
    uint4 v;
    asm volatile("ld.shared.v4.u32 {%0,%1,%2,%3}, [%4];" : "=r"(v.x), "=r"(v.y), "=r"(v.z), "=r"(v.w) : "r"(a) : "memory");
    return v;
}
__device__ __forceinline__ void sts128(uint32_t a, uint4 v) {
    asm volatile("st.shared.v4.u32 [%0], {%1,%2,%3,%4};" ::"r"(a), "r"(v.x), "r"(v.y), "r"(v.z), "r"(v.w) : "memory");
}
#define LD_Q "ld.relaxed.gpu.global"
__device__ __forceinline__ uint4 ldg_q128(const void* p) {
    uint4 v;
    asm volatile(LD_Q ".v4.u32 {%0,%1,%2,%3}, [%4];"
                 : "=r"(v.x), "=r"(v.y), "=r"(v.z), "=r"(v.w) : "l"(p) : "memory");
    return v;
}
__device__ __forceinline__ uint2 ldg_q64(const void* p) {
    uint2 v;
    asm volatile(LD_Q ".v2.u32 {%0,%1}, [%2];" : "=r"(v.x), "=r"(v.y) : "l"(p) : "memory");
    return v;
}
__device__ __forceinline__ void red_v4(float4* p, float a, float b, float c, float d) {
    asm volatile("red.global.add.v4.f32 [%0], {%1,%2,%3,%4};" ::"l"(p), "f"(a), "f"(b), "f"(c), "f"(d) : "memory");
}
__device__ __forceinline__ uint2 down_row(uint2 r, const float* wd) {
    float x0 = bflo(r.x), x1 = bfhi(r.x), x2 = bflo(r.y), x3 = bfhi(r.y);
    float y[4];
#pragma unroll
    for (int j = 0; j < 4; j++) y[j] = x0 * wd[j] + x1 * wd[4 + j] + x2 * wd[8 + j] + x3 * wd[12 + j];
    return make_uint2(pack_bf2(y[0], y[1]), pack_bf2(y[2], y[3]));
}
__device__ __forceinline__ uint32_t prmt(uint32_t a, uint32_t b, uint32_t s) {
    uint32_t r;
    asm("prmt.b32 %0, %1, %2, %3;" : "=r"(r) : "r"(a), "r"(b), "r"(s));
    return r;
}
__device__ __forceinline__ uint32_t bitsel(uint32_t a, uint32_t b, uint32_t m) {
    uint32_t r;
    asm("lop3.b32 %0, %1, %2, %3, 0xE4;" : "=r"(r) : "r"(a), "r"(b), "r"(m));
    return r;
}
__device__ __forceinline__ uint32_t pack_h2(float lo, float hi) {
    uint32_t r;
    asm("cvt.rn.f16x2.f32 %0, %1, %2;" : "=r"(r) : "f"(hi), "f"(lo));
    return r;
}
__device__ __forceinline__ uint32_t mul_h2(uint32_t a, uint32_t b) {
    uint32_t r;
    asm("mul.rn.f16x2 %0, %1, %2;" : "=r"(r) : "r"(a), "r"(b));
    return r;
}
__device__ __forceinline__ uint32_t lds32nv(uint32_t a) {
    uint32_t v;
    asm volatile("ld.shared.u32 %0, [%1];" : "=r"(v) : "r"(a));
    return v;
}
__device__ __forceinline__ uint32_t lds16nv(uint32_t a) {
    uint32_t v;
    asm volatile("ld.shared.u16 %0, [%1];" : "=r"(v) : "r"(a));
    return v;
}
#define X_CR1
#define X_CR2
#define X_ST1
#define X_ST2
#define ST_Q "st.relaxed.gpu.global"
__device__ __forceinline__ void stg_q128(void* p, uint32_t a, uint32_t b, uint32_t c, uint32_t d, bool on) {
    asm volatile("{.reg .pred q; setp.ne.u32 q, %5, 0; @q " ST_Q ".v4.u32 [%0], {%1,%2,%3,%4};}"
                 ::"l"(p), "r"(a), "r"(b), "r"(c), "r"(d), "r"((uint32_t)on) : "memory");
}
__device__ __forceinline__ void stg_q64(void* p, uint32_t a, uint32_t b, bool on) {
    asm volatile("{.reg .pred q; setp.ne.u32 q, %3, 0; @q " ST_Q ".v2.u32 [%0], {%1,%2};}"
                 ::"l"(p), "r"(a), "r"(b), "r"((uint32_t)on) : "memory");
}
__device__ __forceinline__ void st_rlx_if(uint32_t* p, uint32_t v, bool on) {
    asm volatile("{.reg .pred q; setp.ne.u32 q, %2, 0; @q st.relaxed.gpu.global.u32 [%0], %1;}" ::"l"(p), "r"(v), "r"((uint32_t)on) : "memory");
}
__device__ __forceinline__ uint32_t ld_rlx_if(const uint32_t* p, bool on) {
    uint32_t v;
    asm volatile("{.reg .pred q; setp.ne.u32 q, %2, 0; mov.b32 %0, 0; @q ld.relaxed.gpu.global.u32 %0, [%1];}" : "=&r"(v) : "l"(p), "r"((uint32_t)on) : "memory");
    return v;
}
__device__ __forceinline__ void ldq128_keep(uint4& v, const void* p, bool on) {
    asm volatile("{.reg .pred q; setp.ne.u32 q, %5, 0; @q ld.relaxed.gpu.global.v4.u32 {%0,%1,%2,%3}, [%4];}"
                 : "+r"(v.x), "+r"(v.y), "+r"(v.z), "+r"(v.w) : "l"(p), "r"((uint32_t)on) : "memory");
}
__device__ __forceinline__ void ldq64_keep(uint2& v, const void* p, bool on) {
    asm volatile("{.reg .pred q; setp.ne.u32 q, %3, 0; @q ld.relaxed.gpu.global.v2.u32 {%0,%1}, [%2];}"
                 : "+r"(v.x), "+r"(v.y) : "l"(p), "r"((uint32_t)on) : "memory");
}
__device__ __forceinline__ void atoms_add_keep(uint32_t& o, uint32_t a, uint32_t v, bool on) {
    asm volatile("{.reg .pred q; setp.ne.u32 q, %3, 0; @q atom.shared.add.u32 %0, [%1], %2;}" : "+r"(o) : "r"(a), "r"(v), "r"((uint32_t)on) : "memory");
}
__device__ __forceinline__ void reds_add(uint32_t a, uint32_t v) { asm volatile("red.shared.add.u32 [%0], %1;" ::"r"(a), "r"(v) : "memory"); }
__device__ __forceinline__ void sts32_if(uint32_t a, uint32_t v, bool on) {
    asm volatile("{.reg .pred q; setp.ne.u32 q, %2, 0; @q st.shared.u32 [%0], %1;}" ::"r"(a), "r"(v), "r"((uint32_t)on) : "memory");
}
__device__ __forceinline__ void sts64_if(uint32_t a, uint32_t x, uint32_t y, bool on) {
    asm volatile("{.reg .pred q; setp.ne.u32 q, %3, 0; @q st.shared.v2.u32 [%0], {%1,%2};}" ::"r"(a), "r"(x), "r"(y), "r"((uint32_t)on) : "memory");
}
__device__ __forceinline__ void lds128_keep(uint4& v, uint32_t a, bool on) {
    asm volatile("{.reg .pred q; setp.ne.u32 q, %5, 0; @q ld.volatile.shared.v4.u32 {%0,%1,%2,%3}, [%4];}"
                 : "+r"(v.x), "+r"(v.y), "+r"(v.z), "+r"(v.w) : "r"(a), "r"((uint32_t)on) : "memory");
}
__device__ __forceinline__ void or3_if(uint32_t& x, uint32_t a, uint32_t b, bool on) {
    asm("{.reg .pred q; setp.ne.u32 q, %3, 0; @q lop3.b32 %0, %0, %1, %2, 0xfe;}" : "+r"(x) : "r"(a), "r"(b), "r"((uint32_t)on));
}
__device__ __forceinline__ uint32_t clk() {
    uint32_t t;
    asm volatile("mov.u32 %0, %%clock;" : "=r"(t) :: "memory");
    return t;
}
__device__ __forceinline__ void sg_add(int row, float a, float b, float c, float d) {
    red_v4(g_Sg + row, a, b, c, d);
    st_rlx(g_dirty + (row >> 5), 1u);
}
__device__ __forceinline__ void slow_add(const uint2* m, uint32_t sb, int in, int out, float c) {
    const uint2 r = __ldg(m + in);
    const float x[4] = {bflo(r.x), bfhi(r.x), bflo(r.y), bfhi(r.y)};
    float y[4] = {0.f, 0.f, 0.f, 0.f};
#pragma unroll
    for (int k = 0; k < 4; k++) {
        const uint4 q = lds128(sb + SM_W + 320 + k * 16);
        y[0] = k ? y[0] + x[k] * __uint_as_float(q.x) : x[k] * __uint_as_float(q.x);
        y[1] = k ? y[1] + x[k] * __uint_as_float(q.y) : x[k] * __uint_as_float(q.y);
        y[2] = k ? y[2] + x[k] * __uint_as_float(q.z) : x[k] * __uint_as_float(q.z);
        y[3] = k ? y[3] + x[k] * __uint_as_float(q.w) : x[k] * __uint_as_float(q.w);
    }
    const uint32_t lo = pack_bf2(y[0], y[1]), hi = pack_bf2(y[2], y[3]);
    sg_add(out, c * bflo(lo), c * bfhi(lo), c * bflo(hi), c * bfhi(hi));
}

struct Mat4 { uint32_t b[4]; };
__device__ __forceinline__ Mat4 load_mat4(const __nv_bfloat16* w, int lane) {
    const unsigned short* u = (const unsigned short*)w + (lane >> 2 & 1);
    const bool on = lane >> 3 == (lane & 3);
    Mat4 m;
#pragma unroll
    for (int k = 0; k < 4; k++) m.b[k] = on ? u[(k & 1) * 8 + (k & 2)] | (uint32_t)u[(k & 1) * 8 + 4 + (k & 2)] << 16 : 0u;
    return m;
}
__device__ __forceinline__ void mul4(const uint4& x, const Mat4& m, float (&y)[8]) {
#pragma unroll
    for (int h = 0; h < 2; h++)
        asm("mma.sync.aligned.m16n8k16.row.col.f32.bf16.bf16.f32 {%0,%1,%2,%3}, {%4,%5,%6,%7}, {%8,%9}, {%10,%10,%10,%10};"
            : "=f"(y[2 * h]), "=f"(y[2 * h + 1]), "=f"(y[4 + 2 * h]), "=f"(y[5 + 2 * h])
            : "r"(x.x), "r"(x.z), "r"(x.y), "r"(x.w), "r"(m.b[2 * h]), "r"(m.b[2 * h + 1]), "f"(0.f));
}

struct Scale { uint32_t eb[4]; bool allslow; };
__device__ __forceinline__ void md_stats(const uint4& in, const Mat4& wd, int lane) {
    float y[8];
    mul4(in, wd, y);
    uint32_t mx[4], se[4];
#pragma unroll
    for (int c = 0; c < 4; c++) {
        uint32_t a = __float_as_uint(y[c]) & 0x7fffffffu, b = __float_as_uint(y[4 + c]) & 0x7fffffffu;
        if (a >= 0x7f800000u) a = 0;
        if (b >= 0x7f800000u) b = 0;
        mx[c] = __reduce_max_sync(0xffffffffu, max(a, b));
        se[c] = __reduce_add_sync(0xffffffffu, (a >> 23) + (b >> 23) + (a ? 1u << 20 : 0u) + (b ? 1u << 20 : 0u));
    }
    if (lane < 4) {
        asm volatile("red.shared.max.u32 [%0], %1;" ::"r"(SB + SM_STAT + lane * 4), "r"(lane == 0 ? mx[0] : lane == 1 ? mx[1] : lane == 2 ? mx[2] : mx[3]) : "memory");
        reds_add(SB + SM_STAT + 16 + lane * 4, lane == 0 ? se[0] : lane == 1 ? se[1] : lane == 2 ? se[2] : se[3]);
    }
}
__device__ __forceinline__ Scale get_scale(uint32_t sb) {
    Scale s;
    s.allslow = false;
#pragma unroll
    for (int k = 0; k < 4; k++) {
        const uint32_t mx = lds32(sb + SM_STAT + 4 * k), se = lds32(sb + SM_STAT + 16 + 4 * k);
        const uint32_t mean = (uint32_t)__fdividef((float)(se & 0xfffffu), (float)max(se >> 20, 1u));
        uint32_t eb = min(min((mx + 0x6e0000u) >> 23, mean + 5u), 227u);
        if (eb < 27u) { s.allslow = s.allslow || mx != 0; eb = 27u; }
        if (eb > 170u) s.allslow = true;
        s.eb[k] = eb;
    }
    return s;
}

__device__ __forceinline__ uint32_t probe_rt(uint32_t* p) {
    uint32_t best = 0xffffffffu;
#pragma unroll 1
    for (int r = 0; r < CFG_PROBES; r++) {
        const uint32_t t0 = clock();
        uint32_t v;
        asm volatile("atom.relaxed.gpu.global.add.u32 %0, [%1], 1;" : "=r"(v) : "l"(p) : "memory");
        if (v > 100000u) __trap();
        const uint32_t t1 = clock();
        best = min(best, t1 - t0);
    }
    return best;
}
__device__ __forceinline__ uint32_t* pub_ptr(const Params& p, int blk, uint32_t sel) {
    const int pr = blk / 44;
    return (uint32_t*)(p.ring + PROBE_OFF + (pr ? 4096u << pr : 0u) + (sel << 12) + 2176 + (blk - pr * 44) * 32);
}
__device__ __forceinline__ void probe(const Params& p, uint32_t sb, int w, int lane) {
    const int blk = blockIdx.x, pr = w >> 1;
    uint32_t off = PROBE_OFF + blk * 16 + (pr ? 4096u << pr : 0u);
    if (pr == 7) off = blk < NWIN ? blk * WIN + 4064 : PROBE_OFF + 3584 + blk % 16 * 32;
    off += (w & 1) * 4096;
    if (lane < 8) st_rlx((uint32_t*)(p.ring + (off & ~31u)) + lane, 0u);
    if (lane == 0) sts32(sb + SM_PROBE + w * 4, probe_rt((uint32_t*)(p.ring + off)));
}
__device__ __forceinline__ void assign_role(const Params& p, uint32_t sb, int lane) {
    {
        const bool x = lane < 8 && lds32(sb + SM_PROBE + lane * 8 + 4) < lds32(sb + SM_PROBE + lane * 8);
        const uint32_t near = __ballot_sync(0xffffffffu, x), bits = near & 1 ? ~near | 1u : near;
        const uint32_t tag = (lds32(sb + SM_MISC + 16) + 1) << 30;
        if (lane < 16) st_rlx(pub_ptr(p, blockIdx.x, lane >> 3) + (lane & 7), tag | (bits & 0xffu));
        constexpr int K = (NCTA + 31) / 32;
        __nanosleep(CFG_P0);
        uint32_t v[K], bad;
        int guard = 0;
        do {
            bad = 0;
#pragma unroll
            for (int k = 0; k < K; k++) {
                const int b = min(lane + 32 * k, NCTA - 1);
                v[k] = ld_rlx(pub_ptr(p, b, near >> (b / 44) & 1));
                bad |= v[k] ^ tag;
            }
            bad = __any_sync(0xffffffffu, bad >> 30);
            if (bad) __nanosleep(CFG_PSLEEP);
            if (++guard > GUARD) __trap();
        } while (bad);
#pragma unroll
        for (int k = 0; k < K; k++) sts32(sb + SM_PUB + (lane + 32 * k) * 4, v[k]);
    }
    __syncwarp();
    constexpr int NP = NCTA / 2, NTAB = H2 + H3;
    const int me = blockIdx.x >> 1, odd = blockIdx.x & 1;
    uint32_t pp[3], key[3];
    int n1 = 0;
#pragma unroll
    for (int k = 0; k < 3; k++) {
        const int i = lane + 32 * k;
        pp[k] = lds32(sb + SM_PUB + min(i, NP - 1) * 8) & 1;
        key[k] = (i * CFG_KM % CFG_KN) << 8 | i;
        n1 += 2 * __popc(__ballot_sync(0xffffffffu, i < NP && pp[k]));
    }
    bool fixed = n1 < NTAB || NCTA - n1 < NTAB;
    if (fixed) {
        n1 = NP / 2 * 2;
        pp[0] = pp[1] = pp[2] = lane & 1;
    }
    const uint32_t mine = __shfl_sync(0xffffffffu, (me < 32 ? key[0] : me < 64 ? key[1] : key[2]) * 2 + (me < 32 ? pp[0] : me < 64 ? pp[1] : pp[2]), me & 31);
    const int part = mine & 1;
    int pos = odd;
#pragma unroll
    for (int k = 0; k < 3; k++) pos += 2 * __popc(__ballot_sync(0xffffffffu, lane + 32 * k < NP && pp[k] == (uint32_t)part && key[k] < mine / 2));
    const int role = pos < H2 ? 1 : pos < NTAB ? 2 : 0;
    const int id = pos < H2 ? part * H2 + pos : pos < NTAB ? part * H3 + pos - H2 : (part ? NCTA - n1 - NTAB : 0) + pos - NTAB;
    const uint32_t v = lds32(sb + SM_PUB + lane * 4);
    uint32_t lin = 0;
#pragma unroll
    for (int b = 0; b < 6; b++) lin |= (__popc(__ballot_sync(0xffffffffu, (v >> (b + 1)) & 1)) > 16 ? 1u : 0u) << b;
    if (lane == 0) {
        sts32(sb + SM_MISC, role << 8 | id);
        sts32(sb + SM_MISC + 4, lin);
        sts32(sb + SM_MISC + 8, NCTA - n1 - NTAB);
        sts32(sb + SM_MISC + 20, part);
        sts32(sb + SM_MISC + 12, role == 0 ? id : role == 1 ? N1 + id : N1 + N2 + id);
    }
}
__device__ __forceinline__ uint32_t sel_of(uint32_t sb, int widx, uint32_t k, int part) {
    return (__popc(k & lds32(sb + SM_MISC + 4)) ^ (lds32(sb + SM_PUB + widx * 4) >> 7) ^ part) & 1;
}
__device__ __forceinline__ uint32_t gran_off(uint32_t sb, int widx, int k, int part) { return (2 * k + sel_of(sb, widx, k, part)) << 12; }
__device__ __forceinline__ uint32_t q1a_off(uint32_t sb, int src, int blk, int part) { return gran_off(sb, 2 * blk + part, src >> 1, part) + (src & 1) * 2048; }
__device__ __forceinline__ uint32_t q1h_off(uint32_t sb, int src, int blk, int part) { return gran_off(sb, 2 * blk + part, 32 + (src >> 2), part) + (src & 3) * 1024; }
__device__ __forceinline__ uint32_t* ctl_word(const Params& p, uint32_t sb, int k, int word, int part) {
    const int widx = CWIN + lds32(sb + SM_MISC + 16);
    return (uint32_t*)(p.ring + (widx * WIN + ((2 * k + sel_of(sb, widx, k, part)) << 12))) + word;
}
__device__ __forceinline__ uint32_t* cred1_of(const Params& p, uint32_t sb, int src) { return ctl_word(p, sb, src >> 3, (src & 7) * 128, src >= (int)lds32(sb + SM_MISC + 8)); }
__device__ __forceinline__ uint32_t* fin1_of(const Params& p, uint32_t sb, int dst) { return ctl_word(p, sb, 8 + (dst >> 3), (dst & 7) * 128, dst / H2); }
__device__ __forceinline__ uint32_t* cred2_of(const Params& p, uint32_t sb, int src) { return ctl_word(p, sb, 16 + (src >> 3), (src & 7) * 128, src / H2); }
__device__ __forceinline__ uint32_t* fin2_of(const Params& p, uint32_t sb, int dst) { return ctl_word(p, sb, 24 + (dst >> 3), (dst & 7) * 128, dst / H3); }
__device__ __forceinline__ uint32_t* rdy_of(const Params& p, uint32_t sb, int word, int part) { return ctl_word(p, sb, 28, word, part); }
__device__ __forceinline__ uint32_t q2_off(uint32_t sb, int blk, int dst) {
    return (N2 + dst) * WIN + gran_off(sb, N2 + dst, (blk >> 1) * 4 + (blk & 1), dst / H3);
}
template <bool IS1>
__device__ __forceinline__ void clear_queues(const Params& p, uint32_t sb, int id, int lane) {
    constexpr int NA = (N1 + 1) / 2, NG = NA + (N1 + 3) / 4, N = IS1 ? NG * N2 : NI * 2;
    if (IS1 && lane == 0) spin_ge(rdy_of(p, sb, 320, lds32(sb + SM_MISC + 20)), NTAIL);
    __syncwarp();
    fence_async_smem();
    for (int k = IS1 ? id + lane * N1 : lane; k < N; k += IS1 ? 32 * N1 : 32) {
        const int wi = k / NG, g = k - wi * NG;
        const uint32_t off = IS1 ? wi * WIN + gran_off(sb, wi, g < NA ? g : 32 + g - NA, wi & 1) : q2_off(sb, k >> 1, id) + (k & 1) * 16384;
        bulk_store(p.ring + off, sb + SM_ZERO, 4096);
    }
    asm volatile("cp.async.bulk.commit_group;" ::: "memory");
    asm volatile("cp.async.bulk.wait_group 0;" ::: "memory");
    if (!IS1) {
        fence_async_all();
        __syncwarp();
        fence_gpu();
        if (lane < NI) red_rlx(rdy_of(p, sb, id / H3 * H2 + lane, id / H3), 1u);
    }
    __syncwarp();
}

struct In8 { uint4 a[2], o[2]; uint2 g[2]; };
__device__ __forceinline__ void p1_load(const Params& p, In8& r, int i4) {
#pragma unroll
    for (int u = 0; u < 2; u++) {
        [[maybe_unused]] uint32_t x, y;
        asm volatile("tex.1d.v4.u32.s32 {%0,%1,%2,%3}, [%4, {%5}];" : "=r"(r.a[u].x), "=r"(r.a[u].y), "=r"(r.a[u].z), "=r"(r.a[u].w) : "l"(p.t_in), "r"(i4 + u * 32));
        asm volatile("tex.1d.v4.u32.s32 {%0,%1,%2,%3}, [%4, {%5}];" : "=r"(r.o[u].x), "=r"(r.o[u].y), "=r"(r.o[u].z), "=r"(r.o[u].w) : "l"(p.t_out), "r"(i4 + u * 32));
        asm volatile("tex.1d.v4.u32.s32 {%0,%1,%2,%3}, [%4, {%5}];" : "=r"(r.g[u].x), "=r"(r.g[u].y), "=r"(x), "=r"(y) : "l"(p.t_ang), "r"(i4 + u * 32));
    }
}
__device__ __forceinline__ uint32_t imad(uint32_t a, uint32_t b, uint32_t c) {
    uint32_t r;
    asm("mad.lo.u32 %0, %1, %2, %3;" : "=r"(r) : "r"(a), "r"(b), "r"(c));
    return r;
}
__device__ __forceinline__ unsigned char* ring_ptr(const Params& p, uint32_t lo) {
    uint64_t r;
    asm("mov.b64 %0, {%1, %2};" : "=l"(r) : "r"(lo), "r"(p.ring_hi));
    return (unsigned char*)r;
}
__device__ __forceinline__ uint32_t opaque32(uint32_t x) {
    asm volatile("" : "+r"(x));
    return x;
}
template <typename T> __device__ __forceinline__ T* opaque(T* p) {
    asm volatile("" : "+l"(p));
    return p;
}
template <int LUT> __device__ __forceinline__ uint32_t lop3(uint32_t a, uint32_t b, uint32_t c) {
    uint32_t r;
    asm("lop3.b32 %0, %1, %2, %3, %4;" : "=r"(r) : "r"(a), "r"(b), "r"(c), "n"(LUT));
    return r;
}
__device__ __forceinline__ uint32_t dp4(uint32_t a, uint32_t b, uint32_t c) {
    uint32_t r;
    asm("dp4a.u32.u32 %0, %1, %2, %3;" : "=r"(r) : "r"(a), "r"(b), "r"(c));
    return r;
}
__device__ __forceinline__ uint32_t dp2(uint32_t a, uint32_t b, uint32_t c) {
    uint32_t r;
    asm("dp2a.lo.u32.u32 %0, %1, %2, %3;" : "=r"(r) : "r"(a), "r"(b), "r"(c));
    return r;
}
__device__ __forceinline__ void p1_put(uint32_t sb, uint32_t wa, uint32_t wb, uint32_t old, bool on) {
    asm volatile("{.reg .pred q; setp.ne.u32 q, %3, 0; @q st.shared.v2.u32 [%0], {%1,%2};}"
                 ::"r"(sb + A_ST + prmt(old, wb, 0xf762)), "r"(wa), "r"(prmt(wb, old, 0x7210)), "r"((uint32_t)on) : "memory");
}
__device__ __forceinline__ void p1_slow_tile(const Params& p, uint32_t sb, int i4) {
    const float f = __bfloat162float(p.freq[0]);
#pragma unroll 1
    for (int u = 0; u < 8; u++) {
        const int k4 = i4 + (u >> 2) * 32;
        if (k4 < p.n4) {
            const size_t t = (size_t)k4 * 4 + (u & 3);
            const float x = __bfloat162float(__float2bfloat16(f * __bfloat162float(p.angle[t])));
            slow_add(p.m, sb, p.idx_in[t], p.idx_out[t], __bfloat162float(__float2bfloat16(cosf(x))));
        }
    }
}
__device__ __forceinline__ void role_p1(const Params& p, uint32_t sb, int id, int w, int lane) {
    lane = __shfl_sync(0xffffffffu, lane, lane);
    const uint32_t f2 = (uint32_t)__bfloat16_as_ushort(p.freq[0]) * 0x10001u;
    constexpr int TG = CFG_TG, NTK = CFG_NTK;
    static_assert(N1 * P1W % NTK == 0 && (NTK == 16 || NTK == 8) && P1W % 2 == 0, "tickets");
    const int first = (N1 * P1W + (id * P1W + w) % NTK) * (TG * 64);
    uint32_t* const tickets = opaque(ctl_word(p, sb, 29 + (id * P1W + w) % NTK / 8, (id * P1W + w) % 8 * 128 + lane, w & 1));
    auto draw = [&]() {
        uint32_t t = 0;
        asm volatile("{.reg .pred q; setp.eq.u32 q, %2, 0; @q atom.relaxed.gpu.global.add.u32 %0, [%1], 1;}" : "+r"(t) : "l"(tickets), "r"(lane) : "memory");
        return t;
    };
    int i4 = (id * P1W + w) * (TG * 64);
    In8 r;
    ACC_DECL
    uint32_t tk = draw();
    p1_load(p, r, i4 + lane);
    while (i4 < p.n4) {
        const int cur = i4;
        i4 += 64;
        if (i4 % (TG * 64) == 0) {
            i4 = min(__shfl_sync(0xffffffffu, tk, 0), 0x7fffffffu / (NTK * TG * 64) - N1 * P1W / NTK - 2) * (NTK * TG * 64) + first;
            tk = draw();
        }
        uint32_t wa[8], wb[8], x2[4];
        x2[0] = mul_bf2(r.g[0].x, f2); x2[1] = mul_bf2(r.g[0].y, f2);
        x2[2] = mul_bf2(r.g[1].x, f2); x2[3] = mul_bf2(r.g[1].y, f2);
        const uint32_t mx = maxabs_bf2(maxabs_bf2(x2[0], x2[1]), maxabs_bf2(x2[2], x2[3]));
        const bool fast = __all_sync(0xffffffffu, cur + 64 <= p.n4 && ((mx & 0x7fffu) <= 0x4300u) && ((mx & 0x7fff0000u) <= 0x43000000u));
        {
            const uint32_t in[8] = {r.a[0].x, r.a[0].y, r.a[0].z, r.a[0].w, r.a[1].x, r.a[1].y, r.a[1].z, r.a[1].w};
            const uint32_t ou[8] = {r.o[0].x, r.o[0].y, r.o[0].z, r.o[0].w, r.o[1].x, r.o[1].y, r.o[1].z, r.o[1].w};
#pragma unroll
            for (int j = 0; j < 8; j += 2) {
                const uint32_t ch = mul_h2(pack_h2(__cosf(bflo(x2[j >> 1])), __cosf(bfhi(x2[j >> 1]))), 0x24002400u);
#pragma unroll
                for (int k = j; k < j + 2; k++) {
                    const uint32_t blk = __umulhi(in[k], p.magic2), il = imad(blk, p.nrows2, in[k]);
                    wa[k] = k & 1 ? bitsel(ch, il, 0xffff0000u) : imad(ch, 65536u, il);
                    wb[k] = imad(blk, 1u << 21, imad(ou[k] >> 5, 1u - (1u << 21), ou[k] << 16));
                }
            }
        }
        p1_load(p, r, i4 + lane);
        if (fast) {
            uint32_t old[8], any = 0;
#pragma unroll
            for (int j = 0; j < 8; j++) old[j] = atoms_add(dp2(wb[j], 0x400u, 0u) + (sb + A_CNT), 0x80001u);
#pragma unroll
            for (int j = 0; j < 8; j++) any |= old[j];
            if (!__any_sync(0xffffffffu, any & 0xffe0u)) {
#pragma unroll
                for (int j = 0; j < 8; j++) p1_put(sb, wa[j], wb[j], old[j], true);
            } else {
                uint32_t pend = 0;
#pragma unroll
                for (int j = 0; j < 8; j++) { p1_put(sb, wa[j], wb[j], old[j], !(old[j] & 0xffe0u)); if (old[j] & 0xffe0u) pend |= 1u << j; }
                ACC(0, 1)
                for (int guard = 0; __any_sync(0xffffffffu, pend); guard++) {
                    __nanosleep(CFG_BSLEEP);
                    ACC(1, 1)
#pragma unroll
                    for (int j = 0; j < 8; j++) {
                        if (__any_sync(0xffffffffu, pend >> j & 1)) {
                            const uint32_t c = lds32v(sb + A_CNT + (pend >> j & 1 ? wb[j] >> 16 : 0) * 4);
                            const bool go = (pend >> j & 1) && (((old[j] >> 19) - (c >> 19) + c) & 8191u) < 32u;
                            p1_put(sb, wa[j], wb[j], old[j], go);
                            if (go) pend &= ~(1u << j);
                        }
                    }
                    if (guard > GUARD) __trap();
                }
            }
        } else {
            p1_slow_tile(p, sb, cur + lane);
            __syncwarp();
        }
    }
    __syncwarp();
    mbar_arrive_if(sb + SM_DONE, lane == 0);
    ACC_SAVE
}

__device__ __forceinline__ void role_flush(const Params& p, uint32_t sb, int id, int f, int lane) {
    lane = __shfl_sync(0xffffffffu, lane, lane);
    const int half = lane >> 4, o = lane >> 2, q = lane & 3;
    const uint32_t hm = half ? 0xffff0000u : 0xffffu, lth = ((1u << lane) - 1) & hm;
    const uint32_t list = sb + A_LIST + f * LISTB + half * LISTH, cnt = sb + A_CNT + (f * GPW * 32 + lane) * 4;
    const uint32_t* const cred = opaque(cred1_of(p, sb, id) + half * 32 + f * GPW);
    const uint32_t pa = opaque32(p.ring_lo + half * WIN + (id >> 1) * 8192 + (id & 1) * 2048 + q * 16);
    const uint32_t ph = opaque32(p.ring_lo + half * WIN + (32 + (id >> 2)) * 8192 + (id & 3) * 1024 + q * 8 - 2048);
    const uint32_t sa = q * 16 + (o & 1) * 64;
    uint32_t qo[GPW], hs[GPW], cr[4] = {0, 0, 0, 0};
#pragma unroll
    for (int g = 0; g < GPW; g++) {
        const int blk = f * GPW + g;
        qo[g] = 32u << 25;
        const uint32_t sa = sel_of(sb, 2 * blk + half, id >> 1, half), sh = sel_of(sb, 2 * blk + half, 32 + (id >> 2), half);
        hs[g] = sa << 31 | (2 * sh + 1 - sa) << 22 | 1u << 24 | (lane & 15) << 15 | (blk * 32 + lane) * 2;
    }
    uint4 x[KR] = {}, y[KR] = {};
    ACC_DECL
    int guard = 0;
    bool idle = false, done = false;
    while (true) {
        uint32_t c[GPW], fr[GPW], end = list, left = 0;
        if (idle && !done && __all_sync(0xffffffffu, mbar_test(sb + SM_DONE, 0))) {
            done = true;
            TR(17, f == 0 && lane == 0);
#pragma unroll
            for (int g = 0; g < GPW; g++) {
                const uint32_t u = lds32v(cnt + g * 128) & 31u, hd = hs[g] ^ (u & 16u ? imad(hs[g], 1u << 24, 1u) & 0x01000001u : 0u);
#pragma unroll 3
                for (uint32_t k = 1; k < 16; k++)
                    sts64_if(sb + A_ST + ((hd & 0x7ffu) << 7) + k * 8, p.rows2, (lane * 16 + k) | (hd & 0x1000000u), (u & 15u) && k >= (u & 15u));
                reds_add(cnt + g * 128, ((0u - u) & 15u) * 0x80001u);
            }
            __syncwarp();
        }
#pragma unroll
        for (int g = 0; g < GPW; g++) c[g] = lds32v(cnt + g * 128);
#pragma unroll
        for (int g = 0; g < GPW; g++) {
            const bool isfull = c[g] & 0xfff0u;
            const uint32_t m = __ballot_sync(0xffffffffu, isfull), rank = __popc(m & lth), r25 = rank << 25;
            const bool ok = isfull && (int)r25 < (int)(cr[g] - qo[g] + (63u << 25));
            const uint32_t n = __popc(__ballot_sync(0xffffffffu, ok) & hm);
            ACC(2, __popc(__ballot_sync(0xffffffffu, isfull && !ok)))
            sts32_if(imad(rank, 4u, end), bitsel(qo[g] + r25, hs[g], 0x7e000000u), ok);
            if (ok) hs[g] ^= imad(hs[g], 1u << 24, 1u) & 0x01000001u;
            fr[g] = ok ? 0u - 16u : 0u;
            left |= c[g] + fr[g];
            qo[g] = imad(n, 1u << 25, qo[g]);
            end = imad(n, 4u, end);
        }
        auto credits = [&]() {
            if (GPW == 4) { const uint4 v = ldg_q128(cred); cr[0] = v.x; cr[1] = v.y; cr[2] = v.z; cr[3] = v.w; }
            else { const uint2 v = ldg_q64(cred); cr[0] = v.x; cr[1] = v.y; }
        };
        if (CFG_CRE) credits();
        __syncwarp();
        ACC(0, 1) ACC(1, (end - list) / 2)
        if (__any_sync(0xffffffffu, end != list)) {
            uint32_t la = list + (o & 3) * 4;
            do {
                uint32_t d[KR];
#pragma unroll
                for (int k = 0; k < KR; k++) d[k] = lds32v(la + 16 * k);
                while (true) {
                    uint32_t bad = 0;
#pragma unroll
                    for (int k = 0; k < KR; k++) {
                        const uint32_t m = d[k] & 0x7ffu;
                        lds128_keep(x[k], imad(m, 128u, sa) + (sb + A_ST), la + 16 * k < end);
                        lds128_keep(y[k], imad(m, 128u, sa ^ 64) + (sb + A_ST), la + 16 * k < end);
                    }
#pragma unroll
                    for (int k = 0; k < KR; k++)
                        or3_if(bad, lop3<0x7e>(x[k].y, x[k].w, d[k]), lop3<0x7e>(y[k].y, y[k].w, d[k]), la + 16 * k < end);
                    if (!__any_sync(0xffffffffu, (int)imad(bad, 128u, 0u) < 0)) break;
                    if (++guard > GUARD) __trap();
                }
#pragma unroll
                for (int k = 0; k < KR; k++) {
                    const uint32_t mi = d[k] & 0x7c0u, dm = d[k] & 0xbec00000u;
                    x[k].x = bitsel(d[k], x[k].x, 0x40078000u);
                    x[k].y = prmt(x[k].y, x[k].w, 0x5410);
                    x[k].w = prmt(y[k].y, y[k].w, 0x5410);
                    y[k].x = bitsel(d[k], y[k].x, 0x40000000u);
                    y[k].y = y[k].z;
                    stg_q128(ring_ptr(p, dp4(dm, 0x20000000u, imad(mi, WIN / 32, pa))), x[k].x, x[k].y, x[k].z, x[k].w, X_ST1 la + 16 * k < end);
                    stg_q64(ring_ptr(p, dp4(dm, 0x10200000u, imad(mi, WIN / 32, ph))), y[k].x, y[k].y, X_ST1 la + 16 * k < end);
                }
                la += 16 * KR;
            } while (__any_sync(0xffffffffu, la < end));
            if (!CFG_CRE) credits();
#pragma unroll
            for (int g = 0; g < GPW; g++) reds_add(cnt + g * 128, fr[g]);
            idle = !__any_sync(0xffffffffu, end - list > 4 * CFG_TH);
            if (done && !__any_sync(0xffffffffu, left & 0xffffu)) break;
            if (idle) __nanosleep(CFG_TS);
        } else {
            if (done && !__any_sync(0xffffffffu, left & 0xffffu)) break;
            if (!CFG_CRE && __any_sync(0xffffffffu, left & 0xfff0u)) credits();
            idle = true;
            __nanosleep(CFG_FSLEEP);
            if (++guard > GUARD) __trap();
        }
    }
#pragma unroll
    for (int g = 0; g < GPW; g++) st_rlx_if(fin1_of(p, sb, half * H2 + f * GPW + g) + id, qo[g] - (32u << 25) + 1u, (lane & 15) == 0);
    TR(18, f == 0 && lane == 0);
    ACC_SAVE
}

__device__ __forceinline__ float h2f(uint32_t h) {
    float f;
    asm("{.reg .b16 t; cvt.u16.u32 t, %1; cvt.f32.f16 %0, t;}" : "=f"(f) : "r"(h));
    return f;
}
__device__ __forceinline__ void p2_slow(const Params& p, uint32_t sb, const uint32_t* tmp, int row0, uint32_t dst) {
#pragma unroll 1
    for (int j = 0; j < 4; j++)
        if (tmp[8 + j] & 0x40u) slow_add(p.m, sb, row0 + (tmp[j] & 0x7fffu), (tmp[4 + j] & 0x7fffu) * 32 + dst, h2f(tmp[j] >> 16) * 64.0f);
}
__device__ __forceinline__ uint32_t mul_h2_hi(uint32_t a, uint32_t b) {
    uint32_t r;
    asm("{.reg .b16 l, h; .reg .b32 t; mov.b32 {l, h}, %2; mov.b32 t, {h, h}; mul.rn.f16x2 %0, %1, t;}" : "=r"(r) : "r"(a), "r"(b));
    return r;
}
template <bool CHECK>
__device__ __forceinline__ void role_p2(const Params& p, uint32_t sb, int id, int w, int lane) {
    lane = __shfl_sync(0xffffffffu, lane, lane);
    const int part = id / H2, blk = id - part * H2, row0 = blk * p.rows2;
    const int o = lane >> 2, q = lane & 3;
    uint32_t* const cbase = (uint32_t*)(p.ring + (CWIN + lds32(sb + SM_MISC + 16)) * WIN);
    const uint32_t cred = opaque32((uint32_t)(uintptr_t)(cbase + part * 32 + blk));
    const uint32_t pa = opaque32(p.ring_lo + (2 * blk + part) * WIN + q * 16), ph = opaque32(pa - q * 8);
    const uint32_t po = opaque32(p.ring_lo + (q2_off(sb, blk, part * H3) & ~4096u) + q * 16 + (o & 1) * 64);
    const uint32_t sel = __ballot_sync(0xffffffffu, q2_off(sb, blk, part * H3 + (lane & 15)) & 4096u) << 12;
    const uint32_t* const fins = fin1_of(p, sb, id);
    uint32_t st[QPW] = {}, sq[QPW] = {};
    uint4 qa[NBT];
    uint2 qh[NBT];
    auto load = [&](int k) {
        qa[k] = ldg_q128(ring_ptr(p, pa + (bitsel(sq[k], st[k] >> 19, 0x7f800u) & 0x7ffc0u)));
        qh[k] = ldg_q64(ring_ptr(p, ph + (bitsel(sq[k] >> 9, st[k] >> 20, 0x7fc00u) & 0x7ffe0u)));
    };
#pragma unroll
    for (int k = 0; k < QPW; k++) {
        const int src = w * QPW + k;
        st[k] = o << 25 | (src < N1 ? 1u : 5u);
        sq[k] = src < N1 ? q1h_off(sb, src, blk, part) << 9 | q1a_off(sb, src, blk, part) | (uint32_t)(cred1_of(p, sb, src) - cbase) / 8 : 0x7e000u * 513u;
    }
#pragma unroll
    for (int k = 0; k < NBT; k++) load(k);
    ACC_DECL
    int guard = 0;
    uint32_t streak = 0;
    while (true) {
        uint32_t nn[NBT], xx[NBT][4], hh[NBT][2], dd[NBT], any = 0;
        bool last = false;
#pragma unroll
        for (int k = 0; k < NBT; k++) {
            const uint4 a = qa[k];
            const uint2 h = qh[k];
            uint32_t n = 8;
            const uint32_t miss = __ballot_sync(0xffffffffu, (int)imad((a.x ^ st[k]) & (h.x ^ st[k]), 2u, 0u) >= 0);
            if (miss) {
                n = (__ffs(miss) - 1) >> 2;
                if (!__any_sync(0xffffffffu, st[k] & 8u)) { if (streak < CFG_PSTREAK) n &= CFG_PMASK; }
                else if (!__any_sync(0xffffffffu, ((st[k] >> 6) + ((n - o) << 19) ^ st[k]) & 0x1f80000u)) { st[k] |= 4u; last = true; }
            }
            ACC(1, n == 0) ACC(2, n != 0) ACC(3, n)
            st[k] = imad(n, 1u << 25, st[k]);
            st_rlx_if((uint32_t*)ring_ptr(p, imad(sq[k] & 0x7f0u, 32u, cred)), st[k], X_CR1 lane == 0 && n);
            xx[k][0] = bitsel(a.x, 0x00040000u, 0xbff87fffu); xx[k][1] = a.z; xx[k][2] = h.x & 0xbfffffffu; xx[k][3] = h.y;
            hh[k][0] = a.y; hh[k][1] = a.w; dd[k] = a.x >> 13 & 0x3cu; nn[k] = n;
            any |= n;
        }
        if (!any) {
#pragma unroll
            for (int k = 0; k < QPW; k++) {
                const uint32_t fin = ld_rlx(fins + ((sq[k] >> 12 & 62u) | (sq[k] >> 11 & 1u)));
                if (fin & 1u) st[k] |= (fin >> 6 & 0x1f80000u) | 8u;
            }
            if (++guard > GUARD) __trap();
            streak++;
        } else streak = 0;
        if (last) {
            uint32_t all = 4u;
#pragma unroll
            for (int k = 0; k < QPW; k++) all &= st[k];
            last = __all_sync(0xffffffffu, all);
        }
        {
            uint32_t t[QPW], u[QPW];
#pragma unroll
            for (int k = 0; k < QPW; k++) { t[k] = st[(k + NBT) % QPW]; u[k] = sq[(k + NBT) % QPW]; }
#pragma unroll
            for (int k = 0; k < QPW; k++) { st[k] = t[k]; sq[k] = u[k]; }
        }
#pragma unroll
        for (int k = 0; k < NBT; k++) load(k);
#pragma unroll
      for (int k = 0; k < NBT; k++) {
        if (nn[k]) {
            const uint32_t* const x = xx[k];
            const uint32_t h0 = hh[k][0], h1 = hh[k][1], d4 = dd[k];
            const bool v = o < nn[k];
            uint32_t old = 0, ta[4], tb[4], w0[4], w1[4];
            atoms_add_keep(old, sb + SM_CNT2 + d4, 0x10001u, q == 0 && v);
#pragma unroll
            for (int j = 0; j < 4; j++) {
                ta[j] = lds32nv(dp2(x[j], 4u, 0u) + (sb + B_TA));
                tb[j] = lds16nv(dp2(x[j], 2u, 0u) + (sb + B_TB));
            }
            old = __shfl_sync(0xffffffffu, old, lane & 28);
            const uint32_t tag = old << 8 & 0x40000000u;
#pragma unroll
            for (int j = 0; j < 4; j++) {
                const uint32_t z = prmt(j & 2 ? h1 : h0, 0, j & 1 ? 0x4342 : 0x4140);
                const uint32_t t23 = prmt((ta[j] & 0x60076007u) * 2050u, tb[j], 0x5341) & 0xfffcffffu;
                w0[j] = (imad(z, 128u, j & 1 ? 0u : tag) & 0x78007800u) | mul_h2_hi(ta[j] & 0x9ff89ff8u, x[j]);
                w1[j] = (imad(z, 2048u, 0u) & 0x78007800u) | mul_h2_hi(t23, x[j]);
            }
            if (CHECK && v && ((tb[0] | tb[1] | tb[2] | tb[3]) & 0x40u)) {
                uint32_t tmp[12];
#pragma unroll
                for (int j = 0; j < 4; j++) {
                    tmp[j] = x[j]; tmp[4 + j] = (j & 2 ? h1 : h0) >> (j & 1 ? 16 : 0); tmp[8 + j] = tb[j];
                    if (tb[j] & 0x40u) { w0[j] &= 0x78007800u; w1[j] &= 0x78007800u; }
                }
                p2_slow(p, sb, tmp, row0, part * H3 + d4 / 4);
            }
            const uint32_t off = (bitsel(old >> 9, old >> 7, 0x0f80u) & 0x4f80u) + imad(d4, WIN / 4, (sel >> (d4 / 4) & 4096u) + po);
            bool wait = old & (0x10000u - NQ2);
            if (!__any_sync(0xffffffffu, wait)) {
                stg_q128(ring_ptr(p, off), w0[0], w1[0], w0[1], w1[1], X_ST2 v);
                stg_q128(ring_ptr(p, off ^ 64u), w0[2], w1[2], w0[3], w1[3], X_ST2 v);
            } else {
                bool pend = v;
                ACC(0, 1)
                for (int g2 = 0;; g2++) {
                    stg_q128(ring_ptr(p, off), w0[0], w1[0], w0[1], w1[1], pend && !wait);
                    stg_q128(ring_ptr(p, off ^ 64u), w0[2], w1[2], w0[3], w1[3], pend && !wait);
                    pend = wait;
                    if (!__any_sync(0xffffffffu, pend)) break;
                    __nanosleep(CFG_BSLEEP);
                    const uint32_t c = lds32v(sb + SM_CNT2 + d4);
                    wait = pend && (((old >> 16) - (c >> 16) + c) & 0xffffu) >= NQ2;
                    if (g2 > GUARD) __trap();
                }
            }
        }
      }
        if (last) break;
    }
    TR(17, w == 0 && lane == 0);
    __syncwarp();
    uint32_t rank = 0;
    if (lane == 0) { __threadfence_block(); rank = atoms_add(sb + SM_FIN, 1u); __threadfence_block(); }
    if (__shfl_sync(0xffffffffu, rank, 0) == P2W - 1 && lane < 16)
        st_rlx(fin2_of(p, sb, part * H3 + lane) + blk, FIN | (((lds32v(sb + SM_CNT2 + lane * 4) >> 16) - NQ2) & 0xffffu));
    __syncwarp();
    mbar_arrive_if(sb + SM_DONE, lane == 0);
    ACC_SAVE
}
__device__ __forceinline__ void role_credit(const Params& p, uint32_t sb, int id, int lane) {
    const uint32_t* const cred = cred2_of(p, sb, id) + (lane & 15);
    uint32_t last = 0;
    for (int guard = 0;; guard++) {
        if (__all_sync(0xffffffffu, mbar_test(sb + SM_DONE, 0))) break;
        const uint32_t c = ld_rlx(cred);
        if (lane < 16 && c != last) reds_add(sb + SM_CNT2 + lane * 4, 0u - ((c - last) & 0xffffu));
        last = c;
        __nanosleep(CFG_CSLEEP);
        if (guard > GUARD) __trap();
    }
}

__device__ __forceinline__ void p3_wrap(uint32_t sb, int id, const uint32_t* tmp) {
    const Scale sc = get_scale(sb);
#pragma unroll 1
    for (int j = 0; j < 8; j++) {
        const uint32_t old = tmp[4 + j], v = tmp[12 + j], nw = old + v, t = (old ^ nw) & (v ^ nw);
        if (t & 0x80008000u) {
            const float k = (t & 0x8000u) ? ((v & 0x8000u) ? -1.0f : 1.0f) : 0.0f;
            const float q = (t & 0x80000000u) ? ((int)v < 0 ? -65536.0f : 65536.0f) : 0.0f;
            const uint32_t e0 = (j & 1) ? sc.eb[2] : sc.eb[0], e1 = (j & 1) ? sc.eb[3] : sc.eb[1];
            const float lo = k * 65536.0f * __uint_as_float((e0 - 10) << 23), hi = (q - k) * __uint_as_float((e1 - 10) << 23);
            if (j & 1) sg_add(tmp[j >> 1] * 32 + id, 0.f, 0.f, lo, hi);
            else sg_add(tmp[j >> 1] * 32 + id, lo, hi, 0.f, 0.f);
        }
    }
}
__device__ __forceinline__ uint32_t p3_val(uint32_t w) {
    const uint32_t mk = prmt(w, 0, 0xBB99);
    return ((w & 0x07ff07ffu) ^ mk) - mk;
}
__device__ __forceinline__ void role_p3(const Params& p, uint32_t sb, int id, int w, int lane) {
    lane = __shfl_sync(0xffffffffu, lane, lane);
    uint32_t* const cred = opaque(cred2_of(p, sb, id / H3 * H2 + w) + id % H3);
    const uint32_t pq = opaque32(p.ring_lo + q2_off(sb, w, id) + lane * 16);
    auto off = [&](uint32_t n) { return (n & 1u) << 11 | (n & 2u) << 13; };
    const uint32_t pp = opaque32(pq - lane * 16 + 2032);
    auto tag_of = [&](uint32_t n) { return ~n << 28; };
    uint32_t n = 0, fin = 0, pr = 0;
    uint4 v[4] = {};
    bool have = false, last = false;
    ACC_DECL
    int guard = 0;
    while (true) {
        const uint32_t ex = tag_of(n);
        const bool ok = have && !__any_sync(0xffffffffu, ((v[0].x ^ ex) | (v[1].x ^ ex) | (v[2].x ^ ex) | (v[3].x ^ ex)) & 0x40000000u);
        if (ok) n++;
        const bool ready = __all_sync(0xffffffffu, (have && !ok) || !((pr ^ tag_of(n)) & 0x40000000u));
        st_rlx_if(cred, n * 16, X_CR2 lane == 0 && ok);
        if (!ok && !ready && __all_sync(0xffffffffu, fin & FIN)) {
            const uint32_t left = __shfl_sync(0xffffffffu, (fin - n * 16) & 0xffffu, 0);
            if (left - 1u > 0x8000u) break;
            if (left < 16u) {
#pragma unroll
                for (int u = 0; u < 4; u++) {
                    v[u] = make_uint4(ex & 0x40000000u, 0, 0, 0);
                    ldq128_keep(v[u], ring_ptr(p, pq + off(n)) + u * 512, u * 4 + (lane >> 3) < left);
                }
                have = last = !__any_sync(0xffffffffu, ((v[0].x ^ ex) | (v[1].x ^ ex) | (v[2].x ^ ex) | (v[3].x ^ ex)) & 0x40000000u);
                pr = ~tag_of(n + have);
                if (++guard > GUARD) __trap();
                continue;
            }
        }
        uint32_t row[8], val[16];
#pragma unroll
        for (int u = 0; u < 4; u++) {
            const uint4 x = v[u];
            row[2 * u] = prmt(bitsel(x.x << 1, x.y >> 3, 0x7000f000u), 0, 0x4431);
            row[2 * u + 1] = prmt(bitsel(x.z << 1, x.w >> 3, 0x7000f000u), 0, 0x4431);
            val[4 * u] = p3_val(x.x); val[4 * u + 1] = p3_val(x.y);
            val[4 * u + 2] = p3_val(x.z); val[4 * u + 3] = p3_val(x.w);
        }
#pragma unroll
        for (int u = 0; u < 4; u++) ldq128_keep(v[u], ring_ptr(p, pq + off(n)) + u * 512, ready);
        pr = ld_rlx((const uint32_t*)ring_ptr(p, pp + off(n + ready)));
        ACC(2, have && !ok)
        have = ready;
        if (!ok) {
            ACC(1, 1)
            fin = ld_rlx(fin2_of(p, sb, id) + w);
            if (++guard > GUARD) __trap();
        } else {
#pragma unroll
            for (int u = 0; u < 4; u += 2) {
                uint32_t old[8], chk = 0;
#pragma unroll
                for (int j = 0; j < 4; j++) {
                    old[2 * j] = atoms_add(sb + C_S + row[2 * u + j] * 4, val[4 * u + 2 * j]);
                    old[2 * j + 1] = atoms_add(sb + C_S + ROWS3_MAX * 4 + row[2 * u + j] * 4, val[4 * u + 2 * j + 1]);
                }
#pragma unroll
                for (int j = 0; j < 8; j++) {
                    const uint32_t nw = old[j] + val[4 * u + j];
                    chk |= (old[j] ^ nw) & (val[4 * u + j] ^ nw);
                }
                if (chk & 0x80008000u) {
                    uint32_t tmp[20];
#pragma unroll
                    for (int j = 0; j < 8; j++) { tmp[j >> 1] = row[2 * u + (j >> 1)]; tmp[4 + j] = old[j]; tmp[12 + j] = val[4 * u + j]; }
                    p3_wrap(sb, id, tmp);
                }
            }
            __syncwarp();
            if (last) break;
        }
    }
    ACC_SAVE
}

__device__ __forceinline__ void row_gates(const float* sw, const uint32_t* c2, uint32_t dbits, float4& gs, float4& gr) {
    const uint32_t d2 = dbits * 0x10001u;
    gs = gr = make_float4(0.f, 0.f, 0.f, 0.f);
#pragma unroll
    for (int r2 = 0; r2 < 4; r2++) {
        uint32_t df = sub_bf2(d2, c2[r2]);
        uint32_t ar = mul_bf2(mul_bf2(df, df), 0xC120C120u);
        uint32_t rb = pack_bf2(__expf(bflo(ar)), __expf(bfhi(ar)));
        const float r0 = bflo(rb), r1 = bfhi(rb);
        const float4 s0 = *(const float4*)(sw + r2 * 8), s1 = *(const float4*)(sw + r2 * 8 + 4);
        const float4 q0 = *(const float4*)(sw + 32 + r2 * 8), q1 = *(const float4*)(sw + 32 + r2 * 8 + 4);
        gs.x += r0 * s0.x + r1 * s1.x; gs.y += r0 * s0.y + r1 * s1.y;
        gs.z += r0 * s0.z + r1 * s1.z; gs.w += r0 * s0.w + r1 * s1.w;
        gr.x += r0 * q0.x + r1 * q1.x; gr.y += r0 * q0.y + r1 * q1.y;
        gr.z += r0 * q0.z + r1 * q1.z; gr.w += r0 * q0.w + r1 * q1.w;
    }
}
__device__ __forceinline__ uint2 finish_row(const float* wu, const float4& gs, const float4& gr, const float S[4], uint2 mrow) {
    const float a[4] = {S[0] * gs.x, S[1] * gs.y, S[2] * gs.z, S[3] * gs.w};
    float u[4] = {0, 0, 0, 0};
#pragma unroll
    for (int k = 0; k < 4; k++) {
        u[0] += a[k] * wu[4 * k]; u[1] += a[k] * wu[4 * k + 1]; u[2] += a[k] * wu[4 * k + 2]; u[3] += a[k] * wu[4 * k + 3];
    }
    return make_uint2(pack_bf2(bflo(mrow.x) + u[0] * gr.x, bfhi(mrow.x) + u[1] * gr.y),
                      pack_bf2(bflo(mrow.y) + u[2] * gr.z, bfhi(mrow.y) + u[3] * gr.w));
}
__device__ __forceinline__ void load_tail_weights(const Params& p, float* sw, int tid) {
    if (tid < 32) sw[tid] = __bfloat162float(p.w_sbf[tid]);
    else if (tid < 64) sw[tid] = __bfloat162float(p.w_rbf[tid - 32]);
    else if (tid < 80) sw[tid] = __bfloat162float(p.w_up[tid - 64]);
    else if (tid < 96) sw[tid] = __bfloat162float(p.w_down[tid - 80]);
}
__device__ __forceinline__ float exp_ftz(float x) {
    float r;
    asm("ex2.approx.ftz.f32 %0, %1;" : "=f"(r) : "f"(x * 1.4426950408889634f));
    return r;
}
__device__ __forceinline__ void tail_rows(const Params& p, int tidx, int w, int lane) {
    constexpr uint32_t sb = SB;
    if (w == NW - 1 && lane < 2) {
        fence_gpu();
        red_rlx(rdy_of(p, sb, 320, lane), 1u);
    }
    if (w >= NPC * WPP) return;
    const int pc = w / WPP, r0 = pc * RPC + (tidx * WPP + w - pc * WPP) * 8, e0 = r0 * 32;
    const uint32_t G = sb + T_G + w * 6144;
    auto edge = [&](int k) { return e0 + (lane & 1) * 128 + (lane >> 1) + (k & 3) * 32 + (k >> 2) * 16; };
    {
        const int g = lane >> 2, t = lane & 3;
        uint32_t dv[16];
#pragma unroll
        for (int k = 0; k < 16; k++) dv[k] = __ldg((const uint32_t*)p.dist + min(e0 / 2 + k * 8 + g, p.E / 2 - 1));
        uint2 mv[8];
#pragma unroll
        for (int k = 0; k < 8; k++) mv[k] = __ldg(p.m + min(edge(k), p.E - 1));
        const uint32_t c2 = ((const uint32_t*)p.centers)[t];
        const unsigned short* wg = (const unsigned short*)(g < 4 ? p.w_sbf : p.w_rbf) + t * 8 + (g & 3);
        const uint32_t b = wg[0] | (uint32_t)wg[4] << 16;
#pragma unroll
        for (int k = 0; k < 8; k++) sts64(G + 4096 + (k * 32 + lane) * 8, mv[k].x, mv[k].y);
        TR(19, w == 0 && lane == 0 && dv[15] + b + c2 != 0x12345);
#pragma unroll
        for (int k = 0; k < 16; k++) {
            uint32_t a[2];
#pragma unroll
            for (int h = 0; h < 2; h++) {
                const uint32_t df = sub_bf2(prmt(dv[k], 0, h ? 0x3232 : 0x1010), c2);
                const uint32_t ar = mul_bf2(mul_bf2(df, df), 0xC120C120u);
                a[h] = pack_bf2(exp_ftz(bflo(ar)), exp_ftz(bfhi(ar)));
            }
            float d[4];
            asm("mma.sync.aligned.m16n8k8.row.col.f32.bf16.bf16.f32 {%0,%1,%2,%3}, {%4,%5}, {%6}, {%7,%7,%7,%7};"
                : "=f"(d[0]), "=f"(d[1]), "=f"(d[2]), "=f"(d[3]) : "r"(a[0]), "r"(a[1]), "r"(b), "f"(0.f));
            const uint32_t at = G + (((k & 1) * 4 + (k >> 1 & 3)) * 32 + g * 4 + (k >> 3)) * 16 + t * 4;
            sts32(at, pack_bf2(d[0], d[1]));
            sts32(at + 32, pack_bf2(d[2], d[3]));
        }
    }
    __syncwarp();
    TR(20, w == 0 && lane == 0);
    const Scale sc = get_scale(sb);
    const float lsb[4] = {__uint_as_float((sc.eb[0] - 10) << 23), __uint_as_float((sc.eb[1] - 10) << 23),
                          __uint_as_float((sc.eb[2] - 10) << 23), __uint_as_float((sc.eb[3] - 10) << 23)};
    TR(2, w == 0 && lane == 0);
    uint32_t dirty = 0;
    uint4 sx[2] = {}, sy[2] = {};
#pragma unroll 1
    for (int pass = CFG_DRY ? 0 : 1; pass < 2; pass++) {
        if (pass) {
            if (w == pc * WPP && lane < 2) spin_ge(rdy_of(p, sb, lane ? 320 : 160 + 32 * pc, lds32(sb + SM_MISC + 20)), lane ? NTAIL : N3);
            __syncwarp();
            bar_sync(1 + pc, WPP * 32);
            TR(3, w == 0 && lane == 0);
            TR(10, w == NPC * WPP - 1 && lane == 0);
            if (r0 >= (int)p.rows3) return;
            const uint32_t* const src = &g_S[0][lane >> 1][r0 + (lane & 1) * 4];
#pragma unroll
            for (int u = 0; u < 2; u++) {
                sx[u] = ldg_q128(src + u * 16 * ROWS3_MAX);
                sy[u] = ldg_q128(src + (u * 16 + 32) * ROWS3_MAX);
            }
            if (lane < 8 && (r0 + lane) * 32 < p.E && (dirty = ld_rlx(g_dirty + r0 + lane))) st_rlx(g_dirty + r0 + lane, 0u);
            dirty = __ballot_sync(0xffffffffu, dirty != 0);
        }
        asm volatile("" : "+r"(lane));
        float wu[16];
#pragma unroll
        for (int k = 0; k < 4; k++) *(uint4*)(wu + 4 * k) = lds128(sb + SM_W + 256 + 16 * k);
        auto finish = [&](int k, uint32_t x, uint32_t y, bool extra) {
            const int e = edge(k);
            float S[4];
            const uint32_t tx = x + 0x80008000u, ty = y + 0x80008000u;
            S[0] = (__uint_as_float(prmt(tx, 0x4b000000u, 0x7610)) - 8421376.0f) * lsb[0];
            S[1] = (__uint_as_float(prmt(tx, 0x4b000000u, 0x7632)) - 8421376.0f) * lsb[1];
            S[2] = (__uint_as_float(prmt(ty, 0x4b000000u, 0x7610)) - 8421376.0f) * lsb[2];
            S[3] = (__uint_as_float(prmt(ty, 0x4b000000u, 0x7632)) - 8421376.0f) * lsb[3];
            if (extra && e < p.E) {
                const float4 g = __ldcg(g_Sg + e);
                S[0] += g.x; S[1] += g.y; S[2] += g.z; S[3] += g.w;
                __stcg(g_Sg + e, make_float4(0.f, 0.f, 0.f, 0.f));
            }
            const uint4 g = lds128(G + (k * 32 + lane) * 16);
            const uint2 o = finish_row(wu, make_float4(bflo(g.x), bfhi(g.x), bflo(g.y), bfhi(g.y)), make_float4(bflo(g.z), bfhi(g.z), bflo(g.w), bfhi(g.w)), S,
                                       lds64v(G + 4096 + (k * 32 + lane) * 8));
            asm volatile("{.reg .pred q; setp.ne.u32 q, %3, 0; @q st.global.v2.u32 [%0], {%1,%2};}"
                         ::"l"(p.out + e), "r"(o.x), "r"(o.y), "r"((uint32_t)(pass && e < p.E)));
        };
        const uint32_t xs[8] = {sx[0].x, sx[0].y, sx[0].z, sx[0].w, sx[1].x, sx[1].y, sx[1].z, sx[1].w};
        const uint32_t ys[8] = {sy[0].x, sy[0].y, sy[0].z, sy[0].w, sy[1].x, sy[1].y, sy[1].z, sy[1].w};
        if (!dirty) {
#pragma unroll
            for (int k = 0; k < 8; k++) finish(k, xs[k], ys[k], false);
        } else {
            uint32_t tmp[16];
#pragma unroll
            for (int k = 0; k < 8; k++) { tmp[k] = xs[k]; tmp[8 + k] = ys[k]; }
#pragma unroll 1
            for (int k = 0; k < 8; k++) finish(k, tmp[k], tmp[8 + k], dirty >> ((lane & 1) * 4 + (k & 3)) & 1);
        }
    }
    TR(9, w == 0 && lane == 0);
    TR(11, w == NPC * WPP - 1 && lane == 0);
}

#define CFG_MAP1 1
__global__ void __launch_bounds__(NT, 1) k_main(const __grid_constant__ Params p) {
    extern __shared__ __align__(1024) unsigned char smem[];
    constexpr uint32_t sb = SB;
    if ((uint32_t)__cvta_generic_to_shared(smem) != SB) __trap();
    const int tid = threadIdx.x, w = __shfl_sync(0xffffffffu, tid >> 5, 0), lane = tid & 31;
    if (w < NPROBE) probe(p, sb, w, lane);
    else {
        if (tid == NT - 1) sts32(sb + SM_MISC + 16, ld_rlx(&g_epoch) & 1);
        if (tid >= NT - 32 && lane < 12) sts32(sb + SM_FIN + lane * 4, 0u);
        load_tail_weights(p, (float*)(smem + SM_W), tid - NPROBE * 32);
    }
    const Mat4 wd = load_mat4(p.w_down, lane);
    cta_sync();
    if (w) {
        const uint4 in = __ldg((const uint4*)p.m + (size_t)(tid - 32) * (p.E / 2) / (NT - 32));
        for (int i = SM_DATA / 16 + tid - 32; i < ZEND / 16; i += NT - 32) ((uint4*)smem)[i] = make_uint4(0, 0, 0, 0);
        if (tid - 32 < 256) ((uint4*)(smem + SM_ZERO))[tid - 32] = make_uint4(0, 0, 0, 0);
        if (tid < 48) sts32(sb + SM_CNT2 + (tid - 32) * 4, NQ2 << 16);
        __syncwarp();
        if (CFG_PFD && tid == NT - 1) {
            __nanosleep(CFG_PFD);
            const uint32_t n = (p.E / 2 + NCTA - 1) / NCTA, o = blockIdx.x * n;
            if (o < (uint32_t)p.E / 2) asm volatile("cp.async.bulk.prefetch.L2.global [%0], %1;" ::"l"((const uint4*)p.m + o), "r"(min(n, p.E / 2 - o) * 16) : "memory");
        }
        __syncwarp();
        md_stats(in, wd, lane);
    } else assign_role(p, sb, lane);
    if (tid == 0) {
        mbar_init(sb + SM_DONE, lds32(sb + SM_MISC) >> 8 ? P2W : P1W);
    }
    cta_sync();
    const uint32_t rid = __shfl_sync(0xffffffffu, lds32(sb + SM_MISC), 0);
    const int role = rid >> 8, id = rid & 255;
    TR(5, tid == 0);
    if (role == 0) {
        const int ww = CFG_MAP1 == 0 ? ((w & 3) == 3 ? NW : (w >> 2) * 3 + (w & 3)) : CFG_MAP1 == 1 ? (w & 2 ? NW : (w >> 2) * 2 + (w & 1)) : w;
        const int sw = CFG_MAP1 == 0 ? ((w & 3) == 3 ? w >> 2 : NW) : CFG_MAP1 == 1 ? (w & 2 ? (w >> 2) * 2 + (w & 1) : NW) : w - P1W;
        static_assert(CFG_MAP1 == 0 ? (P1W <= NW / 4 * 3 && NF + 2 <= NW / 4) : CFG_MAP1 == 1 ? (P1W <= NW / 2 && NF + 2 <= NW / 2) : true, "warp map");
        for (int i = tid; i < NB; i += NT) sts32(sb + A_CNT + i * 4, 1u << 24);
        cta_sync();
        TR(1, tid == 0);
        if (ww < P1W) role_p1(p, sb, id, ww, lane);
        else if (sw < NF) role_flush(p, sb, id, sw, lane);
        else if (w == NW - 1) {
            uint4* owin = (uint4*)(p.ring + (CWIN + (lds32(sb + SM_MISC + 16) ^ 1)) * WIN);
            for (int i = id * 32 + lane; i < CPAIRS * 512; i += N1 * 32) __stcg(owin + i, make_uint4(0, 0, 0, 0));
            __syncwarp();
        }
    } else if (role == 1) {
        const int row0 = id % H2 * p.rows2;
        const int nrows = min((int)p.rows2, p.E - row0);
        constexpr int NTB = NT - 32, TBD = CFG_TBD;
        bool flagged = false;
        if (w < NW - 1) {
            const Scale sc = get_scale(sb);
            Mat4 ws;
#pragma unroll
            for (int k = 0; k < 4; k++) ws.b[k] = mul_bf2(wd.b[k], ((246u - (lane & 4 ? sc.eb[(k & 2) + 1] : sc.eb[k & 2])) << 7) * 0x10001u);
            const uint4* const src = (const uint4*)(p.m + row0);
            uint4 r2[TBD], nx[TBD];
            auto fetch = [&](int i) {
#pragma unroll
                for (int k = 0; k < TBD; k++)
                    asm volatile("ld.global.nc.v4.u32 {%0,%1,%2,%3}, [%4];" : "=r"(nx[k].x), "=r"(nx[k].y), "=r"(nx[k].z), "=r"(nx[k].w) : "l"(src + min(i + k * NTB, nrows / 2 - 1)));
            };
            fetch(tid);
#pragma unroll 1
            for (int i0 = tid; 2 * (i0 - lane) < nrows; i0 += TBD * NTB) {
#pragma unroll
                for (int k = 0; k < TBD; k++) r2[k] = make_uint4(nx[k].x, nx[k].z, nx[k].y, nx[k].w);
                fetch(i0 + TBD * NTB);
#pragma unroll
                for (int k = 0; k < TBD; k++) {
                    const int i = i0 + k * NTB;
                    float y[8];
                    mul4(make_uint4(r2[k].x, r2[k].z, r2[k].y, r2[k].w), ws, y);
                    uint32_t a[4], h[4], ta[2];
#pragma unroll
                    for (int j = 0; j < 4; j++) { a[j] = pack_h2(y[2 * j], y[2 * j + 1]); h[j] = a[j] + 0x00040004u; }
#pragma unroll
                    for (int j = 0; j < 2; j++) ta[j] = bitsel(h[2 * j], bitsel(h[2 * j + 1] >> 3, h[2 * j + 1] << 7, 0x00070007u), 0x9ff89ff8u);
                    uint32_t tb = prmt(h[1], h[3], 0x7531);
                    const uint32_t b0 = a[0] | a[1] | h[0] | h[1], b1 = a[2] | a[3] | h[2] | h[3];
                    if (__any_sync(0xffffffffu, ((b0 | b1) & 0x60006000u) || sc.allslow)) {
                        if ((b0 & 0x60006000u) || sc.allslow) { ta[0] = 0; tb = (tb & 0xffff0000u) | 0x40u; }
                        if ((b1 & 0x60006000u) || sc.allslow) { ta[1] = 0; tb = (tb & 0xffffu) | 0x400000u; }
                        flagged = true;
                    }
                    sts64_if(sb + B_TA + i * 8, ta[0], ta[1], 2 * i < nrows);
                    sts32_if(sb + B_TB + i * 4, tb, 2 * i < nrows);
                }
            }
            if (tid == 0) {
                sts32(sb + B_TA + p.rows2 * 4, 0u);
                sts16(sb + B_TB + p.rows2 * 2, 0u);
            }
            TR(8, tid == 0);
        } else if (lane == 0) spin_ge(rdy_of(p, sb, id, id / H2), H3);
        __syncwarp();
        flagged = __any_sync(0xffffffffu, __syncthreads_or(flagged));
        TR(1, tid == 0);
        if (w < P2W) {
            if (flagged) role_p2<true>(p, sb, id, w, lane);
            else role_p2<false>(p, sb, id, w, lane);
        } else if (w == P2W) role_credit(p, sb, id, lane);
    } else {
        if (w == 0) clear_queues<false>(p, sb, id, lane);
        if (tid >= 32 && tid < 33 + NPC) mbar_init(sb + SM_CNT2 + (tid - 32) * 8, 1);
        cta_sync();
        TR(1, tid == 0);
        if (w < P3W) role_p3(p, sb, id, w, lane);
        cta_sync();
        TR(2, tid == 0);
        if (w < NPC && lane == 0) {
            fence_async_smem();
            const int n = min(((int)p.rows3 + 7) / 8 * 8 - w * RPC, RPC);
            if (w) mbar_wait(sb + SM_CNT2 + w * 8, 0);
            if (n > 0) {
                bulk_store(g_S[0][id] + w * RPC, sb + C_S + w * RPC * 4, n * 4);
                bulk_store(g_S[1][id] + w * RPC, sb + C_S + (ROWS3_MAX + w * RPC) * 4, n * 4);
            }
            asm volatile("cp.async.bulk.commit_group;" ::: "memory");
            asm volatile("cp.async.bulk.wait_group.read 0;" ::: "memory");
            mbar_arrive(sb + SM_CNT2 + w * 8 + 8);
            asm volatile("cp.async.bulk.wait_group 0;" ::: "memory");
            fence_gpu();
            red_rlx(rdy_of(p, sb, 160 + 32 * w, 0), 1u);
            red_rlx(rdy_of(p, sb, 160 + 32 * w, 1), 1u);
            if (id == 0 && w == 0) red_rlx(&g_epoch, 1u);
            TR(12 + w, true);
        }
        return;
    }
    cta_sync();
    TR(18, tid == 0 && role == 1);
    if (role == 0 && w == NW - 2) clear_queues<true>(p, sb, id, lane);
    tail_rows(p, role * N1 + id, w, lane);
}

__global__ void k_direct(const Params p, long long T) {
    float wd[16];
#pragma unroll
    for (int i = 0; i < 16; i++) wd[i] = __bfloat162float(p.w_down[i]);
    const float f = __bfloat162float(p.freq[0]);
    for (long long t = blockIdx.x * (long long)blockDim.x + threadIdx.x; t < T; t += (long long)gridDim.x * blockDim.x) {
        float x = __bfloat162float(__float2bfloat16(f * __bfloat162float(p.angle[t])));
        float c = __bfloat162float(__float2bfloat16(cosf(x)));
        uint2 md = down_row(__ldg(p.m + p.idx_in[t]), wd);
        red_v4(g_Sg + p.idx_out[t], c * bflo(md.x), c * bfhi(md.x), c * bflo(md.y), c * bfhi(md.y));
    }
}
__global__ void k_direct_tail(const Params p) {
    __shared__ __align__(16) float sw[96];
    load_tail_weights(p, sw, threadIdx.x);
    __syncthreads();
    uint32_t c2[4];
#pragma unroll
    for (int i = 0; i < 4; i++) c2[i] = ((const uint32_t*)p.centers)[i];
    for (int e = blockIdx.x * blockDim.x + threadIdx.x; e < p.E; e += gridDim.x * blockDim.x) {
        float4 g = __ldcg(g_Sg + e);
        __stcg(g_Sg + e, make_float4(0.f, 0.f, 0.f, 0.f));
        const float Sv[4] = {g.x, g.y, g.z, g.w};
        float4 gs, gr;
        row_gates(sw, c2, __bfloat16_as_ushort(p.dist[e]), gs, gr);
        p.out[e] = finish_row(sw + 64, gs, gr, Sv, __ldg(p.m + e));
    }
}

static bool pick_rows(int E, int n, int rows_max, int mult, uint32_t* rows, uint32_t* magic) {
    for (uint32_t r = (E + n - 1) / n; r <= (uint32_t)rows_max; r++) {
        if (r < 2 || r % mult) continue;
        uint64_t mg = ((1ull << 32) + r - 1) / r;
        uint64_t err = mg * r - (1ull << 32);
        if (err * (uint64_t)n < mg) { *rows = r; *magic = (uint32_t)mg; return true; }
    }
    return false;
}

}

extern "C" void kernel_launch(void* const* d_in, const int* in_sizes, int n_in, void* d_out, int out_size) {
    using namespace gs;
    (void)n_in; (void)out_size;
    Params p;
    p.m = (const uint2*)d_in[0];
    p.idx_in = (const int*)d_in[1];
    p.idx_out = (const int*)d_in[2];
    p.dist = (const __nv_bfloat16*)d_in[3];
    p.angle = (const __nv_bfloat16*)d_in[4];
    p.centers = (const __nv_bfloat16*)d_in[5];
    p.freq = (const __nv_bfloat16*)d_in[6];
    p.w_rbf = (const __nv_bfloat16*)d_in[7];
    p.w_sbf = (const __nv_bfloat16*)d_in[8];
    p.w_down = (const __nv_bfloat16*)d_in[9];
    p.w_up = (const __nv_bfloat16*)d_in[10];
    p.out = (uint2*)d_out;
    p.E = in_sizes[3];
    const long long T = in_sizes[1];
    p.n4 = (int)(T / 4);
    p.rows2 = p.magic2 = 0;
    p.ring = nullptr;

    static int sms = 0, rsv = 0;
    if (!sms) {
        int dev = 0;
        cudaGetDevice(&dev);
        cudaDeviceGetAttribute(&rsv, cudaDevAttrReservedSharedMemoryPerBlock, dev);
        cudaDeviceGetAttribute(&sms, cudaDevAttrMultiProcessorCount, dev);
        cudaFuncSetAttribute(k_main, cudaFuncAttributeMaxDynamicSharedMemorySize, SMEM_BYTES);
    }
    cudaStream_t st = cudaStreamPerThread;
    bool fast = (T % 4 == 0) && T > 0 && sms >= NCTA && rsv == (int)SB && p.E >= 65536 && p.E <= E_MAX &&
                p.E % 4 == 0 && (((uintptr_t)p.m | (uintptr_t)p.idx_in | (uintptr_t)p.idx_out | (uintptr_t)p.angle) & 15) == 0 &&
                pick_rows(p.E, NI, ROWS2_MAX, 2, &p.rows2, &p.magic2);
    p.c1 = 1;
    p.nrows2 = 0u - p.rows2;
    p.rows3 = (p.E + 31) / 32;
    fast = fast && (p.rows2 * (NI - 1) + 2 <= (uint32_t)p.E);
    static const void* tkey[3] = {nullptr, nullptr, nullptr};
    static cudaTextureObject_t tex[3] = {0, 0, 0};
    static long long tlen = -1;
    const void* tptr[3] = {p.idx_in, p.idx_out, p.angle};
    for (int k = 0; fast && k < 3; k++) {
        if (tkey[k] == tptr[k] && tlen == T) continue;
        if (tkey[k]) cudaDestroyTextureObject(tex[k]);
        tkey[k] = nullptr;
        cudaResourceDesc rd = {};
        rd.resType = cudaResourceTypeLinear;
        rd.res.linear.devPtr = (void*)tptr[k];
        rd.res.linear.desc = cudaCreateChannelDesc(32, 32, k < 2 ? 32 : 0, k < 2 ? 32 : 0, cudaChannelFormatKindUnsigned);
        rd.res.linear.sizeInBytes = (size_t)T * (k < 2 ? 4 : 2);
        cudaTextureDesc td = {};
        td.readMode = cudaReadModeElementType;
        if (cudaCreateTextureObject(&tex[k], &rd, &td, nullptr) == cudaSuccess) tkey[k] = tptr[k];
        else { (void)cudaGetLastError(); fast = false; }
    }
    if (fast) tlen = T;
    p.t_in = tex[0]; p.t_out = tex[1]; p.t_ang = tex[2];
    if (fast) {
        void* ring = nullptr;
        cudaGetSymbolAddress(&ring, g_ring);
        uintptr_t a = ((uintptr_t)ring + WIN - 1) & ~(uintptr_t)(WIN - 1);
        if (a >> 32 != (a + RING_BYTES - 1) >> 32) a += RING_BYTES;
        p.ring = (unsigned char*)a;
        p.ring_lo = (uint32_t)a;
        p.ring_hi = (uint32_t)(a >> 32);
        k_main<<<NCTA, NT, SMEM_BYTES, st>>>(p);
    } else {
        k_direct<<<sms * 8, 256, 0, st>>>(p, T);
        k_direct_tail<<<sms * 4, 256, 0, st>>>(p);
    }
}
```

```cpp
#include <cuda_runtime.h>
#include <cuda_bf16.h>
#include <stdint.h>

#define CFG_N1 56
#define CFG_NI 22
#define CFG_NW 28
#define CFG_P1W 14
#define CFG_GPW 2
#define CFG_KR 1
#define CFG_SMPAD 0
#define CFG_QPW 3
#define CFG_TG 2
#define CFG_PMASK 8
#define CFG_PSTREAK 1
#define CFG_NBT 1
#define CFG_KM 5
#define CFG_KN 9
#define CFG_TBD 4
#define CFG_P0 500
#define CFG_NTK 16
#define CFG_PFD 200
#define CFG_C1SLEEP 200
#define CFG_TH 14
#define CFG_TS 200
#define CFG_POLL 64
#define CFG_HINT 20000
#define CFG_BSLEEP 100
#define CFG_CSLEEP 200
#define CFG_FSLEEP 100
#define CFG_PSLEEP 100
#define CFG_DRY 1
#define CFG_PROBES 4

namespace gs {

constexpr int E_MAX = 640000;
constexpr int N1 = CFG_N1, NI = CFG_NI, N2 = 2 * NI, N3 = 32, NCTA = N1 + N2 + N3;
constexpr int H2 = NI, H3 = N3 / 2;
constexpr int NB = NI * N3;
constexpr int NW = CFG_NW, NT = NW * 32;
constexpr int GPW = CFG_GPW, NF = NI / GPW;
constexpr int QPW = CFG_QPW, NBT = CFG_NBT;
constexpr int P1W = CFG_P1W, P2W = (N1 + QPW - 1) / QPW, P3W = NI;
constexpr int NQ1 = 32, NQ2 = 64;
constexpr int ROWS2_MAX = ((E_MAX + NI - 1) / NI + 31) / 8 * 8;
constexpr int ROWS3_MAX = (E_MAX / 32 + 31) / 32 * 32;
constexpr int NTAIL = N1 + N2;
constexpr int NPC = 5, WPP = 5, RPC = NTAIL * WPP * 8;
constexpr int GUARD = 1 << 26;
static_assert(NCTA % 4 == 0 && NCTA <= 192, "roles come in CTA pairs, per partition");
static_assert(NI % GPW == 0 && (GPW == 2 || GPW == 4) && QPW >= NBT && QPW <= 4 && NI <= 32 && N1 <= 62, "queue ownership");
static_assert(P1W + NF + 2 <= NW && P2W + 2 <= NW && P3W + 1 <= NW && P1W * 256 + 64 < 8192, "warp roles");
static_assert(ROWS2_MAX + 8 <= 32768 && ROWS3_MAX <= 32768, "index bits");

constexpr uint32_t SB = 1024;
constexpr int SM_DONE = 0, SM_DONE2 = 8;
constexpr int SM_MISC = 16;
constexpr int SM_FIN = 48;
constexpr int SM_STAT = 64;
constexpr int SM_CNT2 = 128;
constexpr int SM_W = 256;
constexpr int SM_PUB = SM_W + 384;
constexpr int SM_PROBE = SM_PUB + 768;
constexpr int SM_CRED = 1792;
constexpr int SM_DATA = 2048;
constexpr int cmax(int a, int b) { return a > b ? a : b; }
constexpr int A_CNT = SM_DATA;
constexpr int A_LIST = A_CNT + NB * 4;
constexpr int KR = CFG_KR, LISTB = (GPW * 32 + 8 * KR) * 4;
constexpr int A_ST = (A_LIST + NF * LISTB + 127) / 128 * 128;
constexpr int A_END = A_ST + NB * 256;
constexpr int B_TA = SM_DATA;
constexpr int B_TB = B_TA + (ROWS2_MAX + 8) * 4;
constexpr int B_END = B_TB + (ROWS2_MAX + 8) * 2;
constexpr int C_S = SM_DATA;
constexpr int C_END = C_S + ROWS3_MAX * 8;
constexpr int T_G = SM_DATA, T_END = T_G + NPC * WPP * 6144;
constexpr int ZEND = cmax(A_END, C_END);
constexpr int SM_ZERO = (cmax(cmax(A_END, B_END), cmax(C_END, T_END)) + 127) / 128 * 128;
constexpr int SMEM_BYTES = SM_ZERO + 4096 + CFG_SMPAD;
static_assert(SMEM_BYTES <= 232448 && SM_PROBE + 128 <= SM_CRED, "shared memory");
static_assert(NPC * RPC >= ROWS3_MAX && NPC * WPP + 2 <= NW, "tail");

constexpr uint32_t FIN = 0x80000000u;

constexpr uint32_t WIN = 524288;
constexpr int CWIN = N2 + N3, NWIN = CWIN + 2, CPAIRS = 31;
constexpr uint32_t PROBE_OFF = (uint32_t)NWIN * WIN;
constexpr int NPROBE = 16;
static_assert(NWIN <= NCTA && NPROBE <= NW, "windows");
constexpr size_t RING_BYTES = (size_t)PROBE_OFF + WIN;
__device__ __align__(128) unsigned char g_ring[2 * RING_BYTES + WIN];
__device__ __align__(128) uint32_t g_S[2][32][ROWS3_MAX];
__device__ __align__(128) float4 g_Sg[E_MAX];
__device__ uint32_t g_dirty[E_MAX / 32];
__device__ uint32_t g_epoch;

#define TR(ev, on)
#define ACC_DECL
#define ACC(i, n)
#define ACC_SAVE

struct Params {
    const uint2* m;
    const int* idx_in;
    const int* idx_out;
    const __nv_bfloat16* dist;
    const __nv_bfloat16* angle;
    const __nv_bfloat16* centers;
    const __nv_bfloat16* freq;
    const __nv_bfloat16* w_rbf;
    const __nv_bfloat16* w_sbf;
    const __nv_bfloat16* w_down;
    const __nv_bfloat16* w_up;
    uint2* out;
    unsigned char* ring;
    cudaTextureObject_t t_in, t_out, t_ang;
    int E, n4;
    uint32_t rows2, nrows2, magic2, rows3;
    uint32_t ring_lo, ring_hi, c1;
};

__device__ __forceinline__ float bflo(uint32_t w) { return __uint_as_float(w << 16); }
__device__ __forceinline__ float bfhi(uint32_t w) { return __uint_as_float(w & 0xffff0000u); }
__device__ __forceinline__ uint32_t pack_bf2(float lo, float hi) {
    uint32_t r;
    asm("cvt.rn.bf16x2.f32 %0, %1, %2;" : "=r"(r) : "f"(hi), "f"(lo));
    return r;
}
__device__ __forceinline__ uint32_t mul_bf2(uint32_t a, uint32_t b) {
    uint32_t r;
    asm("mul.rn.bf16x2 %0, %1, %2;" : "=r"(r) : "r"(a), "r"(b));
    return r;
}
__device__ __forceinline__ uint32_t sub_bf2(uint32_t a, uint32_t b) {
    uint32_t r;
    asm("sub.rn.bf16x2 %0, %1, %2;" : "=r"(r) : "r"(a), "r"(b));
    return r;
}
__device__ __forceinline__ uint32_t maxabs_bf2(uint32_t a, uint32_t b) {
    uint32_t r;
    asm("max.NaN.xorsign.abs.bf16x2 %0, %1, %2;" : "=r"(r) : "r"(a), "r"(b));
    return r;
}
__device__ __forceinline__ void mbar_init(uint32_t a, uint32_t n) {
    asm volatile("mbarrier.init.shared::cta.b64 [%0], %1;" ::"r"(a), "r"(n) : "memory");
}
__device__ __forceinline__ void mbar_arrive(uint32_t a) {
    asm volatile("mbarrier.arrive.shared::cta.b64 _, [%0];" ::"r"(a) : "memory");
}
__device__ __forceinline__ void mbar_arrive_n(uint32_t a, uint32_t n) {
    asm volatile("mbarrier.arrive.shared::cta.b64 _, [%0], %1;" ::"r"(a), "r"(n) : "memory");
}
__device__ __forceinline__ void mbar_arrive_if(uint32_t a, bool on) {
    asm volatile("{.reg .pred q; setp.ne.u32 q, %1, 0; @q mbarrier.arrive.shared::cta.b64 _, [%0];}" ::"r"(a), "r"((uint32_t)on) : "memory");
}
__device__ __forceinline__ void mbar_wait(uint32_t a, uint32_t parity) {
    uint32_t ok;
    int guard = 0;
    do {
        asm volatile("{.reg .pred p; mbarrier.try_wait.parity.shared::cta.b64 p, [%1], %2, %3; selp.u32 %0, 1, 0, p;}"
                     : "=r"(ok) : "r"(a), "r"(parity), "r"(CFG_HINT) : "memory");
        if (!ok) {
            if (++guard > GUARD) __trap();
        }
    } while (!ok);
}
__device__ __forceinline__ void cta_sync() { __syncwarp(); __syncthreads(); }
__device__ __forceinline__ void bar_sync(int id, int n) { asm volatile("bar.sync %0, %1;" ::"r"(id), "r"(n) : "memory"); }
__device__ __forceinline__ void bar_arrive(int id, int n) { asm volatile("bar.arrive %0, %1;" ::"r"(id), "r"(n) : "memory"); }
__device__ __forceinline__ bool mbar_test(uint32_t a, uint32_t parity) {
    uint32_t ok;
    asm volatile("{.reg .pred p; mbarrier.test_wait.parity.shared::cta.b64 p, [%1], %2; selp.u32 %0, 1, 0, p;}"
                 : "=r"(ok) : "r"(a), "r"(parity) : "memory");
    return ok;
}
__device__ __forceinline__ uint32_t ld_acq(const uint32_t* p) {
    uint32_t v;
    asm volatile("ld.acquire.gpu.global.u32 %0, [%1];" : "=r"(v) : "l"(p) : "memory");
    return v;
}
__device__ __forceinline__ uint32_t ld_rlx(const uint32_t* p) {
    uint32_t v;
    asm volatile("ld.relaxed.gpu.global.u32 %0, [%1];" : "=r"(v) : "l"(p) : "memory");
    return v;
}
__device__ __forceinline__ void st_rlx(uint32_t* p, uint32_t v) {
    asm volatile("st.relaxed.gpu.global.u32 [%0], %1;" ::"l"(p), "r"(v) : "memory");
}
__device__ __forceinline__ void red_rlx(uint32_t* p, uint32_t v) {
    asm volatile("red.relaxed.gpu.global.add.u32 [%0], %1;" ::"l"(p), "r"(v) : "memory");
}
__device__ __forceinline__ bool elect_one() {
    uint32_t p;
    asm volatile("{.reg .pred P; elect.sync _|P, 0xffffffff; selp.u32 %0, 1, 0, P;}" : "=r"(p));
    return p;
}
__device__ __forceinline__ uint32_t spin_ge(const uint32_t* p, uint32_t target) {
    int guard = 0;
    while (ld_rlx(p) < target) {
        __nanosleep(CFG_POLL);
        if (++guard > GUARD) __trap();
    }
    return ld_acq(p);
}
__device__ __forceinline__ void fence_gpu() { asm volatile("fence.acq_rel.gpu;" ::: "memory"); }
__device__ __forceinline__ void fence_async_smem() { asm volatile("fence.proxy.async.shared::cta;" ::: "memory"); }
__device__ __forceinline__ void fence_async_all() { asm volatile("fence.proxy.async;" ::: "memory"); }
__device__ __forceinline__ void bulk_store(void* g, uint32_t s, uint32_t bytes) {
    asm volatile("cp.async.bulk.global.shared::cta.bulk_group [%0], [%1], %2;" ::"l"(g), "r"(s), "r"(bytes) : "memory");
}
__device__ __forceinline__ void cp16(uint32_t s, const void* g, bool on) {
    asm volatile("{.reg .pred q; setp.ne.u32 q, %2, 0; @q cp.async.cg.shared.global [%0], [%1], 16;}" ::"r"(s), "l"(g), "r"((uint32_t)on) : "memory");
}
__device__ __forceinline__ void cp_commit() { asm volatile("cp.async.commit_group;" ::: "memory"); }
template <int N> __device__ __forceinline__ void cp_wait() { asm volatile("cp.async.wait_group %0;" ::"n"(N) : "memory"); }
__device__ __forceinline__ uint32_t atoms_add(uint32_t a, uint32_t v) {
    uint32_t o;
    asm volatile("atom.shared.add.u32 %0, [%1], %2;" : "=r"(o) : "r"(a), "r"(v) : "memory");
    return o;
}
__device__ __forceinline__ void sts32(uint32_t a, uint32_t v) { asm volatile("st.shared.u32 [%0], %1;" ::"r"(a), "r"(v) : "memory"); }
__device__ __forceinline__ void sts16(uint32_t a, uint32_t v) { asm volatile("st.shared.u16 [%0], %1;" ::"r"(a), "h"((uint16_t)v) : "memory"); }
__device__ __forceinline__ void sts64(uint32_t a, uint32_t x, uint32_t y) { asm volatile("st.shared.v2.u32 [%0], {%1,%2};" ::"r"(a), "r"(x), "r"(y) : "memory"); }
__device__ __forceinline__ uint32_t lds32(uint32_t a) {
    uint32_t v;
    asm volatile("ld.shared.u32 %0, [%1];" : "=r"(v) : "r"(a) : "memory");
    return v;
}
__device__ __forceinline__ uint2 lds64(uint32_t a) {
    uint2 v;
    asm volatile("ld.shared.v2.u32 {%0,%1}, [%2];" : "=r"(v.x), "=r"(v.y) : "r"(a));
    return v;
}
__device__ __forceinline__ uint2 lds64v(uint32_t a) {
    uint2 v;
    asm volatile("ld.volatile.shared.v2.u32 {%0,%1}, [%2];" : "=r"(v.x), "=r"(v.y) : "r"(a) : "memory");
    return v;
}
__device__ __forceinline__ uint32_t lds32v(uint32_t a) {
    uint32_t v;
    asm volatile("ld.volatile.shared.u32 %0, [%1];" : "=r"(v) : "r"(a) : "memory");
    return v;
}
__device__ __forceinline__ uint4 lds128(uint32_t a) {
    uint4 v;
    asm volatile("ld.shared.v4.u32 {%0,%1,%2,%3}, [%4];" : "=r"(v.x), "=r"(v.y), "=r"(v.z), "=r"(v.w) : "r"(a) : "memory");
    return v;
}
__device__ __forceinline__ void sts128(uint32_t a, uint4 v) {
    asm volatile("st.shared.v4.u32 [%0], {%1,%2,%3,%4};" ::"r"(a), "r"(v.x), "r"(v.y), "r"(v.z), "r"(v.w) : "memory");
}
#define LD_Q "ld.relaxed.gpu.global"
__device__ __forceinline__ uint4 ldg_q128(const void* p) {
    uint4 v;
    asm volatile(LD_Q ".v4.u32 {%0,%1,%2,%3}, [%4];"
                 : "=r"(v.x), "=r"(v.y), "=r"(v.z), "=r"(v.w) : "l"(p) : "memory");
    return v;
}
__device__ __forceinline__ uint2 ldg_q64(const void* p) {
    uint2 v;
    asm volatile(LD_Q ".v2.u32 {%0,%1}, [%2];" : "=r"(v.x), "=r"(v.y) : "l"(p) : "memory");
    return v;
}
__device__ __forceinline__ void red_v4(float4* p, float a, float b, float c, float d) {
    asm volatile("red.global.add.v4.f32 [%0], {%1,%2,%3,%4};" ::"l"(p), "f"(a), "f"(b), "f"(c), "f"(d) : "memory");
}
__device__ __forceinline__ uint2 down_row(uint2 r, const float* wd) {
    float x0 = bflo(r.x), x1 = bfhi(r.x), x2 = bflo(r.y), x3 = bfhi(r.y);
    float y[4];
#pragma unroll
    for (int j = 0; j < 4; j++) y[j] = x0 * wd[j] + x1 * wd[4 + j] + x2 * wd[8 + j] + x3 * wd[12 + j];
    return make_uint2(pack_bf2(y[0], y[1]), pack_bf2(y[2], y[3]));
}
__device__ __forceinline__ uint32_t prmt(uint32_t a, uint32_t b, uint32_t s) {
    uint32_t r;
    asm("prmt.b32 %0, %1, %2, %3;" : "=r"(r) : "r"(a), "r"(b), "r"(s));
    return r;
}
__device__ __forceinline__ uint32_t bitsel(uint32_t a, uint32_t b, uint32_t m) {
    uint32_t r;
    asm("lop3.b32 %0, %1, %2, %3, 0xE4;" : "=r"(r) : "r"(a), "r"(b), "r"(m));
    return r;
}
__device__ __forceinline__ uint32_t pack_h2(float lo, float hi) {
    uint32_t r;
    asm("cvt.rn.f16x2.f32 %0, %1, %2;" : "=r"(r) : "f"(hi), "f"(lo));
    return r;
}
__device__ __forceinline__ uint32_t mul_h2(uint32_t a, uint32_t b) {
    uint32_t r;
    asm("mul.rn.f16x2 %0, %1, %2;" : "=r"(r) : "r"(a), "r"(b));
    return r;
}
__device__ __forceinline__ uint32_t lds32nv(uint32_t a) {
    uint32_t v;
    asm volatile("ld.shared.u32 %0, [%1];" : "=r"(v) : "r"(a));
    return v;
}
__device__ __forceinline__ uint32_t lds16nv(uint32_t a) {
    uint32_t v;
    asm volatile("ld.shared.u16 %0, [%1];" : "=r"(v) : "r"(a));
    return v;
}
#define X_CR1
#define X_CR2
#define X_ST1
#define X_ST2
#define ST_Q "st.relaxed.gpu.global"
__device__ __forceinline__ void stg_q128(void* p, uint32_t a, uint32_t b, uint32_t c, uint32_t d, bool on) {
    asm volatile("{.reg .pred q; setp.ne.u32 q, %5, 0; @q " ST_Q ".v4.u32 [%0], {%1,%2,%3,%4};}"
                 ::"l"(p), "r"(a), "r"(b), "r"(c), "r"(d), "r"((uint32_t)on) : "memory");
}
__device__ __forceinline__ void stg_q64(void* p, uint32_t a, uint32_t b, bool on) {
    asm volatile("{.reg .pred q; setp.ne.u32 q, %3, 0; @q " ST_Q ".v2.u32 [%0], {%1,%2};}"
                 ::"l"(p), "r"(a), "r"(b), "r"((uint32_t)on) : "memory");
}
__device__ __forceinline__ void st_rlx_if(uint32_t* p, uint32_t v, bool on) {
    asm volatile("{.reg .pred q; setp.ne.u32 q, %2, 0; @q st.relaxed.gpu.global.u32 [%0], %1;}" ::"l"(p), "r"(v), "r"((uint32_t)on) : "memory");
}
__device__ __forceinline__ uint32_t ld_rlx_if(const uint32_t* p, bool on) {
    uint32_t v;
    asm volatile("{.reg .pred q; setp.ne.u32 q, %2, 0; mov.b32 %0, 0; @q ld.relaxed.gpu.global.u32 %0, [%1];}" : "=&r"(v) : "l"(p), "r"((uint32_t)on) : "memory");
    return v;
}
__device__ __forceinline__ void ldq128_keep(uint4& v, const void* p, bool on) {
    asm volatile("{.reg .pred q; setp.ne.u32 q, %5, 0; @q ld.relaxed.gpu.global.v4.u32 {%0,%1,%2,%3}, [%4];}"
                 : "+r"(v.x), "+r"(v.y), "+r"(v.z), "+r"(v.w) : "l"(p), "r"((uint32_t)on) : "memory");
}
__device__ __forceinline__ void ldq64_keep(uint2& v, const void* p, bool on) {
    asm volatile("{.reg .pred q; setp.ne.u32 q, %3, 0; @q ld.relaxed.gpu.global.v2.u32 {%0,%1}, [%2];}"
                 : "+r"(v.x), "+r"(v.y) : "l"(p), "r"((uint32_t)on) : "memory");
}
__device__ __forceinline__ void atoms_add_keep(uint32_t& o, uint32_t a, uint32_t v, bool on) {
    asm volatile("{.reg .pred q; setp.ne.u32 q, %3, 0; @q atom.shared.add.u32 %0, [%1], %2;}" : "+r"(o) : "r"(a), "r"(v), "r"((uint32_t)on) : "memory");
}
__device__ __forceinline__ void reds_add(uint32_t a, uint32_t v) { asm volatile("red.shared.add.u32 [%0], %1;" ::"r"(a), "r"(v) : "memory"); }
__device__ __forceinline__ void sts32_if(uint32_t a, uint32_t v, bool on) {
    asm volatile("{.reg .pred q; setp.ne.u32 q, %2, 0; @q st.shared.u32 [%0], %1;}" ::"r"(a), "r"(v), "r"((uint32_t)on) : "memory");
}
__device__ __forceinline__ void sts64_if(uint32_t a, uint32_t x, uint32_t y, bool on) {
    asm volatile("{.reg .pred q; setp.ne.u32 q, %3, 0; @q st.shared.v2.u32 [%0], {%1,%2};}" ::"r"(a), "r"(x), "r"(y), "r"((uint32_t)on) : "memory");
}
__device__ __forceinline__ void lds128_keep(uint4& v, uint32_t a, bool on) {
    asm volatile("{.reg .pred q; setp.ne.u32 q, %5, 0; @q ld.volatile.shared.v4.u32 {%0,%1,%2,%3}, [%4];}"
                 : "+r"(v.x), "+r"(v.y), "+r"(v.z), "+r"(v.w) : "r"(a), "r"((uint32_t)on) : "memory");
}
__device__ __forceinline__ void or3_if(uint32_t& x, uint32_t a, uint32_t b, bool on) {
    asm("{.reg .pred q; setp.ne.u32 q, %3, 0; @q lop3.b32 %0, %0, %1, %2, 0xfe;}" : "+r"(x) : "r"(a), "r"(b), "r"((uint32_t)on));
}
__device__ __forceinline__ uint32_t clk() {
    uint32_t t;
    asm volatile("mov.u32 %0, %%clock;" : "=r"(t) :: "memory");
    return t;
}
__device__ __forceinline__ void sg_add(int row, float a, float b, float c, float d) {
    red_v4(g_Sg + row, a, b, c, d);
    st_rlx(g_dirty + (row >> 5), 1u);
}
__device__ __forceinline__ void slow_add(const uint2* m, uint32_t sb, int in, int out, float c) {
    const uint2 r = __ldg(m + in);
    const float x[4] = {bflo(r.x), bfhi(r.x), bflo(r.y), bfhi(r.y)};
    float y[4] = {0.f, 0.f, 0.f, 0.f};
#pragma unroll
    for (int k = 0; k < 4; k++) {
        const uint4 q = lds128(sb + SM_W + 320 + k * 16);
        y[0] = k ? y[0] + x[k] * __uint_as_float(q.x) : x[k] * __uint_as_float(q.x);
        y[1] = k ? y[1] + x[k] * __uint_as_float(q.y) : x[k] * __uint_as_float(q.y);
        y[2] = k ? y[2] + x[k] * __uint_as_float(q.z) : x[k] * __uint_as_float(q.z);
        y[3] = k ? y[3] + x[k] * __uint_as_float(q.w) : x[k] * __uint_as_float(q.w);
    }
    const uint32_t lo = pack_bf2(y[0], y[1]), hi = pack_bf2(y[2], y[3]);
    sg_add(out, c * bflo(lo), c * bfhi(lo), c * bflo(hi), c * bfhi(hi));
}

struct Mat4 { uint32_t b[4]; };
__device__ __forceinline__ Mat4 load_mat4(const __nv_bfloat16* w, int lane) {
    const unsigned short* u = (const unsigned short*)w + (lane >> 2 & 1);
    const bool on = lane >> 3 == (lane & 3);
    Mat4 m;
#pragma unroll
    for (int k = 0; k < 4; k++) m.b[k] = on ? u[(k & 1) * 8 + (k & 2)] | (uint32_t)u[(k & 1) * 8 + 4 + (k & 2)] << 16 : 0u;
    return m;
}
__device__ __forceinline__ void mul4(const uint4& x, const Mat4& m, float (&y)[8]) {
#pragma unroll
    for (int h = 0; h < 2; h++)
        asm("mma.sync.aligned.m16n8k16.row.col.f32.bf16.bf16.f32 {%0,%1,%2,%3}, {%4,%5,%6,%7}, {%8,%9}, {%10,%10,%10,%10};"
            : "=f"(y[2 * h]), "=f"(y[2 * h + 1]), "=f"(y[4 + 2 * h]), "=f"(y[5 + 2 * h])
            : "r"(x.x), "r"(x.z), "r"(x.y), "r"(x.w), "r"(m.b[2 * h]), "r"(m.b[2 * h + 1]), "f"(0.f));
}

struct Scale { uint32_t eb[4]; bool allslow; };
__device__ __forceinline__ void md_stats(const uint4& in, const Mat4& wd, int lane) {
    float y[8];
    mul4(in, wd, y);
    uint32_t mx[4], se[4];
#pragma unroll
    for (int c = 0; c < 4; c++) {
        uint32_t a = __float_as_uint(y[c]) & 0x7fffffffu, b = __float_as_uint(y[4 + c]) & 0x7fffffffu;
        if (a >= 0x7f800000u) a = 0;
        if (b >= 0x7f800000u) b = 0;
        mx[c] = __reduce_max_sync(0xffffffffu, max(a, b));
        se[c] = __reduce_add_sync(0xffffffffu, (a >> 23) + (b >> 23) + (a ? 1u << 20 : 0u) + (b ? 1u << 20 : 0u));
    }
    if (lane < 4) {
        asm volatile("red.shared.max.u32 [%0], %1;" ::"r"(SB + SM_STAT + lane * 4), "r"(lane == 0 ? mx[0] : lane == 1 ? mx[1] : lane == 2 ? mx[2] : mx[3]) : "memory");
        reds_add(SB + SM_STAT + 16 + lane * 4, lane == 0 ? se[0] : lane == 1 ? se[1] : lane == 2 ? se[2] : se[3]);
    }
}
__device__ __forceinline__ Scale get_scale(uint32_t sb) {
    Scale s;
    s.allslow = false;
#pragma unroll
    for (int k = 0; k < 4; k++) {
        const uint32_t mx = lds32(sb + SM_STAT + 4 * k), se = lds32(sb + SM_STAT + 16 + 4 * k);
        const uint32_t mean = (uint32_t)__fdividef((float)(se & 0xfffffu), (float)max(se >> 20, 1u));
        uint32_t eb = min(min((mx + 0x6e0000u) >> 23, mean + 5u), 227u);
        if (eb < 27u) { s.allslow = s.allslow || mx != 0; eb = 27u; }
        if (eb > 170u) s.allslow = true;
        s.eb[k] = eb;
    }
    return s;
}

__device__ __forceinline__ uint32_t probe_rt(uint32_t* p) {
    uint32_t best = 0xffffffffu;
#pragma unroll 1
    for (int r = 0; r < CFG_PROBES; r++) {
        const uint32_t t0 = clock();
        uint32_t v;
        asm volatile("atom.relaxed.gpu.global.add.u32 %0, [%1], 1;" : "=r"(v) : "l"(p) : "memory");
        if (v > 100000u) __trap();
        const uint32_t t1 = clock();
        best = min(best, t1 - t0);
    }
    return best;
}
__device__ __forceinline__ uint32_t* pub_ptr(const Params& p, int blk, uint32_t sel) {
    const int pr = blk / 44;
    return (uint32_t*)(p.ring + PROBE_OFF + (pr ? 4096u << pr : 0u) + (sel << 12) + 2176 + (blk - pr * 44) * 32);
}
__device__ __forceinline__ void probe(const Params& p, uint32_t sb, int w, int lane) {
    const int blk = blockIdx.x, pr = w >> 1;
    uint32_t off = PROBE_OFF + blk * 16 + (pr ? 4096u << pr : 0u);
    if (pr == 7) off = blk < NWIN ? blk * WIN + 4064 : PROBE_OFF + 3584 + blk % 16 * 32;
    off += (w & 1) * 4096;
    if (lane < 8) st_rlx((uint32_t*)(p.ring + (off & ~31u)) + lane, 0u);
    if (lane == 0) sts32(sb + SM_PROBE + w * 4, probe_rt((uint32_t*)(p.ring + off)));
}
__device__ __forceinline__ void assign_role(const Params& p, uint32_t sb, int lane) {
    {
        const bool x = lane < 8 && lds32(sb + SM_PROBE + lane * 8 + 4) < lds32(sb + SM_PROBE + lane * 8);
        const uint32_t near = __ballot_sync(0xffffffffu, x), bits = near & 1 ? ~near | 1u : near;
        const uint32_t tag = (lds32(sb + SM_MISC + 16) + 1) << 30;
        if (lane < 16) st_rlx(pub_ptr(p, blockIdx.x, lane >> 3) + (lane & 7), tag | (bits & 0xffu));
        constexpr int K = (NCTA + 31) / 32;
        __nanosleep(CFG_P0);
        uint32_t v[K], bad;
        int guard = 0;
        do {
            bad = 0;
#pragma unroll
            for (int k = 0; k < K; k++) {
                const int b = min(lane + 32 * k, NCTA - 1);
                v[k] = ld_rlx(pub_ptr(p, b, near >> (b / 44) & 1));
                bad |= v[k] ^ tag;
            }
            bad = __any_sync(0xffffffffu, bad >> 30);
            if (bad) __nanosleep(CFG_PSLEEP);
            if (++guard > GUARD) __trap();
        } while (bad);
#pragma unroll
        for (int k = 0; k < K; k++) sts32(sb + SM_PUB + (lane + 32 * k) * 4, v[k]);
    }
    __syncwarp();
    constexpr int NP = NCTA / 2, NTAB = H2 + H3;
    const int me = blockIdx.x >> 1, odd = blockIdx.x & 1;
    uint32_t pp[3], key[3];
    int n1 = 0;
#pragma unroll
    for (int k = 0; k < 3; k++) {
        const int i = lane + 32 * k;
        pp[k] = lds32(sb + SM_PUB + min(i, NP - 1) * 8) & 1;
        key[k] = (i * CFG_KM % CFG_KN) << 8 | i;
        n1 += 2 * __popc(__ballot_sync(0xffffffffu, i < NP && pp[k]));
    }
    bool fixed = n1 < NTAB || NCTA - n1 < NTAB;
    if (fixed) {
        n1 = NP / 2 * 2;
        pp[0] = pp[1] = pp[2] = lane & 1;
    }
    const uint32_t mine = __shfl_sync(0xffffffffu, (me < 32 ? key[0] : me < 64 ? key[1] : key[2]) * 2 + (me < 32 ? pp[0] : me < 64 ? pp[1] : pp[2]), me & 31);
    const int part = mine & 1;
    int pos = odd;
#pragma unroll
    for (int k = 0; k < 3; k++) pos += 2 * __popc(__ballot_sync(0xffffffffu, lane + 32 * k < NP && pp[k] == (uint32_t)part && key[k] < mine / 2));
    const int role = pos < H2 ? 1 : pos < NTAB ? 2 : 0;
    const int id = pos < H2 ? part * H2 + pos : pos < NTAB ? part * H3 + pos - H2 : (part ? NCTA - n1 - NTAB : 0) + pos - NTAB;
    const uint32_t v = lds32(sb + SM_PUB + lane * 4);
    uint32_t lin = 0;
#pragma unroll
    for (int b = 0; b < 6; b++) lin |= (__popc(__ballot_sync(0xffffffffu, (v >> (b + 1)) & 1)) > 16 ? 1u : 0u) << b;
    if (lane == 0) {
        sts32(sb + SM_MISC, role << 8 | id);
        sts32(sb + SM_MISC + 4, lin);
        sts32(sb + SM_MISC + 8, NCTA - n1 - NTAB);
        sts32(sb + SM_MISC + 20, part);
        sts32(sb + SM_MISC + 12, role == 0 ? id : role == 1 ? N1 + id : N1 + N2 + id);
    }
}
__device__ __forceinline__ uint32_t sel_of(uint32_t sb, int widx, uint32_t k, int part) {
    return (__popc(k & lds32(sb + SM_MISC + 4)) ^ (lds32(sb + SM_PUB + widx * 4) >> 7) ^ part) & 1;
}
__device__ __forceinline__ uint32_t gran_off(uint32_t sb, int widx, int k, int part) { return (2 * k + sel_of(sb, widx, k, part)) << 12; }
__device__ __forceinline__ uint32_t q1a_off(uint32_t sb, int src, int blk, int part) { return gran_off(sb, 2 * blk + part, src >> 1, part) + (src & 1) * 2048; }
__device__ __forceinline__ uint32_t q1h_off(uint32_t sb, int src, int blk, int part) { return gran_off(sb, 2 * blk + part, 32 + (src >> 2), part) + (src & 3) * 1024; }
__device__ __forceinline__ uint32_t* ctl_word(const Params& p, uint32_t sb, int k, int word, int part) {
    const int widx = CWIN + lds32(sb + SM_MISC + 16);
    return (uint32_t*)(p.ring + (widx * WIN + ((2 * k + sel_of(sb, widx, k, part)) << 12))) + word;
}
__device__ __forceinline__ uint32_t* cred1_of(const Params& p, uint32_t sb, int src) { return ctl_word(p, sb, src >> 3, (src & 7) * 128, src >= (int)lds32(sb + SM_MISC + 8)); }
__device__ __forceinline__ uint32_t* fin1_of(const Params& p, uint32_t sb, int dst) { return ctl_word(p, sb, 8 + (dst >> 3), (dst & 7) * 128, dst / H2); }
__device__ __forceinline__ uint32_t* cred2_of(const Params& p, uint32_t sb, int src) { return ctl_word(p, sb, 16 + (src >> 3), (src & 7) * 128, src / H2); }
__device__ __forceinline__ uint32_t* fin2_of(const Params& p, uint32_t sb, int dst) { return ctl_word(p, sb, 24 + (dst >> 3), (dst & 7) * 128, dst / H3); }
__device__ __forceinline__ uint32_t* rdy_of(const Params& p, uint32_t sb, int word, int part) { return ctl_word(p, sb, 28, word, part); }
__device__ __forceinline__ uint32_t q2_off(uint32_t sb, int blk, int dst) {
    return (N2 + dst) * WIN + gran_off(sb, N2 + dst, (blk >> 1) * 4 + (blk & 1), dst / H3);
}
template <bool IS1>
__device__ __forceinline__ void clear_queues(const Params& p, uint32_t sb, int id, int lane) {
    constexpr int NA = (N1 + 1) / 2, NG = NA + (N1 + 3) / 4, N = IS1 ? NG * N2 : NI * 2;
    if (IS1 && lane == 0) spin_ge(rdy_of(p, sb, 320, lds32(sb + SM_MISC + 20)), NTAIL);
    __syncwarp();
    fence_async_smem();
    for (int k = IS1 ? id + lane * N1 : lane; k < N; k += IS1 ? 32 * N1 : 32) {
        const int wi = k / NG, g = k - wi * NG;
        const uint32_t off = IS1 ? wi * WIN + gran_off(sb, wi, g < NA ? g : 32 + g - NA, wi & 1) : q2_off(sb, k >> 1, id) + (k & 1) * 16384;
        bulk_store(p.ring + off, sb + SM_ZERO, 4096);
    }
    asm volatile("cp.async.bulk.commit_group;" ::: "memory");
    asm volatile("cp.async.bulk.wait_group 0;" ::: "memory");
    if (!IS1) {
        fence_async_all();
        __syncwarp();
        fence_gpu();
        if (lane < NI) red_rlx(rdy_of(p, sb, id / H3 * H2 + lane, id / H3), 1u);
    }
    __syncwarp();
}

struct In8 { uint4 a[2], o[2]; uint2 g[2]; };
__device__ __forceinline__ void p1_load(const Params& p, In8& r, int i4) {
#pragma unroll
    for (int u = 0; u < 2; u++) {
        [[maybe_unused]] uint32_t x, y;
        asm volatile("tex.1d.v4.u32.s32 {%0,%1,%2,%3}, [%4, {%5}];" : "=r"(r.a[u].x), "=r"(r.a[u].y), "=r"(r.a[u].z), "=r"(r.a[u].w) : "l"(p.t_in), "r"(i4 + u * 32));
        asm volatile("tex.1d.v4.u32.s32 {%0,%1,%2,%3}, [%4, {%5}];" : "=r"(r.o[u].x), "=r"(r.o[u].y), "=r"(r.o[u].z), "=r"(r.o[u].w) : "l"(p.t_out), "r"(i4 + u * 32));
        asm volatile("tex.1d.v4.u32.s32 {%0,%1,%2,%3}, [%4, {%5}];" : "=r"(r.g[u].x), "=r"(r.g[u].y), "=r"(x), "=r"(y) : "l"(p.t_ang), "r"(i4 + u * 32));
    }
}
__device__ __forceinline__ uint32_t imad(uint32_t a, uint32_t b, uint32_t c) {
    uint32_t r;
    asm("mad.lo.u32 %0, %1, %2, %3;" : "=r"(r) : "r"(a), "r"(b), "r"(c));
    return r;
}
__device__ __forceinline__ unsigned char* ring_ptr(const Params& p, uint32_t lo) {
    uint64_t r;
    asm("mov.b64 %0, {%1, %2};" : "=l"(r) : "r"(lo), "r"(p.ring_hi));
    return (unsigned char*)r;
}
__device__ __forceinline__ uint32_t keep32(uint32_t x) {
    return __shfl_sync(0xffffffffu, x, threadIdx.x & 31);
}
__device__ __forceinline__ uint32_t opaque32(uint32_t x) {
    asm volatile("" : "+r"(x));
    return x;
}
template <typename T> __device__ __forceinline__ T* opaque(T* p) {
    asm volatile("" : "+l"(p));
    return p;
}
template <int LUT> __device__ __forceinline__ uint32_t lop3(uint32_t a, uint32_t b, uint32_t c) {
    uint32_t r;
    asm("lop3.b32 %0, %1, %2, %3, %4;" : "=r"(r) : "r"(a), "r"(b), "r"(c), "n"(LUT));
    return r;
}
__device__ __forceinline__ uint32_t dp4(uint32_t a, uint32_t b, uint32_t c) {
    uint32_t r;
    asm("dp4a.u32.u32 %0, %1, %2, %3;" : "=r"(r) : "r"(a), "r"(b), "r"(c));
    return r;
}
__device__ __forceinline__ uint32_t dp2(uint32_t a, uint32_t b, uint32_t c) {
    uint32_t r;
    asm("dp2a.lo.u32.u32 %0, %1, %2, %3;" : "=r"(r) : "r"(a), "r"(b), "r"(c));
    return r;
}
__device__ __forceinline__ void p1_put(uint32_t sb, uint32_t wa, uint32_t wb, uint32_t old, bool on) {
    asm volatile("{.reg .pred q; setp.ne.u32 q, %3, 0; @q st.shared.v2.u32 [%0], {%1,%2};}"
                 ::"r"(sb + A_ST + prmt(old, wb, 0xf762)), "r"(wa), "r"(prmt(wb, old, 0x7210)), "r"((uint32_t)on) : "memory");
}
__device__ __forceinline__ void p1_slow_tile(const Params& p, uint32_t sb, int i4) {
    const float f = __bfloat162float(p.freq[0]);
#pragma unroll 1
    for (int u = 0; u < 8; u++) {
        const int k4 = i4 + (u >> 2) * 32;
        if (k4 < p.n4) {
            const size_t t = (size_t)k4 * 4 + (u & 3);
            const float x = __bfloat162float(__float2bfloat16(f * __bfloat162float(p.angle[t])));
            slow_add(p.m, sb, p.idx_in[t], p.idx_out[t], __bfloat162float(__float2bfloat16(cosf(x))));
        }
    }
}
__device__ __forceinline__ void role_p1(const Params& p, uint32_t sb, int id, int w, int lane) {
    lane = keep32(lane);
    const uint32_t f2 = (uint32_t)__bfloat16_as_ushort(p.freq[0]) * 0x10001u;
    constexpr int TG = CFG_TG, NTK = CFG_NTK;
    static_assert(N1 * P1W % NTK == 0 && (NTK == 16 || NTK == 8) && P1W % 2 == 0, "tickets");
    const int first = (N1 * P1W + (id * P1W + w) % NTK) * (TG * 64);
    uint32_t* const tickets = opaque(ctl_word(p, sb, 29 + (id * P1W + w) % NTK / 8, (id * P1W + w) % 8 * 128 + lane, w & 1));
    auto draw = [&]() {
        uint32_t t = 0;
        asm volatile("{.reg .pred q; setp.eq.u32 q, %2, 0; @q atom.relaxed.gpu.global.add.u32 %0, [%1], 1;}" : "+r"(t) : "l"(tickets), "r"(lane) : "memory");
        return t;
    };
    int i4 = (id * P1W + w) * (TG * 64);
    In8 r;
    ACC_DECL
    uint32_t tk = draw();
    p1_load(p, r, i4 + lane);
    while (i4 < p.n4) {
        const int cur = i4;
        i4 += 64;
        if (i4 % (TG * 64) == 0) {
            i4 = min(__shfl_sync(0xffffffffu, tk, 0), 0x7fffffffu / (NTK * TG * 64) - N1 * P1W / NTK - 2) * (NTK * TG * 64) + first;
            tk = draw();
        }
        uint32_t wa[8], wb[8], x2[4];
        x2[0] = mul_bf2(r.g[0].x, f2); x2[1] = mul_bf2(r.g[0].y, f2);
        x2[2] = mul_bf2(r.g[1].x, f2); x2[3] = mul_bf2(r.g[1].y, f2);
        const uint32_t mx = maxabs_bf2(maxabs_bf2(x2[0], x2[1]), maxabs_bf2(x2[2], x2[3]));
        const bool fast = __all_sync(0xffffffffu, cur + 64 <= p.n4 && ((mx & 0x7fffu) <= 0x4300u) && ((mx & 0x7fff0000u) <= 0x43000000u));
        {
            const uint32_t in[8] = {r.a[0].x, r.a[0].y, r.a[0].z, r.a[0].w, r.a[1].x, r.a[1].y, r.a[1].z, r.a[1].w};
            const uint32_t ou[8] = {r.o[0].x, r.o[0].y, r.o[0].z, r.o[0].w, r.o[1].x, r.o[1].y, r.o[1].z, r.o[1].w};
#pragma unroll
            for (int j = 0; j < 8; j += 2) {
                const uint32_t ch = mul_h2(pack_h2(__cosf(bflo(x2[j >> 1])), __cosf(bfhi(x2[j >> 1]))), 0x24002400u);
#pragma unroll
                for (int k = j; k < j + 2; k++) {
                    const uint32_t blk = __umulhi(in[k], p.magic2), il = imad(blk, p.nrows2, in[k]);
                    wa[k] = k & 1 ? bitsel(ch, il, 0xffff0000u) : imad(ch, 65536u, il);
                    wb[k] = imad(blk, 1u << 21, imad(ou[k] >> 5, 1u - (1u << 21), ou[k] << 16));
                }
            }
        }
        p1_load(p, r, i4 + lane);
        if (fast) {
            uint32_t old[8], any = 0;
#pragma unroll
            for (int j = 0; j < 8; j++) old[j] = atoms_add(dp2(wb[j], 0x400u, 0u) + (sb + A_CNT), 0x80001u);
#pragma unroll
            for (int j = 0; j < 8; j++) any |= old[j];
            if (!__any_sync(0xffffffffu, any & 0xffe0u)) {
#pragma unroll
                for (int j = 0; j < 8; j++) p1_put(sb, wa[j], wb[j], old[j], true);
            } else {
                uint32_t pend = 0;
#pragma unroll
                for (int j = 0; j < 8; j++) { p1_put(sb, wa[j], wb[j], old[j], !(old[j] & 0xffe0u)); if (old[j] & 0xffe0u) pend |= 1u << j; }
                ACC(0, 1)
                for (int guard = 0; __any_sync(0xffffffffu, pend); guard++) {
                    __nanosleep(CFG_BSLEEP);
                    ACC(1, 1)
#pragma unroll
                    for (int j = 0; j < 8; j++) {
                        if (__any_sync(0xffffffffu, pend >> j & 1)) {
                            const uint32_t c = lds32v(sb + A_CNT + (pend >> j & 1 ? wb[j] >> 16 : 0) * 4);
                            const bool go = (pend >> j & 1) && (((old[j] >> 19) - (c >> 19) + c) & 8191u) < 32u;
                            p1_put(sb, wa[j], wb[j], old[j], go);
                            if (go) pend &= ~(1u << j);
                        }
                    }
                    if (guard > GUARD) __trap();
                }
            }
        } else {
            p1_slow_tile(p, sb, cur + lane);
            __syncwarp();
        }
    }
    __syncwarp();
    mbar_arrive_if(sb + SM_DONE, lane == 0);
    ACC_SAVE
}

__device__ __forceinline__ void role_flush(const Params& p, uint32_t sb, int id, int f, int lane) {
    lane = keep32(lane);
    const int half = lane >> 4, o = lane >> 2, q = lane & 3;
    const uint32_t hm = keep32(half ? 0xffff0000u : 0xffffu), lth = keep32(((1u << lane) - 1) & hm);
    const uint32_t list = sb + A_LIST + f * LISTB, cnt = keep32(sb + A_CNT + (f * GPW * 32 + lane) * 4);
    const uint32_t cred = opaque32(sb + SM_CRED + (half * 32 + f * GPW) * 4);
    const uint32_t pa = opaque32(p.ring_lo + (id >> 1) * 8192 + (id & 1) * 2048 + q * 16);
    const uint32_t ph = opaque32(p.ring_lo + (32 + (id >> 2)) * 8192 + (id & 3) * 1024 + q * 8 - 2048);
    const uint32_t sa = q * 16 + (o & 1) * 64;
    uint32_t qo[GPW], hs[GPW], cr[4] = {0, 0, 0, 0};
#pragma unroll
    for (int g = 0; g < GPW; g++) {
        const int blk = f * GPW + g;
        qo[g] = 32u << 25;
        const uint32_t sa = sel_of(sb, 2 * blk + half, id >> 1, half), sh = sel_of(sb, 2 * blk + half, 32 + (id >> 2), half);
        hs[g] = sa << 31 | (2 * sh + 1 - sa) << 22 | 1u << 24 | (lane & 15) << 15 | (blk * 32 + lane) * 2;
    }
    uint4 x[KR] = {}, y[KR] = {};
    uint32_t c[GPW] = {};
    auto scan = [&]() {
#pragma unroll
        for (int g = 0; g < GPW; g++) c[g] = lds32v(cnt + g * 128);
    };
    auto credits = [&]() {
        if (GPW == 4) { const uint4 v = lds128(cred); cr[0] = v.x; cr[1] = v.y; cr[2] = v.z; cr[3] = v.w; }
        else { const uint2 v = lds64v(cred); cr[0] = v.x; cr[1] = v.y; }
    };
    ACC_DECL
    int guard = 0;
    bool idle = false, done = false;
    while (true) {
        uint32_t fr[GPW], rank[GPW], num = 0, left = 0;
        bool ok[GPW];
        if (idle && !done && __all_sync(0xffffffffu, mbar_test(sb + SM_DONE, 0))) {
            done = true;
            TR(17, f == 0 && lane == 0);
#pragma unroll
            for (int g = 0; g < GPW; g++) {
                const uint32_t u = lds32v(cnt + g * 128) & 31u, hd = hs[g] ^ (u & 16u ? imad(hs[g], 1u << 24, 1u) & 0x01000001u : 0u);
#pragma unroll 3
                for (uint32_t k = 1; k < 16; k++)
                    sts64_if(sb + A_ST + ((hd & 0x7ffu) << 7) + k * 8, p.rows2, (lane * 16 + k) | (hd & 0x1000000u), (u & 15u) && k >= (u & 15u));
                reds_add(cnt + g * 128, ((0u - u) & 15u) * 0x80001u);
            }
            __syncwarp();
            scan();
        }
#pragma unroll
        for (int g = 0; g < GPW; g++) {
            const bool isfull = c[g] & 0xfff0u;
            rank[g] = __popc(__ballot_sync(0xffffffffu, isfull) & lth);
            ok[g] = isfull && (int)(rank[g] << 25) < (int)(cr[g] - qo[g] + (63u << 25));
            ACC(2, __popc(__ballot_sync(0xffffffffu, isfull && !ok[g])))
        }
#pragma unroll
        for (int g = 0; g < GPW; g++) {
            const uint32_t m = __ballot_sync(0xffffffffu, ok[g]), n = __popc(m & hm), all = __popc(m), e = num + rank[g] + (half ? all - n : 0u);
            sts32_if(KR == 2 ? list + (e & 48u) * 4 + (e & 7u) * 8 + (e >> 1 & 4u) : imad(e, 4u, list), bitsel(imad(rank[g], 1u << 25, qo[g]), hs[g], 0x7e000000u), ok[g]);
            if (ok[g]) hs[g] ^= imad(hs[g], 1u << 24, 1u) & 0x01000001u;
            fr[g] = ok[g] ? 0u - 16u : 0u;
            left |= c[g] + fr[g];
            qo[g] = imad(n, 1u << 25, qo[g]);
            num += all;
        }
        __syncwarp();
        ACC(0, 1) ACC(1, num)
        if (num) {
            uint32_t la = list + o * (KR == 2 ? 8 : 4);
            int todo = (int)num - o, rest = num;
            do {
                uint32_t d[KR];
                if (KR == 2) { const uint2 v = lds64v(la); d[0] = v.x; d[KR - 1] = v.y; }
                else {
#pragma unroll
                    for (int k = 0; k < KR; k++) d[k] = lds32v(la + 32 * k);
                }
                while (true) {
                    uint32_t bad = 0;
#pragma unroll
                    for (int k = 0; k < KR; k++) {
                        const uint32_t m = d[k] & 0x7ffu;
                        lds128_keep(x[k], imad(m, 128u, sa) + (sb + A_ST), todo > 8 * k);
                        lds128_keep(y[k], imad(m, 128u, sa ^ 64) + (sb + A_ST), todo > 8 * k);
                    }
#pragma unroll
                    for (int k = 0; k < KR; k++)
                        or3_if(bad, lop3<0x7e>(x[k].y, x[k].w, d[k]), lop3<0x7e>(y[k].y, y[k].w, d[k]), todo > 8 * k);
                    if (!__any_sync(0xffffffffu, (int)imad(bad, 128u, 0u) < 0)) break;
                    if (++guard > GUARD) __trap();
                }
#pragma unroll
                for (int k = 0; k < KR; k++) {
                    const uint32_t mi = d[k] & 0x7e0u, dm = d[k] & 0xbec00000u;
                    x[k].x = bitsel(d[k], x[k].x, 0x40078000u);
                    x[k].y = prmt(x[k].y, x[k].w, 0x5410);
                    x[k].w = prmt(y[k].y, y[k].w, 0x5410);
                    y[k].x = bitsel(d[k], y[k].x, 0x40000000u);
                    y[k].y = y[k].z;
                    stg_q128(ring_ptr(p, dp4(dm, 0x20000000u, imad(mi, WIN / 32, pa))), x[k].x, x[k].y, x[k].z, x[k].w, X_ST1 todo > 8 * k);
                    stg_q64(ring_ptr(p, dp4(dm, 0x10200000u, imad(mi, WIN / 32, ph))), y[k].x, y[k].y, X_ST1 todo > 8 * k);
                }
                la += 32 * KR;
                todo -= 8 * KR;
                rest -= 8 * KR;
            } while (rest > 0);
#pragma unroll
            for (int g = 0; g < GPW; g++) c[g] = atoms_add(cnt + g * 128, fr[g]) + fr[g];
            credits();
            idle = num <= CFG_TH;
            if (done && !__any_sync(0xffffffffu, left & 0xffffu)) break;
            if (idle) { __nanosleep(CFG_TS); scan(); credits(); }
        } else {
            if (done && !__any_sync(0xffffffffu, left & 0xffffu)) break;
            idle = true;
            __nanosleep(CFG_FSLEEP);
            scan();
            credits();
            if (++guard > GUARD) __trap();
        }
    }
#pragma unroll
    for (int g = 0; g < GPW; g++) st_rlx_if(fin1_of(p, sb, half * H2 + f * GPW + g) + id, qo[g] - (32u << 25) + 1u, (lane & 15) == 0);
    mbar_arrive_if(sb + SM_DONE2, lane == 0);
    TR(18, f == 0 && lane == 0);
    ACC_SAVE
}
__device__ __forceinline__ void role_credit1(const Params& p, uint32_t sb, int id, int lane) {
    const uint32_t* const cred = cred1_of(p, sb, id) + lane * 2;
    for (int guard = 0; !__all_sync(0xffffffffu, mbar_test(sb + SM_DONE2, 0)); guard++) {
        const uint2 v = ldg_q64(cred);
        sts64(sb + SM_CRED + lane * 8, v.x, v.y);
        __nanosleep(CFG_C1SLEEP);
        if (guard > GUARD) __trap();
    }
}

__device__ __forceinline__ float h2f(uint32_t h) {
    float f;
    asm("{.reg .b16 t; cvt.u16.u32 t, %1; cvt.f32.f16 %0, t;}" : "=f"(f) : "r"(h));
    return f;
}
__device__ __forceinline__ void p2_slow(const Params& p, uint32_t sb, const uint32_t* tmp, int row0, uint32_t dst) {
#pragma unroll 1
    for (int j = 0; j < 4; j++)
        if (tmp[8 + j] & 0x40u) slow_add(p.m, sb, row0 + (tmp[j] & 0x7fffu), (tmp[4 + j] & 0x7fffu) * 32 + dst, h2f(tmp[j] >> 16) * 64.0f);
}
__device__ __forceinline__ uint32_t mul_h2_hi(uint32_t a, uint32_t b) {
    uint32_t r;
    asm("{.reg .b16 l, h; .reg .b32 t; mov.b32 {l, h}, %2; mov.b32 t, {h, h}; mul.rn.f16x2 %0, %1, t;}" : "=r"(r) : "r"(a), "r"(b));
    return r;
}
template <bool CHECK>
__device__ __forceinline__ void role_p2(const Params& p, uint32_t sb, int id, int w, int lane) {
    lane = keep32(lane);
    const int part = id / H2, blk = id - part * H2, row0 = blk * p.rows2;
    const int o = lane >> 2, q = lane & 3;
    uint32_t* const cbase = (uint32_t*)(p.ring + (CWIN + lds32(sb + SM_MISC + 16)) * WIN);
    const uint32_t cred = opaque32((uint32_t)(uintptr_t)(cbase + part * 32 + blk));
    const uint32_t pa = opaque32(p.ring_lo + (2 * blk + part) * WIN + q * 16), ph = opaque32(pa - q * 8);
    const uint32_t po = opaque32(p.ring_lo + (q2_off(sb, blk, part * H3) & ~4096u) + q * 16 + (o & 1) * 64);
    const uint32_t sel = __ballot_sync(0xffffffffu, q2_off(sb, blk, part * H3 + (lane & 15)) & 4096u) << 12;
    const uint32_t* const fins = fin1_of(p, sb, id);
    uint32_t st[QPW] = {}, sq[QPW] = {};
    uint4 qa[NBT];
    uint2 qh[NBT];
    auto load = [&](int k) {
        qa[k] = ldg_q128(ring_ptr(p, pa + (bitsel(sq[k], st[k] >> 19, 0x7f800u) & 0x7ffc0u)));
        qh[k] = ldg_q64(ring_ptr(p, ph + (bitsel(sq[k] >> 9, st[k] >> 20, 0x7fc00u) & 0x7ffe0u)));
    };
#pragma unroll
    for (int k = 0; k < QPW; k++) {
        const int src = w * QPW + k;
        st[k] = o << 25 | (src < N1 ? 1u : 5u);
        sq[k] = src < N1 ? q1h_off(sb, src, blk, part) << 9 | q1a_off(sb, src, blk, part) | (uint32_t)(cred1_of(p, sb, src) - cbase) / 8 : 0x7e000u * 513u;
    }
#pragma unroll
    for (int k = 0; k < NBT; k++) load(k);
    ACC_DECL
    int guard = 0;
    uint32_t streak = 0;
    while (true) {
        uint32_t nn[NBT], xx[NBT][4], hh[NBT][2], dd[NBT], any = 0;
        bool last = false;
#pragma unroll
        for (int k = 0; k < NBT; k++) {
            const uint4 a = qa[k];
            const uint2 h = qh[k];
            uint32_t n = 8;
            const uint32_t miss = __ballot_sync(0xffffffffu, (int)imad((a.x ^ st[k]) & (h.x ^ st[k]), 2u, 0u) >= 0);
            if (miss) {
                n = (__ffs(miss) - 1) >> 2;
                if (!__any_sync(0xffffffffu, st[k] & 8u)) { if (streak < CFG_PSTREAK) n &= CFG_PMASK; }
                else if (!__any_sync(0xffffffffu, ((st[k] >> 6) + ((n - o) << 19) ^ st[k]) & 0x1f80000u)) { st[k] |= 4u; last = true; }
            }
            ACC(1, n == 0) ACC(2, n != 0) ACC(3, n)
            st[k] = imad(n, 1u << 25, st[k]);
            st_rlx_if((uint32_t*)ring_ptr(p, imad(sq[k] & 0x7f0u, 32u, cred)), st[k], X_CR1 lane == 0 && n);
            xx[k][0] = bitsel(a.x, 0x00040000u, 0xbff87fffu); xx[k][1] = a.z; xx[k][2] = h.x & 0xbfffffffu; xx[k][3] = h.y;
            hh[k][0] = a.y; hh[k][1] = a.w; dd[k] = a.x >> 13 & 0x3cu; nn[k] = n;
            any |= n;
        }
        if (!any) {
#pragma unroll
            for (int k = 0; k < QPW; k++) {
                const uint32_t fin = ld_rlx(fins + ((sq[k] >> 12 & 62u) | (sq[k] >> 11 & 1u)));
                if (fin & 1u) st[k] |= (fin >> 6 & 0x1f80000u) | 8u;
            }
            if (++guard > GUARD) __trap();
            streak++;
        } else streak = 0;
        if (last) {
            uint32_t all = 4u;
#pragma unroll
            for (int k = 0; k < QPW; k++) all &= st[k];
            last = __all_sync(0xffffffffu, all);
        }
        {
            uint32_t t[QPW], u[QPW];
#pragma unroll
            for (int k = 0; k < QPW; k++) { t[k] = st[(k + NBT) % QPW]; u[k] = sq[(k + NBT) % QPW]; }
#pragma unroll
            for (int k = 0; k < QPW; k++) { st[k] = t[k]; sq[k] = u[k]; }
        }
#pragma unroll
        for (int k = 0; k < NBT; k++) load(k);
#pragma unroll
      for (int k = 0; k < NBT; k++) {
        if (nn[k]) {
            const uint32_t* const x = xx[k];
            const uint32_t h0 = hh[k][0], h1 = hh[k][1], d4 = dd[k];
            const bool v = o < nn[k];
            uint32_t old = 0, ta[4], tb[4], w0[4], w1[4];
            atoms_add_keep(old, sb + SM_CNT2 + d4, 0x10001u, q == 0 && v);
#pragma unroll
            for (int j = 0; j < 4; j++) {
                ta[j] = lds32nv(dp2(x[j], 4u, 0u) + (sb + B_TA));
                tb[j] = lds16nv(dp2(x[j], 2u, 0u) + (sb + B_TB));
            }
            old = __shfl_sync(0xffffffffu, old, lane & 28);
            const uint32_t tag = old << 8 & 0x40000000u;
#pragma unroll
            for (int j = 0; j < 4; j++) {
                const uint32_t z = prmt(j & 2 ? h1 : h0, 0, j & 1 ? 0x4342 : 0x4140);
                const uint32_t t23 = prmt((ta[j] & 0x60076007u) * 2050u, tb[j], 0x5341) & 0xfffcffffu;
                w0[j] = (imad(z, 128u, j & 1 ? 0u : tag) & 0x78007800u) | mul_h2_hi(ta[j] & 0x9ff89ff8u, x[j]);
                w1[j] = (imad(z, 2048u, 0u) & 0x78007800u) | mul_h2_hi(t23, x[j]);
            }
            if (CHECK && v && ((tb[0] | tb[1] | tb[2] | tb[3]) & 0x40u)) {
                uint32_t tmp[12];
#pragma unroll
                for (int j = 0; j < 4; j++) {
                    tmp[j] = x[j]; tmp[4 + j] = (j & 2 ? h1 : h0) >> (j & 1 ? 16 : 0); tmp[8 + j] = tb[j];
                    if (tb[j] & 0x40u) { w0[j] &= 0x78007800u; w1[j] &= 0x78007800u; }
                }
                p2_slow(p, sb, tmp, row0, part * H3 + d4 / 4);
            }
            const uint32_t off = (bitsel(old >> 9, old >> 7, 0x0f80u) & 0x4f80u) + imad(d4, WIN / 4, (sel >> (d4 / 4) & 4096u) + po);
            bool wait = old & (0x10000u - NQ2);
            if (!__any_sync(0xffffffffu, wait)) {
                stg_q128(ring_ptr(p, off), w0[0], w1[0], w0[1], w1[1], X_ST2 v);
                stg_q128(ring_ptr(p, off ^ 64u), w0[2], w1[2], w0[3], w1[3], X_ST2 v);
            } else {
                bool pend = v;
                ACC(0, 1)
                for (int g2 = 0;; g2++) {
                    stg_q128(ring_ptr(p, off), w0[0], w1[0], w0[1], w1[1], pend && !wait);
                    stg_q128(ring_ptr(p, off ^ 64u), w0[2], w1[2], w0[3], w1[3], pend && !wait);
                    pend = wait;
                    if (!__any_sync(0xffffffffu, pend)) break;
                    __nanosleep(CFG_BSLEEP);
                    const uint32_t c = lds32v(sb + SM_CNT2 + d4);
                    wait = pend && (((old >> 16) - (c >> 16) + c) & 0xffffu) >= NQ2;
                    if (g2 > GUARD) __trap();
                }
            }
        }
      }
        if (last) break;
    }
    TR(17, w == 0 && lane == 0);
    __syncwarp();
    uint32_t rank = 0;
    if (lane == 0) { __threadfence_block(); rank = atoms_add(sb + SM_FIN, 1u); __threadfence_block(); }
    if (__shfl_sync(0xffffffffu, rank, 0) == P2W - 1 && lane < 16)
        st_rlx(fin2_of(p, sb, part * H3 + lane) + blk, FIN | (((lds32v(sb + SM_CNT2 + lane * 4) >> 16) - NQ2) & 0xffffu));
    __syncwarp();
    mbar_arrive_if(sb + SM_DONE, lane == 0);
    ACC_SAVE
}
__device__ __forceinline__ void role_credit(const Params& p, uint32_t sb, int id, int lane) {
    const uint32_t* const cred = cred2_of(p, sb, id) + (lane & 15);
    uint32_t last = 0;
    for (int guard = 0;; guard++) {
        if (__all_sync(0xffffffffu, mbar_test(sb + SM_DONE, 0))) break;
        const uint32_t c = ld_rlx(cred);
        if (lane < 16 && c != last) reds_add(sb + SM_CNT2 + lane * 4, 0u - ((c - last) & 0xffffu));
        last = c;
        __nanosleep(CFG_CSLEEP);
        if (guard > GUARD) __trap();
    }
}

__device__ __forceinline__ void p3_wrap(uint32_t sb, int id, const uint32_t* tmp) {
    const Scale sc = get_scale(sb);
#pragma unroll 1
    for (int j = 0; j < 8; j++) {
        const uint32_t old = tmp[4 + j], v = tmp[12 + j], nw = old + v, t = (old ^ nw) & (v ^ nw);
        if (t & 0x80008000u) {
            const float k = (t & 0x8000u) ? ((v & 0x8000u) ? -1.0f : 1.0f) : 0.0f;
            const float q = (t & 0x80000000u) ? ((int)v < 0 ? -65536.0f : 65536.0f) : 0.0f;
            const uint32_t e0 = (j & 1) ? sc.eb[2] : sc.eb[0], e1 = (j & 1) ? sc.eb[3] : sc.eb[1];
            const float lo = k * 65536.0f * __uint_as_float((e0 - 10) << 23), hi = (q - k) * __uint_as_float((e1 - 10) << 23);
            if (j & 1) sg_add(tmp[j >> 1] * 32 + id, 0.f, 0.f, lo, hi);
            else sg_add(tmp[j >> 1] * 32 + id, lo, hi, 0.f, 0.f);
        }
    }
}
__device__ __forceinline__ uint32_t p3_val(uint32_t w) {
    const uint32_t mk = prmt(w, 0, 0xBB99);
    return ((w & 0x07ff07ffu) ^ mk) - mk;
}
__device__ __forceinline__ void role_p3(const Params& p, uint32_t sb, int id, int w, int lane) {
    lane = keep32(lane);
    uint32_t* const cred = opaque(cred2_of(p, sb, id / H3 * H2 + w) + id % H3);
    const uint32_t pq = opaque32(p.ring_lo + q2_off(sb, w, id) + lane * 16);
    auto off = [&](uint32_t n) { return (n & 1u) << 11 | (n & 2u) << 13; };
    const uint32_t pp = opaque32(pq - lane * 16 + 2032);
    auto tag_of = [&](uint32_t n) { return ~n << 28; };
    uint32_t n = 0, fin = 0, pr = 0;
    uint4 v[4] = {};
    bool have = false, last = false;
    ACC_DECL
    int guard = 0;
    while (true) {
        const uint32_t ex = tag_of(n);
        const bool ok = have && !__any_sync(0xffffffffu, ((v[0].x ^ ex) | (v[1].x ^ ex) | (v[2].x ^ ex) | (v[3].x ^ ex)) & 0x40000000u);
        if (ok) n++;
        const bool ready = __all_sync(0xffffffffu, (have && !ok) || !((pr ^ tag_of(n)) & 0x40000000u));
        st_rlx_if(cred, n * 16, X_CR2 lane == 0 && ok);
        if (!ok && !ready && __all_sync(0xffffffffu, fin & FIN)) {
            const uint32_t left = __shfl_sync(0xffffffffu, (fin - n * 16) & 0xffffu, 0);
            if (left - 1u > 0x8000u) break;
            if (left < 16u) {
#pragma unroll
                for (int u = 0; u < 4; u++) {
                    v[u] = make_uint4(ex & 0x40000000u, 0, 0, 0);
                    ldq128_keep(v[u], ring_ptr(p, pq + off(n)) + u * 512, u * 4 + (lane >> 3) < left);
                }
                have = last = !__any_sync(0xffffffffu, ((v[0].x ^ ex) | (v[1].x ^ ex) | (v[2].x ^ ex) | (v[3].x ^ ex)) & 0x40000000u);
                pr = ~tag_of(n + have);
                if (++guard > GUARD) __trap();
                continue;
            }
        }
        uint32_t row[8], val[16];
#pragma unroll
        for (int u = 0; u < 4; u++) {
            const uint4 x = v[u];
            row[2 * u] = prmt(bitsel(x.x << 1, x.y >> 3, 0x7000f000u), 0, 0x4431);
            row[2 * u + 1] = prmt(bitsel(x.z << 1, x.w >> 3, 0x7000f000u), 0, 0x4431);
            val[4 * u] = p3_val(x.x); val[4 * u + 1] = p3_val(x.y);
            val[4 * u + 2] = p3_val(x.z); val[4 * u + 3] = p3_val(x.w);
        }
#pragma unroll
        for (int u = 0; u < 4; u++) ldq128_keep(v[u], ring_ptr(p, pq + off(n)) + u * 512, ready);
        pr = ld_rlx((const uint32_t*)ring_ptr(p, pp + off(n + ready)));
        ACC(2, have && !ok)
        have = ready;
        if (!ok) {
            ACC(1, 1)
            fin = ld_rlx(fin2_of(p, sb, id) + w);
            if (++guard > GUARD) __trap();
        } else {
#pragma unroll
            for (int u = 0; u < 4; u += 2) {
                uint32_t old[8], chk = 0;
#pragma unroll
                for (int j = 0; j < 4; j++) {
                    old[2 * j] = atoms_add(sb + C_S + row[2 * u + j] * 4, val[4 * u + 2 * j]);
                    old[2 * j + 1] = atoms_add(sb + C_S + ROWS3_MAX * 4 + row[2 * u + j] * 4, val[4 * u + 2 * j + 1]);
                }
#pragma unroll
                for (int j = 0; j < 8; j++) {
                    const uint32_t nw = old[j] + val[4 * u + j];
                    chk |= (old[j] ^ nw) & (val[4 * u + j] ^ nw);
                }
                if (chk & 0x80008000u) {
                    uint32_t tmp[20];
#pragma unroll
                    for (int j = 0; j < 8; j++) { tmp[j >> 1] = row[2 * u + (j >> 1)]; tmp[4 + j] = old[j]; tmp[12 + j] = val[4 * u + j]; }
                    p3_wrap(sb, id, tmp);
                }
            }
            __syncwarp();
            if (last) break;
        }
    }
    ACC_SAVE
}

__device__ __forceinline__ void row_gates(const float* sw, const uint32_t* c2, uint32_t dbits, float4& gs, float4& gr) {
    const uint32_t d2 = dbits * 0x10001u;
    gs = gr = make_float4(0.f, 0.f, 0.f, 0.f);
#pragma unroll
    for (int r2 = 0; r2 < 4; r2++) {
        uint32_t df = sub_bf2(d2, c2[r2]);
        uint32_t ar = mul_bf2(mul_bf2(df, df), 0xC120C120u);
        uint32_t rb = pack_bf2(__expf(bflo(ar)), __expf(bfhi(ar)));
        const float r0 = bflo(rb), r1 = bfhi(rb);
        const float4 s0 = *(const float4*)(sw + r2 * 8), s1 = *(const float4*)(sw + r2 * 8 + 4);
        const float4 q0 = *(const float4*)(sw + 32 + r2 * 8), q1 = *(const float4*)(sw + 32 + r2 * 8 + 4);
        gs.x += r0 * s0.x + r1 * s1.x; gs.y += r0 * s0.y + r1 * s1.y;
        gs.z += r0 * s0.z + r1 * s1.z; gs.w += r0 * s0.w + r1 * s1.w;
        gr.x += r0 * q0.x + r1 * q1.x; gr.y += r0 * q0.y + r1 * q1.y;
        gr.z += r0 * q0.z + r1 * q1.z; gr.w += r0 * q0.w + r1 * q1.w;
    }
}
__device__ __forceinline__ uint2 finish_row(const float* wu, const float4& gs, const float4& gr, const float S[4], uint2 mrow) {
    const float a[4] = {S[0] * gs.x, S[1] * gs.y, S[2] * gs.z, S[3] * gs.w};
    float u[4] = {0, 0, 0, 0};
#pragma unroll
    for (int k = 0; k < 4; k++) {
        u[0] += a[k] * wu[4 * k]; u[1] += a[k] * wu[4 * k + 1]; u[2] += a[k] * wu[4 * k + 2]; u[3] += a[k] * wu[4 * k + 3];
    }
    return make_uint2(pack_bf2(bflo(mrow.x) + u[0] * gr.x, bfhi(mrow.x) + u[1] * gr.y),
                      pack_bf2(bflo(mrow.y) + u[2] * gr.z, bfhi(mrow.y) + u[3] * gr.w));
}
__device__ __forceinline__ void load_tail_weights(const Params& p, float* sw, int tid) {
    if (tid < 32) sw[tid] = __bfloat162float(p.w_sbf[tid]);
    else if (tid < 64) sw[tid] = __bfloat162float(p.w_rbf[tid - 32]);
    else if (tid < 80) sw[tid] = __bfloat162float(p.w_up[tid - 64]);
    else if (tid < 96) sw[tid] = __bfloat162float(p.w_down[tid - 80]);
}
__device__ __forceinline__ float exp_ftz(float x) {
    float r;
    asm("ex2.approx.ftz.f32 %0, %1;" : "=f"(r) : "f"(x * 1.4426950408889634f));
    return r;
}
__device__ __forceinline__ void tail_rows(const Params& p, int tidx, int w, int lane) {
    constexpr uint32_t sb = SB;
    if (w == NW - 1 && lane < 2) {
        fence_gpu();
        red_rlx(rdy_of(p, sb, 320, lane), 1u);
    }
    if (w >= NPC * WPP) return;
    const int pc = w / WPP, r0 = pc * RPC + (tidx * WPP + w - pc * WPP) * 8, e0 = r0 * 32;
    const uint32_t G = sb + T_G + w * 6144;
    auto edge = [&](int k) { return e0 + (lane & 1) * 128 + (lane >> 1) + (k & 3) * 32 + (k >> 2) * 16; };
    {
        const int g = lane >> 2, t = lane & 3;
        uint32_t dv[16];
#pragma unroll
        for (int k = 0; k < 16; k++) dv[k] = __ldg((const uint32_t*)p.dist + min(e0 / 2 + k * 8 + g, p.E / 2 - 1));
        uint2 mv[8];
#pragma unroll
        for (int k = 0; k < 8; k++) mv[k] = __ldg(p.m + min(edge(k), p.E - 1));
        const uint32_t c2 = ((const uint32_t*)p.centers)[t];
        const unsigned short* wg = (const unsigned short*)(g < 4 ? p.w_sbf : p.w_rbf) + t * 8 + (g & 3);
        const uint32_t b = wg[0] | (uint32_t)wg[4] << 16;
#pragma unroll
        for (int k = 0; k < 8; k++) sts64(G + 4096 + (k * 32 + lane) * 8, mv[k].x, mv[k].y);
        TR(19, w == 0 && lane == 0 && dv[15] + b + c2 != 0x12345);
#pragma unroll
        for (int k = 0; k < 16; k++) {
            uint32_t a[2];
#pragma unroll
            for (int h = 0; h < 2; h++) {
                const uint32_t df = sub_bf2(prmt(dv[k], 0, h ? 0x3232 : 0x1010), c2);
                const uint32_t ar = mul_bf2(mul_bf2(df, df), 0xC120C120u);
                a[h] = pack_bf2(exp_ftz(bflo(ar)), exp_ftz(bfhi(ar)));
            }
            float d[4];
            asm("mma.sync.aligned.m16n8k8.row.col.f32.bf16.bf16.f32 {%0,%1,%2,%3}, {%4,%5}, {%6}, {%7,%7,%7,%7};"
                : "=f"(d[0]), "=f"(d[1]), "=f"(d[2]), "=f"(d[3]) : "r"(a[0]), "r"(a[1]), "r"(b), "f"(0.f));
            const uint32_t at = G + (((k & 1) * 4 + (k >> 1 & 3)) * 32 + g * 4 + (k >> 3)) * 16 + t * 4;
            sts32(at, pack_bf2(d[0], d[1]));
            sts32(at + 32, pack_bf2(d[2], d[3]));
        }
    }
    __syncwarp();
    TR(20, w == 0 && lane == 0);
    const Scale sc = get_scale(sb);
    const float lsb[4] = {__uint_as_float((sc.eb[0] - 10) << 23), __uint_as_float((sc.eb[1] - 10) << 23),
                          __uint_as_float((sc.eb[2] - 10) << 23), __uint_as_float((sc.eb[3] - 10) << 23)};
    TR(2, w == 0 && lane == 0);
    uint32_t dirty = 0;
    uint4 sx[2] = {}, sy[2] = {};
#pragma unroll 1
    for (int pass = CFG_DRY ? 0 : 1; pass < 2; pass++) {
        if (pass) {
            if (w == pc * WPP && lane < 2) spin_ge(rdy_of(p, sb, lane ? 320 : 160 + 32 * pc, lds32(sb + SM_MISC + 20)), lane ? NTAIL : N3);
            __syncwarp();
            bar_sync(1 + pc, WPP * 32);
            TR(3, w == 0 && lane == 0);
            TR(10, w == NPC * WPP - 1 && lane == 0);
            if (r0 >= (int)p.rows3) return;
            const uint32_t* const src = &g_S[0][lane >> 1][r0 + (lane & 1) * 4];
#pragma unroll
            for (int u = 0; u < 2; u++) {
                sx[u] = ldg_q128(src + u * 16 * ROWS3_MAX);
                sy[u] = ldg_q128(src + (u * 16 + 32) * ROWS3_MAX);
            }
            if (lane < 8 && (r0 + lane) * 32 < p.E && (dirty = ld_rlx(g_dirty + r0 + lane))) st_rlx(g_dirty + r0 + lane, 0u);
            dirty = __ballot_sync(0xffffffffu, dirty != 0);
        }
        asm volatile("" : "+r"(lane));
        float wu[16];
#pragma unroll
        for (int k = 0; k < 4; k++) *(uint4*)(wu + 4 * k) = lds128(sb + SM_W + 256 + 16 * k);
        auto finish = [&](int k, uint32_t x, uint32_t y, bool extra) {
            const int e = edge(k);
            float S[4];
            const uint32_t tx = x + 0x80008000u, ty = y + 0x80008000u;
            S[0] = (__uint_as_float(prmt(tx, 0x4b000000u, 0x7610)) - 8421376.0f) * lsb[0];
            S[1] = (__uint_as_float(prmt(tx, 0x4b000000u, 0x7632)) - 8421376.0f) * lsb[1];
            S[2] = (__uint_as_float(prmt(ty, 0x4b000000u, 0x7610)) - 8421376.0f) * lsb[2];
            S[3] = (__uint_as_float(prmt(ty, 0x4b000000u, 0x7632)) - 8421376.0f) * lsb[3];
            if (extra && e < p.E) {
                const float4 g = __ldcg(g_Sg + e);
                S[0] += g.x; S[1] += g.y; S[2] += g.z; S[3] += g.w;
                __stcg(g_Sg + e, make_float4(0.f, 0.f, 0.f, 0.f));
            }
            const uint4 g = lds128(G + (k * 32 + lane) * 16);
            const uint2 o = finish_row(wu, make_float4(bflo(g.x), bfhi(g.x), bflo(g.y), bfhi(g.y)), make_float4(bflo(g.z), bfhi(g.z), bflo(g.w), bfhi(g.w)), S,
                                       lds64v(G + 4096 + (k * 32 + lane) * 8));
            asm volatile("{.reg .pred q; setp.ne.u32 q, %3, 0; @q st.global.v2.u32 [%0], {%1,%2};}"
                         ::"l"(p.out + e), "r"(o.x), "r"(o.y), "r"((uint32_t)(pass && e < p.E)));
        };
        const uint32_t xs[8] = {sx[0].x, sx[0].y, sx[0].z, sx[0].w, sx[1].x, sx[1].y, sx[1].z, sx[1].w};
        const uint32_t ys[8] = {sy[0].x, sy[0].y, sy[0].z, sy[0].w, sy[1].x, sy[1].y, sy[1].z, sy[1].w};
        if (!dirty) {
#pragma unroll
            for (int k = 0; k < 8; k++) finish(k, xs[k], ys[k], false);
        } else {
            uint32_t tmp[16];
#pragma unroll
            for (int k = 0; k < 8; k++) { tmp[k] = xs[k]; tmp[8 + k] = ys[k]; }
#pragma unroll 1
            for (int k = 0; k < 8; k++) finish(k, tmp[k], tmp[8 + k], dirty >> ((lane & 1) * 4 + (k & 3)) & 1);
        }
    }
    TR(9, w == 0 && lane == 0);
    TR(11, w == NPC * WPP - 1 && lane == 0);
}

#define CFG_MAP1 1
__global__ void __launch_bounds__(NT, 1) k_main(const __grid_constant__ Params p) {
    extern __shared__ __align__(1024) unsigned char smem[];
    constexpr uint32_t sb = SB;
    if ((uint32_t)__cvta_generic_to_shared(smem) != SB) __trap();
    const int tid = threadIdx.x, w = __shfl_sync(0xffffffffu, tid >> 5, 0), lane = tid & 31;
    if (w < NPROBE) probe(p, sb, w, lane);
    else {
        if (tid == NT - 1) sts32(sb + SM_MISC + 16, ld_rlx(&g_epoch) & 1);
        if (tid >= NT - 32 && lane < 12) sts32(sb + SM_FIN + lane * 4, 0u);
        load_tail_weights(p, (float*)(smem + SM_W), tid - NPROBE * 32);
    }
    const Mat4 wd = load_mat4(p.w_down, lane);
    cta_sync();
    if (w) {
        const uint4 in = __ldg((const uint4*)p.m + (size_t)(tid - 32) * (p.E / 2) / (NT - 32));
        for (int i = SM_DATA / 16 + tid - 32; i < ZEND / 16; i += NT - 32) ((uint4*)smem)[i] = make_uint4(0, 0, 0, 0);
        if (tid - 32 < 256) ((uint4*)(smem + SM_ZERO))[tid - 32] = make_uint4(0, 0, 0, 0);
        if (tid < 48) sts32(sb + SM_CNT2 + (tid - 32) * 4, NQ2 << 16);
        __syncwarp();
        if (CFG_PFD && tid == NT - 1) {
            __nanosleep(CFG_PFD);
            const uint32_t n = (p.E / 2 + NCTA - 1) / NCTA, o = blockIdx.x * n;
            if (o < (uint32_t)p.E / 2) asm volatile("cp.async.bulk.prefetch.L2.global [%0], %1;" ::"l"((const uint4*)p.m + o), "r"(min(n, p.E / 2 - o) * 16) : "memory");
        }
        __syncwarp();
        md_stats(in, wd, lane);
    } else assign_role(p, sb, lane);
    if (tid == 0) {
        mbar_init(sb + SM_DONE, lds32(sb + SM_MISC) >> 8 ? P2W : P1W);
        mbar_init(sb + SM_DONE2, NF);
    }
    cta_sync();
    const uint32_t rid = __shfl_sync(0xffffffffu, lds32(sb + SM_MISC), 0);
    const int role = rid >> 8, id = rid & 255;
    TR(5, tid == 0);
    if (role == 0) {
        const int ww = CFG_MAP1 == 0 ? ((w & 3) == 3 ? NW : (w >> 2) * 3 + (w & 3)) : CFG_MAP1 == 1 ? (w & 2 ? NW : (w >> 2) * 2 + (w & 1)) : w;
        const int sw = CFG_MAP1 == 0 ? ((w & 3) == 3 ? w >> 2 : NW) : CFG_MAP1 == 1 ? (w & 2 ? (w >> 2) * 2 + (w & 1) : NW) : w - P1W;
        static_assert(CFG_MAP1 == 0 ? (P1W <= NW / 4 * 3 && NF + 2 <= NW / 4) : CFG_MAP1 == 1 ? (P1W <= NW / 2 && NF + 2 <= NW / 2) : true, "warp map");
        for (int i = tid; i < NB; i += NT) sts32(sb + A_CNT + i * 4, 1u << 24);
        if (tid < 64) sts32(sb + SM_CRED + tid * 4, 0u);
        cta_sync();
        TR(1, tid == 0);
        if (ww < P1W) role_p1(p, sb, id, ww, lane);
        else if (sw < NF) role_flush(p, sb, id, sw, lane);
        else if (sw == NF) role_credit1(p, sb, id, lane);
        else if (w == NW - 1) {
            uint4* owin = (uint4*)(p.ring + (CWIN + (lds32(sb + SM_MISC + 16) ^ 1)) * WIN);
            for (int i = id * 32 + lane; i < CPAIRS * 512; i += N1 * 32) __stcg(owin + i, make_uint4(0, 0, 0, 0));
            __syncwarp();
        }
    } else if (role == 1) {
        const int row0 = id % H2 * p.rows2;
        const int nrows = min((int)p.rows2, p.E - row0);
        constexpr int NTB = NT - 32, TBD = CFG_TBD;
        bool flagged = false;
        if (w < NW - 1) {
            const Scale sc = get_scale(sb);
            Mat4 ws;
#pragma unroll
            for (int k = 0; k < 4; k++) ws.b[k] = mul_bf2(wd.b[k], ((246u - (lane & 4 ? sc.eb[(k & 2) + 1] : sc.eb[k & 2])) << 7) * 0x10001u);
            const uint4* const src = (const uint4*)(p.m + row0);
            uint4 r2[TBD], nx[TBD];
            auto fetch = [&](int i) {
#pragma unroll
                for (int k = 0; k < TBD; k++)
                    asm volatile("ld.global.nc.v4.u32 {%0,%1,%2,%3}, [%4];" : "=r"(nx[k].x), "=r"(nx[k].y), "=r"(nx[k].z), "=r"(nx[k].w) : "l"(src + min(i + k * NTB, nrows / 2 - 1)));
            };
            fetch(tid);
#pragma unroll 1
            for (int i0 = tid; 2 * (i0 - lane) < nrows; i0 += TBD * NTB) {
#pragma unroll
                for (int k = 0; k < TBD; k++) r2[k] = make_uint4(nx[k].x, nx[k].z, nx[k].y, nx[k].w);
                fetch(i0 + TBD * NTB);
#pragma unroll
                for (int k = 0; k < TBD; k++) {
                    const int i = i0 + k * NTB;
                    float y[8];
                    mul4(make_uint4(r2[k].x, r2[k].z, r2[k].y, r2[k].w), ws, y);
                    uint32_t a[4], h[4], ta[2];
#pragma unroll
                    for (int j = 0; j < 4; j++) { a[j] = pack_h2(y[2 * j], y[2 * j + 1]); h[j] = a[j] + 0x00040004u; }
#pragma unroll
                    for (int j = 0; j < 2; j++) ta[j] = bitsel(h[2 * j], bitsel(h[2 * j + 1] >> 3, h[2 * j + 1] << 7, 0x00070007u), 0x9ff89ff8u);
                    uint32_t tb = prmt(h[1], h[3], 0x7531);
                    const uint32_t b0 = a[0] | a[1] | h[0] | h[1], b1 = a[2] | a[3] | h[2] | h[3];
                    if (__any_sync(0xffffffffu, ((b0 | b1) & 0x60006000u) || sc.allslow)) {
                        if ((b0 & 0x60006000u) || sc.allslow) { ta[0] = 0; tb = (tb & 0xffff0000u) | 0x40u; }
                        if ((b1 & 0x60006000u) || sc.allslow) { ta[1] = 0; tb = (tb & 0xffffu) | 0x400000u; }
                        flagged = true;
                    }
                    sts64_if(sb + B_TA + i * 8, ta[0], ta[1], 2 * i < nrows);
                    sts32_if(sb + B_TB + i * 4, tb, 2 * i < nrows);
                }
            }
            if (tid == 0) {
                sts32(sb + B_TA + p.rows2 * 4, 0u);
                sts16(sb + B_TB + p.rows2 * 2, 0u);
            }
            TR(8, tid == 0);
        } else if (lane == 0) spin_ge(rdy_of(p, sb, id, id / H2), H3);
        __syncwarp();
        flagged = __any_sync(0xffffffffu, __syncthreads_or(flagged));
        TR(1, tid == 0);
        if (w < P2W) {
            if (flagged) role_p2<true>(p, sb, id, w, lane);
            else role_p2<false>(p, sb, id, w, lane);
        } else if (w == P2W) role_credit(p, sb, id, lane);
    } else {
        if (w == 0) clear_queues<false>(p, sb, id, lane);
        if (tid >= 32 && tid < 33 + NPC) mbar_init(sb + SM_CNT2 + (tid - 32) * 8, 1);
        cta_sync();
        TR(1, tid == 0);
        if (w < P3W) role_p3(p, sb, id, w, lane);
        cta_sync();
        TR(2, tid == 0);
        if (w < NPC && lane == 0) {
            fence_async_smem();
            const int n = min(((int)p.rows3 + 7) / 8 * 8 - w * RPC, RPC);
            if (w) mbar_wait(sb + SM_CNT2 + w * 8, 0);
            if (n > 0) {
                bulk_store(g_S[0][id] + w * RPC, sb + C_S + w * RPC * 4, n * 4);
                bulk_store(g_S[1][id] + w * RPC, sb + C_S + (ROWS3_MAX + w * RPC) * 4, n * 4);
            }
            asm volatile("cp.async.bulk.commit_group;" ::: "memory");
            asm volatile("cp.async.bulk.wait_group.read 0;" ::: "memory");
            mbar_arrive(sb + SM_CNT2 + w * 8 + 8);
            asm volatile("cp.async.bulk.wait_group 0;" ::: "memory");
            fence_gpu();
            red_rlx(rdy_of(p, sb, 160 + 32 * w, 0), 1u);
            red_rlx(rdy_of(p, sb, 160 + 32 * w, 1), 1u);
            if (id == 0 && w == 0) red_rlx(&g_epoch, 1u);
            TR(12 + w, true);
        }
        return;
    }
    cta_sync();
    TR(18, tid == 0 && role == 1);
    if (role == 0 && w == NW - 2) clear_queues<true>(p, sb, id, lane);
    tail_rows(p, role * N1 + id, w, lane);
}

__global__ void k_direct(const Params p, long long T) {
    float wd[16];
#pragma unroll
    for (int i = 0; i < 16; i++) wd[i] = __bfloat162float(p.w_down[i]);
    const float f = __bfloat162float(p.freq[0]);
    for (long long t = blockIdx.x * (long long)blockDim.x + threadIdx.x; t < T; t += (long long)gridDim.x * blockDim.x) {
        float x = __bfloat162float(__float2bfloat16(f * __bfloat162float(p.angle[t])));
        float c = __bfloat162float(__float2bfloat16(cosf(x)));
        uint2 md = down_row(__ldg(p.m + p.idx_in[t]), wd);
        red_v4(g_Sg + p.idx_out[t], c * bflo(md.x), c * bfhi(md.x), c * bflo(md.y), c * bfhi(md.y));
    }
}
__global__ void k_direct_tail(const Params p) {
    __shared__ __align__(16) float sw[96];
    load_tail_weights(p, sw, threadIdx.x);
    __syncthreads();
    uint32_t c2[4];
#pragma unroll
    for (int i = 0; i < 4; i++) c2[i] = ((const uint32_t*)p.centers)[i];
    for (int e = blockIdx.x * blockDim.x + threadIdx.x; e < p.E; e += gridDim.x * blockDim.x) {
        float4 g = __ldcg(g_Sg + e);
        __stcg(g_Sg + e, make_float4(0.f, 0.f, 0.f, 0.f));
        const float Sv[4] = {g.x, g.y, g.z, g.w};
        float4 gs, gr;
        row_gates(sw, c2, __bfloat16_as_ushort(p.dist[e]), gs, gr);
        p.out[e] = finish_row(sw + 64, gs, gr, Sv, __ldg(p.m + e));
    }
}

static bool pick_rows(int E, int n, int rows_max, int mult, uint32_t* rows, uint32_t* magic) {
    for (uint32_t r = (E + n - 1) / n; r <= (uint32_t)rows_max; r++) {
        if (r < 2 || r % mult) continue;
        uint64_t mg = ((1ull << 32) + r - 1) / r;
        uint64_t err = mg * r - (1ull << 32);
        if (err * (uint64_t)n < mg) { *rows = r; *magic = (uint32_t)mg; return true; }
    }
    return false;
}

}

extern "C" void kernel_launch(void* const* d_in, const int* in_sizes, int n_in, void* d_out, int out_size) {
    using namespace gs;
    (void)n_in; (void)out_size;
    Params p;
    p.m = (const uint2*)d_in[0];
    p.idx_in = (const int*)d_in[1];
    p.idx_out = (const int*)d_in[2];
    p.dist = (const __nv_bfloat16*)d_in[3];
    p.angle = (const __nv_bfloat16*)d_in[4];
    p.centers = (const __nv_bfloat16*)d_in[5];
    p.freq = (const __nv_bfloat16*)d_in[6];
    p.w_rbf = (const __nv_bfloat16*)d_in[7];
    p.w_sbf = (const __nv_bfloat16*)d_in[8];
    p.w_down = (const __nv_bfloat16*)d_in[9];
    p.w_up = (const __nv_bfloat16*)d_in[10];
    p.out = (uint2*)d_out;
    p.E = in_sizes[3];
    const long long T = in_sizes[1];
    p.n4 = (int)(T / 4);
    p.rows2 = p.magic2 = 0;
    p.ring = nullptr;

    static int sms = 0, rsv = 0;
    if (!sms) {
        int dev = 0;
        cudaGetDevice(&dev);
        cudaDeviceGetAttribute(&rsv, cudaDevAttrReservedSharedMemoryPerBlock, dev);
        cudaDeviceGetAttribute(&sms, cudaDevAttrMultiProcessorCount, dev);
        cudaFuncSetAttribute(k_main, cudaFuncAttributeMaxDynamicSharedMemorySize, SMEM_BYTES);
    }
    cudaStream_t st = cudaStreamPerThread;
    bool fast = (T % 4 == 0) && T > 0 && sms >= NCTA && rsv == (int)SB && p.E >= 65536 && p.E <= E_MAX &&
                p.E % 4 == 0 && (((uintptr_t)p.m | (uintptr_t)p.idx_in | (uintptr_t)p.idx_out | (uintptr_t)p.angle) & 15) == 0 &&
                pick_rows(p.E, NI, ROWS2_MAX, 2, &p.rows2, &p.magic2);
    p.c1 = 1;
    p.nrows2 = 0u - p.rows2;
    p.rows3 = (p.E + 31) / 32;
    fast = fast && (p.rows2 * (NI - 1) + 2 <= (uint32_t)p.E);
    static const void* tkey[3] = {nullptr, nullptr, nullptr};
    static cudaTextureObject_t tex[3] = {0, 0, 0};
    static long long tlen = -1;
    const void* tptr[3] = {p.idx_in, p.idx_out, p.angle};
    for (int k = 0; fast && k < 3; k++) {
        if (tkey[k] == tptr[k] && tlen == T) continue;
        if (tkey[k]) cudaDestroyTextureObject(tex[k]);
        tkey[k] = nullptr;
        cudaResourceDesc rd = {};
        rd.resType = cudaResourceTypeLinear;
        rd.res.linear.devPtr = (void*)tptr[k];
        rd.res.linear.desc = cudaCreateChannelDesc(32, 32, k < 2 ? 32 : 0, k < 2 ? 32 : 0, cudaChannelFormatKindUnsigned);
        rd.res.linear.sizeInBytes = (size_t)T * (k < 2 ? 4 : 2);
        cudaTextureDesc td = {};
        td.readMode = cudaReadModeElementType;
        if (cudaCreateTextureObject(&tex[k], &rd, &td, nullptr) == cudaSuccess) tkey[k] = tptr[k];
        else { (void)cudaGetLastError(); fast = false; }
    }
    if (fast) tlen = T;
    p.t_in = tex[0]; p.t_out = tex[1]; p.t_ang = tex[2];
    if (fast) {
        void* ring = nullptr;
        cudaGetSymbolAddress(&ring, g_ring);
        uintptr_t a = ((uintptr_t)ring + WIN - 1) & ~(uintptr_t)(WIN - 1);
        if (a >> 32 != (a + RING_BYTES - 1) >> 32) a += RING_BYTES;
        p.ring = (unsigned char*)a;
        p.ring_lo = (uint32_t)a;
        p.ring_hi = (uint32_t)(a >> 32);
        k_main<<<NCTA, NT, SMEM_BYTES, st>>>(p);
    } else {
        k_direct<<<sms * 8, 256, 0, st>>>(p, T);
        k_direct_tail<<<sms * 4, 256, 0, st>>>(p);
    }
}
```

```cpp
#include <cuda_runtime.h>
#include <cuda_bf16.h>
#include <stdint.h>

#define CFG_N1 56
#define CFG_NI 22
#define CFG_NW 28
#define CFG_P1W 14
#define CFG_GPW 2
#define CFG_KR 1
#define CFG_SMPAD 0
#define CFG_QPW 3
#define CFG_TG 2
#define CFG_PMASK 8
#define CFG_PSTREAK 1
#define CFG_NBT 1
#define CFG_KM 5
#define CFG_KN 9
#define CFG_TBD 4
#define CFG_P0 500
#define CFG_PFD 200
#define CFG_C1SLEEP 200
#define CFG_PK1 6
#define CFG_PK2 8
#define CFG_PK3 11
#define CFG_CLN 2
#define CFG_CLS 300
#define CFG_TH 14
#define CFG_TS 200
#define CFG_POLL 64
#define CFG_HINT 20000
#define CFG_BSLEEP 100
#define CFG_CSLEEP 200
#define CFG_FSLEEP 100
#define CFG_PSLEEP 100
#define CFG_DRY 1
#define CFG_PROBES 4

namespace gs {

constexpr int E_MAX = 640000;
constexpr int N1 = CFG_N1, NI = CFG_NI, N2 = 2 * NI, N3 = 32, NCTA = N1 + N2 + N3;
constexpr int H2 = NI, H3 = N3 / 2;
constexpr int NB = NI * N3;
constexpr int NW = CFG_NW, NT = NW * 32;
constexpr int GPW = CFG_GPW, NF = (NI + GPW - 1) / GPW;
constexpr int QPW = CFG_QPW, NBT = CFG_NBT;
constexpr int P1W = CFG_P1W, P2W = (N1 + QPW - 1) / QPW, P3W = NI;
constexpr int NQ1 = 32, NQ2 = 64;
constexpr int ROWS2_MAX = ((E_MAX + NI - 1) / NI + 31) / 8 * 8;
constexpr int ROWS3_MAX = (E_MAX / 32 + 31) / 32 * 32;
constexpr int NTAIL = N1 + N2;
constexpr int NPC = 5, WPP = 5, RPC = NTAIL * WPP * 8;
constexpr int GUARD = 1 << 26;
static_assert(NCTA % 4 == 0 && NCTA <= 192, "roles come in CTA pairs, per partition");
static_assert((GPW == 2 || GPW == 4) && QPW >= NBT && QPW <= 4 && NI <= 32 && N1 <= 62, "queue ownership");
static_assert(P1W + NF + 2 <= NW && P2W + 2 <= NW && P3W + 1 <= NW && P1W * 256 + 64 < 8192, "warp roles");
static_assert(ROWS2_MAX + 8 <= 32768 && ROWS3_MAX <= 32768, "index bits");

constexpr uint32_t SB = 1024;
constexpr int SM_DONE = 0, SM_DONE2 = 8;
constexpr int SM_MISC = 16;
constexpr int SM_FIN = 48;
constexpr int SM_STAT = 64;
constexpr int SM_CNT2 = 128;
constexpr int SM_W = 256;
constexpr int SM_PUB = SM_W + 384;
constexpr int SM_PROBE = SM_PUB + 768;
constexpr int SM_CRED = 1792;
constexpr int SM_DATA = 2048;
constexpr int cmax(int a, int b) { return a > b ? a : b; }
constexpr int A_CNT = SM_DATA;
constexpr int A_LIST = A_CNT + NF * GPW * 128;
constexpr int KR = CFG_KR, LISTB = (GPW * 32 + 8 * KR) * 4;
constexpr int A_ST = (A_LIST + NF * LISTB + 127) / 128 * 128;
constexpr int A_END = A_ST + NB * 256;
constexpr int B_TA = SM_DATA;
constexpr int B_TB = B_TA + (ROWS2_MAX + 8) * 4;
constexpr int B_END = B_TB + (ROWS2_MAX + 8) * 2;
constexpr int C_S = SM_DATA;
constexpr int C_END = C_S + ROWS3_MAX * 8;
constexpr int T_G = SM_DATA, TWB = 4096 + 2048 + 512, T_END = T_G + NPC * WPP * TWB;
constexpr int ZEND = cmax(A_END, C_END);
constexpr int SM_ZERO = (cmax(C_END, T_END) + 127) / 128 * 128;
constexpr int SMEM_BYTES = cmax(cmax(A_END, B_END), SM_ZERO + 4096) + CFG_SMPAD;
static_assert(SMEM_BYTES <= 232448 && SM_PROBE + 128 <= SM_CRED, "shared memory");
static_assert(NPC * RPC >= ROWS3_MAX && NPC * WPP + 2 <= NW, "tail");

constexpr uint32_t FIN = 0x80000000u;

constexpr uint32_t WIN = 524288;
constexpr int CWIN = N2 + N3, NWIN = CWIN + 2, CPAIRS = 31;
constexpr uint32_t PROBE_OFF = (uint32_t)NWIN * WIN;
constexpr int NPROBE = 16;
static_assert(NWIN <= NCTA && NPROBE <= NW, "windows");
constexpr size_t RING_BYTES = (size_t)PROBE_OFF + WIN;
__device__ __align__(128) unsigned char g_ring[2 * RING_BYTES + WIN];
__device__ __align__(128) uint32_t g_S[2][32][ROWS3_MAX];
__device__ __align__(128) float4 g_Sg[E_MAX];
__device__ uint32_t g_dirty[E_MAX / 32];
__device__ uint32_t g_epoch;

#define TR(ev, on)
#define ACC_DECL
#define ACC(i, n)
#define ACC_SAVE

struct Params {
    const uint2* m;
    const int* idx_in;
    const int* idx_out;
    const __nv_bfloat16* dist;
    const __nv_bfloat16* angle;
    const __nv_bfloat16* centers;
    const __nv_bfloat16* freq;
    const __nv_bfloat16* w_rbf;
    const __nv_bfloat16* w_sbf;
    const __nv_bfloat16* w_down;
    const __nv_bfloat16* w_up;
    uint2* out;
    unsigned char* ring;
    cudaTextureObject_t t_in, t_out, t_ang;
    int E, n4;
    uint32_t rows2, nrows2, magic2, rows3;
    uint32_t ring_lo, ring_hi, c1;
};

__device__ __forceinline__ float bflo(uint32_t w) { return __uint_as_float(w << 16); }
__device__ __forceinline__ float bfhi(uint32_t w) { return __uint_as_float(w & 0xffff0000u); }
__device__ __forceinline__ uint32_t pack_bf2(float lo, float hi) {
    uint32_t r;
    asm("cvt.rn.bf16x2.f32 %0, %1, %2;" : "=r"(r) : "f"(hi), "f"(lo));
    return r;
}
__device__ __forceinline__ uint32_t mul_bf2(uint32_t a, uint32_t b) {
    uint32_t r;
    asm("mul.rn.bf16x2 %0, %1, %2;" : "=r"(r) : "r"(a), "r"(b));
    return r;
}
__device__ __forceinline__ uint32_t sub_bf2(uint32_t a, uint32_t b) {
    uint32_t r;
    asm("sub.rn.bf16x2 %0, %1, %2;" : "=r"(r) : "r"(a), "r"(b));
    return r;
}
__device__ __forceinline__ uint32_t maxabs_bf2(uint32_t a, uint32_t b) {
    uint32_t r;
    asm("max.NaN.xorsign.abs.bf16x2 %0, %1, %2;" : "=r"(r) : "r"(a), "r"(b));
    return r;
}
__device__ __forceinline__ void mbar_init(uint32_t a, uint32_t n) {
    asm volatile("mbarrier.init.shared::cta.b64 [%0], %1;" ::"r"(a), "r"(n) : "memory");
}
__device__ __forceinline__ void mbar_arrive(uint32_t a) {
    asm volatile("mbarrier.arrive.shared::cta.b64 _, [%0];" ::"r"(a) : "memory");
}
__device__ __forceinline__ void mbar_arrive_n(uint32_t a, uint32_t n) {
    asm volatile("mbarrier.arrive.shared::cta.b64 _, [%0], %1;" ::"r"(a), "r"(n) : "memory");
}
__device__ __forceinline__ void mbar_arrive_if(uint32_t a, bool on) {
    asm volatile("{.reg .pred q; setp.ne.u32 q, %1, 0; @q mbarrier.arrive.shared::cta.b64 _, [%0];}" ::"r"(a), "r"((uint32_t)on) : "memory");
}
__device__ __forceinline__ void mbar_wait(uint32_t a, uint32_t parity) {
    uint32_t ok;
    int guard = 0;
    do {
        asm volatile("{.reg .pred p; mbarrier.try_wait.parity.shared::cta.b64 p, [%1], %2, %3; selp.u32 %0, 1, 0, p;}"
                     : "=r"(ok) : "r"(a), "r"(parity), "r"(CFG_HINT) : "memory");
        if (!ok) {
            if (++guard > GUARD) __trap();
        }
    } while (!ok);
}
__device__ __forceinline__ void cta_sync() { __syncwarp(); __syncthreads(); }
__device__ __forceinline__ void bar_sync(int id, int n) { asm volatile("bar.sync %0, %1;" ::"r"(id), "r"(n) : "memory"); }
__device__ __forceinline__ void bar_arrive(int id, int n) { asm volatile("bar.arrive %0, %1;" ::"r"(id), "r"(n) : "memory"); }
__device__ __forceinline__ bool mbar_test(uint32_t a, uint32_t parity) {
    uint32_t ok;
    asm volatile("{.reg .pred p; mbarrier.test_wait.parity.shared::cta.b64 p, [%1], %2; selp.u32 %0, 1, 0, p;}"
                 : "=r"(ok) : "r"(a), "r"(parity) : "memory");
    return ok;
}
__device__ __forceinline__ uint32_t ld_acq(const uint32_t* p) {
    uint32_t v;
    asm volatile("ld.acquire.gpu.global.u32 %0, [%1];" : "=r"(v) : "l"(p) : "memory");
    return v;
}
__device__ __forceinline__ uint32_t ld_rlx(const uint32_t* p) {
    uint32_t v;
    asm volatile("ld.relaxed.gpu.global.u32 %0, [%1];" : "=r"(v) : "l"(p) : "memory");
    return v;
}
__device__ __forceinline__ void st_rlx(uint32_t* p, uint32_t v) {
    asm volatile("st.relaxed.gpu.global.u32 [%0], %1;" ::"l"(p), "r"(v) : "memory");
}
__device__ __forceinline__ void red_rlx(uint32_t* p, uint32_t v) {
    asm volatile("red.relaxed.gpu.global.add.u32 [%0], %1;" ::"l"(p), "r"(v) : "memory");
}
__device__ __forceinline__ bool elect_one() {
    uint32_t p;
    asm volatile("{.reg .pred P; elect.sync _|P, 0xffffffff; selp.u32 %0, 1, 0, P;}" : "=r"(p));
    return p;
}
__device__ __forceinline__ uint32_t spin_ge(const uint32_t* p, uint32_t target) {
    int guard = 0;
    while (ld_rlx(p) < target) {
        __nanosleep(CFG_POLL);
        if (++guard > GUARD) __trap();
    }
    return ld_acq(p);
}
__device__ __forceinline__ void fence_gpu() { asm volatile("fence.acq_rel.gpu;" ::: "memory"); }
__device__ __forceinline__ void fence_async_smem() { asm volatile("fence.proxy.async.shared::cta;" ::: "memory"); }
__device__ __forceinline__ void fence_async_all() { asm volatile("fence.proxy.async;" ::: "memory"); }
__device__ __forceinline__ void bulk_store(void* g, uint32_t s, uint32_t bytes) {
    asm volatile("cp.async.bulk.global.shared::cta.bulk_group [%0], [%1], %2;" ::"l"(g), "r"(s), "r"(bytes) : "memory");
}
__device__ __forceinline__ void cp16(uint32_t s, const void* g, bool on) {
    asm volatile("{.reg .pred q; setp.ne.u32 q, %2, 0; @q cp.async.cg.shared.global [%0], [%1], 16;}" ::"r"(s), "l"(g), "r"((uint32_t)on) : "memory");
}
__device__ __forceinline__ void cp16z(uint32_t s, const void* g, int bytes) {
    asm volatile("cp.async.cg.shared.global [%0], [%1], 16, %2;" ::"r"(s), "l"(g), "r"(bytes) : "memory");
}
__device__ __forceinline__ void cp_commit() { asm volatile("cp.async.commit_group;" ::: "memory"); }
template <int N> __device__ __forceinline__ void cp_wait() { asm volatile("cp.async.wait_group %0;" ::"n"(N) : "memory"); }
__device__ __forceinline__ uint32_t atoms_add(uint32_t a, uint32_t v) {
    uint32_t o;
    asm volatile("atom.shared.add.u32 %0, [%1], %2;" : "=r"(o) : "r"(a), "r"(v) : "memory");
    return o;
}
__device__ __forceinline__ void sts32(uint32_t a, uint32_t v) { asm volatile("st.shared.u32 [%0], %1;" ::"r"(a), "r"(v) : "memory"); }
__device__ __forceinline__ void sts16(uint32_t a, uint32_t v) { asm volatile("st.shared.u16 [%0], %1;" ::"r"(a), "h"((uint16_t)v) : "memory"); }
__device__ __forceinline__ void sts64(uint32_t a, uint32_t x, uint32_t y) { asm volatile("st.shared.v2.u32 [%0], {%1,%2};" ::"r"(a), "r"(x), "r"(y) : "memory"); }
__device__ __forceinline__ uint32_t lds32(uint32_t a) {
    uint32_t v;
    asm volatile("ld.shared.u32 %0, [%1];" : "=r"(v) : "r"(a) : "memory");
    return v;
}
__device__ __forceinline__ uint2 lds64(uint32_t a) {
    uint2 v;
    asm volatile("ld.shared.v2.u32 {%0,%1}, [%2];" : "=r"(v.x), "=r"(v.y) : "r"(a));
    return v;
}
__device__ __forceinline__ uint2 lds64v(uint32_t a) {
    uint2 v;
    asm volatile("ld.volatile.shared.v2.u32 {%0,%1}, [%2];" : "=r"(v.x), "=r"(v.y) : "r"(a) : "memory");
    return v;
}
__device__ __forceinline__ uint32_t lds32v(uint32_t a) {
    uint32_t v;
    asm volatile("ld.volatile.shared.u32 %0, [%1];" : "=r"(v) : "r"(a) : "memory");
    return v;
}
__device__ __forceinline__ uint4 lds128(uint32_t a) {
    uint4 v;
    asm volatile("ld.shared.v4.u32 {%0,%1,%2,%3}, [%4];" : "=r"(v.x), "=r"(v.y), "=r"(v.z), "=r"(v.w) : "r"(a) : "memory");
    return v;
}
__device__ __forceinline__ void sts128(uint32_t a, uint4 v) {
    asm volatile("st.shared.v4.u32 [%0], {%1,%2,%3,%4};" ::"r"(a), "r"(v.x), "r"(v.y), "r"(v.z), "r"(v.w) : "memory");
}
#define LD_Q "ld.relaxed.gpu.global"
__device__ __forceinline__ uint4 ldg_q128(const void* p) {
    uint4 v;
    asm volatile(LD_Q ".v4.u32 {%0,%1,%2,%3}, [%4];"
                 : "=r"(v.x), "=r"(v.y), "=r"(v.z), "=r"(v.w) : "l"(p) : "memory");
    return v;
}
__device__ __forceinline__ uint2 ldg_q64(const void* p) {
    uint2 v;
    asm volatile(LD_Q ".v2.u32 {%0,%1}, [%2];" : "=r"(v.x), "=r"(v.y) : "l"(p) : "memory");
    return v;
}
__device__ __forceinline__ void red_v4(float4* p, float a, float b, float c, float d) {
    asm volatile("red.global.add.v4.f32 [%0], {%1,%2,%3,%4};" ::"l"(p), "f"(a), "f"(b), "f"(c), "f"(d) : "memory");
}
__device__ __forceinline__ uint2 down_row(uint2 r, const float* wd) {
    float x0 = bflo(r.x), x1 = bfhi(r.x), x2 = bflo(r.y), x3 = bfhi(r.y);
    float y[4];
#pragma unroll
    for (int j = 0; j < 4; j++) y[j] = x0 * wd[j] + x1 * wd[4 + j] + x2 * wd[8 + j] + x3 * wd[12 + j];
    return make_uint2(pack_bf2(y[0], y[1]), pack_bf2(y[2], y[3]));
}
__device__ __forceinline__ uint32_t prmt(uint32_t a, uint32_t b, uint32_t s) {
    uint32_t r;
    asm("prmt.b32 %0, %1, %2, %3;" : "=r"(r) : "r"(a), "r"(b), "r"(s));
    return r;
}
__device__ __forceinline__ uint32_t bitsel(uint32_t a, uint32_t b, uint32_t m) {
    uint32_t r;
    asm("lop3.b32 %0, %1, %2, %3, 0xE4;" : "=r"(r) : "r"(a), "r"(b), "r"(m));
    return r;
}
__device__ __forceinline__ uint32_t pack_h2(float lo, float hi) {
    uint32_t r;
    asm("cvt.rn.f16x2.f32 %0, %1, %2;" : "=r"(r) : "f"(hi), "f"(lo));
    return r;
}
__device__ __forceinline__ uint32_t mul_h2(uint32_t a, uint32_t b) {
    uint32_t r;
    asm("mul.rn.f16x2 %0, %1, %2;" : "=r"(r) : "r"(a), "r"(b));
    return r;
}
__device__ __forceinline__ uint32_t lds32nv(uint32_t a) {
    uint32_t v;
    asm volatile("ld.shared.u32 %0, [%1];" : "=r"(v) : "r"(a));
    return v;
}
__device__ __forceinline__ uint32_t lds16nv(uint32_t a) {
    uint32_t v;
    asm volatile("ld.shared.u16 %0, [%1];" : "=r"(v) : "r"(a));
    return v;
}
#define X_CR1
#define X_CR2
#define X_ST1
#define X_ST2
#define ST_Q "st.relaxed.gpu.global"
__device__ __forceinline__ void stg_q128(void* p, uint32_t a, uint32_t b, uint32_t c, uint32_t d, bool on) {
    asm volatile("{.reg .pred q; setp.ne.u32 q, %5, 0; @q " ST_Q ".v4.u32 [%0], {%1,%2,%3,%4};}"
                 ::"l"(p), "r"(a), "r"(b), "r"(c), "r"(d), "r"((uint32_t)on) : "memory");
}
__device__ __forceinline__ void stg_q64(void* p, uint32_t a, uint32_t b, bool on) {
    asm volatile("{.reg .pred q; setp.ne.u32 q, %3, 0; @q " ST_Q ".v2.u32 [%0], {%1,%2};}"
                 ::"l"(p), "r"(a), "r"(b), "r"((uint32_t)on) : "memory");
}
__device__ __forceinline__ void st_rlx_if(uint32_t* p, uint32_t v, bool on) {
    asm volatile("{.reg .pred q; setp.ne.u32 q, %2, 0; @q st.relaxed.gpu.global.u32 [%0], %1;}" ::"l"(p), "r"(v), "r"((uint32_t)on) : "memory");
}
__device__ __forceinline__ uint32_t ld_rlx_if(const uint32_t* p, bool on) {
    uint32_t v;
    asm volatile("{.reg .pred q; setp.ne.u32 q, %2, 0; mov.b32 %0, 0; @q ld.relaxed.gpu.global.u32 %0, [%1];}" : "=&r"(v) : "l"(p), "r"((uint32_t)on) : "memory");
    return v;
}
__device__ __forceinline__ void ldq128_keep(uint4& v, const void* p, bool on) {
    asm volatile("{.reg .pred q; setp.ne.u32 q, %5, 0; @q ld.relaxed.gpu.global.v4.u32 {%0,%1,%2,%3}, [%4];}"
                 : "+r"(v.x), "+r"(v.y), "+r"(v.z), "+r"(v.w) : "l"(p), "r"((uint32_t)on) : "memory");
}
__device__ __forceinline__ void ldq64_keep(uint2& v, const void* p, bool on) {
    asm volatile("{.reg .pred q; setp.ne.u32 q, %3, 0; @q ld.relaxed.gpu.global.v2.u32 {%0,%1}, [%2];}"
                 : "+r"(v.x), "+r"(v.y) : "l"(p), "r"((uint32_t)on) : "memory");
}
__device__ __forceinline__ void atoms_add_keep(uint32_t& o, uint32_t a, uint32_t v, bool on) {
    asm volatile("{.reg .pred q; setp.ne.u32 q, %3, 0; @q atom.shared.add.u32 %0, [%1], %2;}" : "+r"(o) : "r"(a), "r"(v), "r"((uint32_t)on) : "memory");
}
__device__ __forceinline__ void reds_add(uint32_t a, uint32_t v) { asm volatile("red.shared.add.u32 [%0], %1;" ::"r"(a), "r"(v) : "memory"); }
__device__ __forceinline__ void sts32_if(uint32_t a, uint32_t v, bool on) {
    asm volatile("{.reg .pred q; setp.ne.u32 q, %2, 0; @q st.shared.u32 [%0], %1;}" ::"r"(a), "r"(v), "r"((uint32_t)on) : "memory");
}
__device__ __forceinline__ void sts64_if(uint32_t a, uint32_t x, uint32_t y, bool on) {
    asm volatile("{.reg .pred q; setp.ne.u32 q, %3, 0; @q st.shared.v2.u32 [%0], {%1,%2};}" ::"r"(a), "r"(x), "r"(y), "r"((uint32_t)on) : "memory");
}
__device__ __forceinline__ void lds128_keep(uint4& v, uint32_t a, bool on) {
    asm volatile("{.reg .pred q; setp.ne.u32 q, %5, 0; @q ld.volatile.shared.v4.u32 {%0,%1,%2,%3}, [%4];}"
                 : "+r"(v.x), "+r"(v.y), "+r"(v.z), "+r"(v.w) : "r"(a), "r"((uint32_t)on) : "memory");
}
__device__ __forceinline__ void or3_if(uint32_t& x, uint32_t a, uint32_t b, bool on) {
    asm("{.reg .pred q; setp.ne.u32 q, %3, 0; @q lop3.b32 %0, %0, %1, %2, 0xfe;}" : "+r"(x) : "r"(a), "r"(b), "r"((uint32_t)on));
}
__device__ __forceinline__ uint32_t clk() {
    uint32_t t;
    asm volatile("mov.u32 %0, %%clock;" : "=r"(t) :: "memory");
    return t;
}
__device__ __forceinline__ void sg_add(int row, float a, float b, float c, float d) {
    red_v4(g_Sg + row, a, b, c, d);
    st_rlx(g_dirty + (row >> 5), 1u);
}
__device__ __forceinline__ void slow_add(const uint2* m, uint32_t sb, int in, int out, float c) {
    const uint2 r = __ldg(m + in);
    const float x[4] = {bflo(r.x), bfhi(r.x), bflo(r.y), bfhi(r.y)};
    float y[4] = {0.f, 0.f, 0.f, 0.f};
#pragma unroll
    for (int k = 0; k < 4; k++) {
        const uint4 q = lds128(sb + SM_W + 320 + k * 16);
        y[0] = k ? y[0] + x[k] * __uint_as_float(q.x) : x[k] * __uint_as_float(q.x);
        y[1] = k ? y[1] + x[k] * __uint_as_float(q.y) : x[k] * __uint_as_float(q.y);
        y[2] = k ? y[2] + x[k] * __uint_as_float(q.z) : x[k] * __uint_as_float(q.z);
        y[3] = k ? y[3] + x[k] * __uint_as_float(q.w) : x[k] * __uint_as_float(q.w);
    }
    const uint32_t lo = pack_bf2(y[0], y[1]), hi = pack_bf2(y[2], y[3]);
    sg_add(out, c * bflo(lo), c * bfhi(lo), c * bflo(hi), c * bfhi(hi));
}

struct Mat4 { uint32_t b[4]; };
__device__ __forceinline__ Mat4 load_mat4(const __nv_bfloat16* w, int lane) {
    const unsigned short* u = (const unsigned short*)w + (lane >> 2 & 1);
    const bool on = lane >> 3 == (lane & 3);
    Mat4 m;
#pragma unroll
    for (int k = 0; k < 4; k++) m.b[k] = on ? u[(k & 1) * 8 + (k & 2)] | (uint32_t)u[(k & 1) * 8 + 4 + (k & 2)] << 16 : 0u;
    return m;
}
__device__ __forceinline__ void mul4(const uint4& x, const Mat4& m, float (&y)[8]) {
#pragma unroll
    for (int h = 0; h < 2; h++)
        asm("mma.sync.aligned.m16n8k16.row.col.f32.bf16.bf16.f32 {%0,%1,%2,%3}, {%4,%5,%6,%7}, {%8,%9}, {%10,%10,%10,%10};"
            : "=f"(y[2 * h]), "=f"(y[2 * h + 1]), "=f"(y[4 + 2 * h]), "=f"(y[5 + 2 * h])
            : "r"(x.x), "r"(x.z), "r"(x.y), "r"(x.w), "r"(m.b[2 * h]), "r"(m.b[2 * h + 1]), "f"(0.f));
}

struct Scale { uint32_t eb[4]; bool allslow; };
__device__ __forceinline__ void md_stats(const uint4& in, const Mat4& wd, int lane) {
    float y[8];
    mul4(in, wd, y);
    uint32_t mx[4], se[4];
#pragma unroll
    for (int c = 0; c < 4; c++) {
        uint32_t a = __float_as_uint(y[c]) & 0x7fffffffu, b = __float_as_uint(y[4 + c]) & 0x7fffffffu;
        if (a >= 0x7f800000u) a = 0;
        if (b >= 0x7f800000u) b = 0;
        mx[c] = __reduce_max_sync(0xffffffffu, max(a, b));
        se[c] = __reduce_add_sync(0xffffffffu, (a >> 23) + (b >> 23) + (a ? 1u << 20 : 0u) + (b ? 1u << 20 : 0u));
    }
    if (lane < 4) {
        asm volatile("red.shared.max.u32 [%0], %1;" ::"r"(SB + SM_STAT + lane * 4), "r"(lane == 0 ? mx[0] : lane == 1 ? mx[1] : lane == 2 ? mx[2] : mx[3]) : "memory");
        reds_add(SB + SM_STAT + 16 + lane * 4, lane == 0 ? se[0] : lane == 1 ? se[1] : lane == 2 ? se[2] : se[3]);
    }
}
__device__ __forceinline__ Scale get_scale(uint32_t sb) {
    Scale s;
    s.allslow = false;
#pragma unroll
    for (int k = 0; k < 4; k++) {
        const uint32_t mx = lds32(sb + SM_STAT + 4 * k), se = lds32(sb + SM_STAT + 16 + 4 * k);
        const uint32_t mean = (uint32_t)__fdividef((float)(se & 0xfffffu), (float)max(se >> 20, 1u));
        uint32_t eb = min(min((mx + 0x6e0000u) >> 23, mean + 5u), 227u);
        if (eb < 27u) { s.allslow = s.allslow || mx != 0; eb = 27u; }
        if (eb > 170u) s.allslow = true;
        s.eb[k] = eb;
    }
    return s;
}

__device__ __forceinline__ uint32_t probe_rt(uint32_t* p) {
    uint32_t best = 0xffffffffu;
#pragma unroll 1
    for (int r = 0; r < CFG_PROBES; r++) {
        const uint32_t t0 = clock();
        uint32_t v;
        asm volatile("atom.relaxed.gpu.global.add.u32 %0, [%1], 1;" : "=r"(v) : "l"(p) : "memory");
        if (v > 100000u) __trap();
        const uint32_t t1 = clock();
        best = min(best, t1 - t0);
    }
    return best;
}
__device__ __forceinline__ uint32_t* pub_ptr(const Params& p, int blk, uint32_t sel) {
    const int pr = blk / 44;
    return (uint32_t*)(p.ring + PROBE_OFF + (pr ? 4096u << pr : 0u) + (sel << 12) + 2176 + (blk - pr * 44) * 32);
}
__device__ __forceinline__ void probe(const Params& p, uint32_t sb, int w, int lane) {
    const int blk = blockIdx.x, pr = w >> 1;
    uint32_t off = PROBE_OFF + blk * 16 + (pr ? 4096u << pr : 0u);
    if (pr == 7) off = blk < NWIN ? blk * WIN + 4064 : PROBE_OFF + 3584 + blk % 16 * 32;
    off += (w & 1) * 4096;
    if (lane < 8) st_rlx((uint32_t*)(p.ring + (off & ~31u)) + lane, 0u);
    if (lane == 0) sts32(sb + SM_PROBE + w * 4, probe_rt((uint32_t*)(p.ring + off)));
}
__device__ __forceinline__ void assign_role(const Params& p, uint32_t sb, int lane) {
    {
        const bool x = lane < 8 && lds32(sb + SM_PROBE + lane * 8 + 4) < lds32(sb + SM_PROBE + lane * 8);
        const uint32_t near = __ballot_sync(0xffffffffu, x), bits = near & 1 ? ~near | 1u : near;
        const uint32_t tag = (lds32(sb + SM_MISC + 16) + 1) << 30;
        if (lane < 16) st_rlx(pub_ptr(p, blockIdx.x, lane >> 3) + (lane & 7), tag | (bits & 0xffu));
        constexpr int K = (NCTA + 31) / 32;
        __nanosleep(CFG_P0);
        uint32_t v[K], bad;
        int guard = 0;
        do {
            bad = 0;
#pragma unroll
            for (int k = 0; k < K; k++) {
                const int b = min(lane + 32 * k, NCTA - 1);
                v[k] = ld_rlx(pub_ptr(p, b, near >> (b / 44) & 1));
                bad |= v[k] ^ tag;
            }
            bad = __any_sync(0xffffffffu, bad >> 30);
            if (bad) __nanosleep(CFG_PSLEEP);
            if (++guard > GUARD) __trap();
        } while (bad);
#pragma unroll
        for (int k = 0; k < K; k++) sts32(sb + SM_PUB + (lane + 32 * k) * 4, v[k]);
    }
    __syncwarp();
    constexpr int NP = NCTA / 2, NTAB = H2 + H3;
    const int me = blockIdx.x >> 1, odd = blockIdx.x & 1;
    uint32_t pp[3], key[3];
    int n1 = 0;
#pragma unroll
    for (int k = 0; k < 3; k++) {
        const int i = lane + 32 * k;
        pp[k] = lds32(sb + SM_PUB + min(i, NP - 1) * 8) & 1;
        key[k] = (i * CFG_KM % CFG_KN) << 8 | i;
        n1 += 2 * __popc(__ballot_sync(0xffffffffu, i < NP && pp[k]));
    }
    bool fixed = n1 < NTAB || NCTA - n1 < NTAB;
    if (fixed) {
        n1 = NP / 2 * 2;
        pp[0] = pp[1] = pp[2] = lane & 1;
    }
    const uint32_t mine = __shfl_sync(0xffffffffu, (me < 32 ? key[0] : me < 64 ? key[1] : key[2]) * 2 + (me < 32 ? pp[0] : me < 64 ? pp[1] : pp[2]), me & 31);
    const int part = mine & 1;
    int pos = odd;
#pragma unroll
    for (int k = 0; k < 3; k++) pos += 2 * __popc(__ballot_sync(0xffffffffu, lane + 32 * k < NP && pp[k] == (uint32_t)part && key[k] < mine / 2));
    const int role = pos < H2 ? 1 : pos < NTAB ? 2 : 0;
    const int id = pos < H2 ? part * H2 + pos : pos < NTAB ? part * H3 + pos - H2 : (part ? NCTA - n1 - NTAB : 0) + pos - NTAB;
    const uint32_t v = lds32(sb + SM_PUB + lane * 4);
    uint32_t lin = 0;
#pragma unroll
    for (int b = 0; b < 6; b++) lin |= (__popc(__ballot_sync(0xffffffffu, (v >> (b + 1)) & 1)) > 16 ? 1u : 0u) << b;
    if (lane == 0) {
        sts32(sb + SM_MISC, role << 8 | id);
        sts32(sb + SM_MISC + 4, lin);
        sts32(sb + SM_MISC + 8, NCTA - n1 - NTAB);
        sts32(sb + SM_MISC + 20, part);
        sts32(sb + SM_MISC + 12, role == 0 ? id : role == 1 ? N1 + id : N1 + N2 + id);
    }
}
__device__ __forceinline__ uint32_t sel_of(uint32_t sb, int widx, uint32_t k, int part) {
    return (__popc(k & lds32(sb + SM_MISC + 4)) ^ (lds32(sb + SM_PUB + widx * 4) >> 7) ^ part) & 1;
}
__device__ __forceinline__ uint32_t gran_off(uint32_t sb, int widx, int k, int part) { return (2 * k + sel_of(sb, widx, k, part)) << 12; }
__device__ __forceinline__ uint32_t q1a_off(uint32_t sb, int src, int blk, int part) { return gran_off(sb, 2 * blk + part, src >> 1, part) + (src & 1) * 2048; }
__device__ __forceinline__ uint32_t q1h_off(uint32_t sb, int src, int blk, int part) { return gran_off(sb, 2 * blk + part, 32 + (src >> 2), part) + (src & 3) * 1024; }
__device__ __forceinline__ uint32_t* ctl_word(const Params& p, uint32_t sb, int k, int word, int part) {
    const int widx = CWIN + lds32(sb + SM_MISC + 16);
    return (uint32_t*)(p.ring + (widx * WIN + ((2 * k + sel_of(sb, widx, k, part)) << 12))) + word;
}
__device__ __forceinline__ uint32_t* cred1_of(const Params& p, uint32_t sb, int src) { return ctl_word(p, sb, src >> 3, (src & 7) * 128, src >= (int)lds32(sb + SM_MISC + 8)); }
__device__ __forceinline__ uint32_t* fin1_of(const Params& p, uint32_t sb, int dst) { return ctl_word(p, sb, 8 + (dst >> 3), (dst & 7) * 128, dst / H2); }
__device__ __forceinline__ uint32_t* cred2_of(const Params& p, uint32_t sb, int src) { return ctl_word(p, sb, 16 + (src >> 3), (src & 7) * 128, src / H2); }
__device__ __forceinline__ uint32_t* fin2_of(const Params& p, uint32_t sb, int dst) { return ctl_word(p, sb, 24 + (dst >> 3), (dst & 7) * 128, dst / H3); }
__device__ __forceinline__ uint32_t* rdy_of(const Params& p, uint32_t sb, int word, int part) { return ctl_word(p, sb, 28, word, part); }
__device__ __forceinline__ uint32_t q2_off(uint32_t sb, int blk, int dst) {
    return (N2 + dst) * WIN + gran_off(sb, N2 + dst, (blk >> 1) * 4 + (blk & 1), dst / H3);
}
template <bool IS1>
__device__ __forceinline__ void clear_queues(const Params& p, uint32_t sb, int id, int lane) {
    constexpr int NA = (N1 + 1) / 2, NG = NA + (N1 + 3) / 4, N = IS1 ? NG * N2 : NI * 2;
    if (IS1) {
#pragma unroll 1
        for (int k = 0; k < 8; k++) sts128(sb + SM_ZERO + (k * 32 + lane) * 16, make_uint4(0, 0, 0, 0));
        if (lane == 0) spin_ge(rdy_of(p, sb, 320, lds32(sb + SM_MISC + 20)), NTAIL);
    }
    __syncwarp();
    fence_async_smem();
    for (int k = IS1 ? id + (lane < CFG_CLN ? lane : N) * N1 : lane; k < N; k += IS1 ? CFG_CLN * N1 : 32) {
        if (IS1 && k >= CFG_CLN * N1) __nanosleep(CFG_CLS);
        const int wi = k / NG, g = k - wi * NG;
        const uint32_t off = IS1 ? wi * WIN + gran_off(sb, wi, g < NA ? g : 32 + g - NA, wi & 1) : q2_off(sb, k >> 1, id) + (k & 1) * 16384;
        bulk_store(p.ring + off, sb + SM_ZERO, 4096);
    }
    asm volatile("cp.async.bulk.commit_group;" ::: "memory");
    asm volatile("cp.async.bulk.wait_group 0;" ::: "memory");
    TR(21, IS1 && lane == 0);
    if (!IS1) {
        fence_async_all();
        __syncwarp();
        fence_gpu();
        if (lane < NI) red_rlx(rdy_of(p, sb, id / H3 * H2 + lane, id / H3), 1u);
    }
    __syncwarp();
}

struct In8 { uint4 a[2], o[2]; uint2 g[2]; };
__device__ __forceinline__ void p1_load(const Params& p, In8& r, int i4) {
#pragma unroll
    for (int u = 0; u < 2; u++) {
        [[maybe_unused]] uint32_t x, y;
        asm volatile("tex.1d.v4.u32.s32 {%0,%1,%2,%3}, [%4, {%5}];" : "=r"(r.a[u].x), "=r"(r.a[u].y), "=r"(r.a[u].z), "=r"(r.a[u].w) : "l"(p.t_in), "r"(i4 + u * 32));
        asm volatile("tex.1d.v4.u32.s32 {%0,%1,%2,%3}, [%4, {%5}];" : "=r"(r.o[u].x), "=r"(r.o[u].y), "=r"(r.o[u].z), "=r"(r.o[u].w) : "l"(p.t_out), "r"(i4 + u * 32));
        asm volatile("tex.1d.v4.u32.s32 {%0,%1,%2,%3}, [%4, {%5}];" : "=r"(r.g[u].x), "=r"(r.g[u].y), "=r"(x), "=r"(y) : "l"(p.t_ang), "r"(i4 + u * 32));
    }
}
__device__ __forceinline__ uint32_t imad(uint32_t a, uint32_t b, uint32_t c) {
    uint32_t r;
    asm("mad.lo.u32 %0, %1, %2, %3;" : "=r"(r) : "r"(a), "r"(b), "r"(c));
    return r;
}
__device__ __forceinline__ unsigned char* ring_ptr(const Params& p, uint32_t lo) {
    uint64_t r;
    asm("mov.b64 %0, {%1, %2};" : "=l"(r) : "r"(lo), "r"(p.ring_hi));
    return (unsigned char*)r;
}
__device__ __forceinline__ uint32_t keep32(uint32_t x) {
    return __shfl_sync(0xffffffffu, x, threadIdx.x & 31);
}
__device__ __forceinline__ uint32_t opaque32(uint32_t x) {
    asm volatile("" : "+r"(x));
    return x;
}
template <typename T> __device__ __forceinline__ T* opaque(T* p) {
    asm volatile("" : "+l"(p));
    return p;
}
template <int LUT> __device__ __forceinline__ uint32_t lop3(uint32_t a, uint32_t b, uint32_t c) {
    uint32_t r;
    asm("lop3.b32 %0, %1, %2, %3, %4;" : "=r"(r) : "r"(a), "r"(b), "r"(c), "n"(LUT));
    return r;
}
__device__ __forceinline__ uint32_t dp4(uint32_t a, uint32_t b, uint32_t c) {
    uint32_t r;
    asm("dp4a.u32.u32 %0, %1, %2, %3;" : "=r"(r) : "r"(a), "r"(b), "r"(c));
    return r;
}
__device__ __forceinline__ uint32_t dp2(uint32_t a, uint32_t b, uint32_t c) {
    uint32_t r;
    asm("dp2a.lo.u32.u32 %0, %1, %2, %3;" : "=r"(r) : "r"(a), "r"(b), "r"(c));
    return r;
}
__device__ __forceinline__ void p1_put(uint32_t sb, uint32_t wa, uint32_t wb, uint32_t old, bool on) {
    asm volatile("{.reg .pred q; setp.ne.u32 q, %3, 0; @q st.shared.v2.u32 [%0], {%1,%2};}"
                 ::"r"(sb + A_ST + prmt(old, wb, 0xf762)), "r"(wa), "r"(prmt(wb, old, 0x7210)), "r"((uint32_t)on) : "memory");
}
__device__ __forceinline__ void p1_slow_tile(const Params& p, uint32_t sb, int i4) {
    const float f = __bfloat162float(p.freq[0]);
#pragma unroll 1
    for (int u = 0; u < 8; u++) {
        const int k4 = i4 + (u >> 2) * 32;
        if (k4 < p.n4) {
            const size_t t = (size_t)k4 * 4 + (u & 3);
            const float x = __bfloat162float(__float2bfloat16(f * __bfloat162float(p.angle[t])));
            slow_add(p.m, sb, p.idx_in[t], p.idx_out[t], __bfloat162float(__float2bfloat16(cosf(x))));
        }
    }
}
__device__ __forceinline__ void role_p1(const Params& p, uint32_t sb, int id, int w, int lane) {
    lane = keep32(lane);
    const uint32_t f2 = (uint32_t)__bfloat16_as_ushort(p.freq[0]) * 0x10001u;
    constexpr int TG = CFG_TG, NTK = P1W;
    static_assert(NTK <= 16, "tickets");
    const int tc = (w + id) % NTK, first = (N1 * P1W + tc) * (TG * 64);
    uint32_t* const tickets = opaque(ctl_word(p, sb, 29 + tc / 8, tc % 8 * 128 + lane, tc & 1));
    auto draw = [&]() {
        uint32_t t = 0;
        asm volatile("{.reg .pred q; setp.eq.u32 q, %2, 0; @q atom.relaxed.gpu.global.add.u32 %0, [%1], 1;}" : "+r"(t) : "l"(tickets), "r"(lane) : "memory");
        return t;
    };
    int i4 = (id * P1W + w) * (TG * 64);
    In8 r;
    ACC_DECL
    uint32_t tk = draw();
    p1_load(p, r, i4 + lane);
    while (i4 < p.n4) {
        const int cur = i4;
        i4 += 64;
        if (i4 % (TG * 64) == 0) {
            i4 = min(__shfl_sync(0xffffffffu, tk, 0), 0x7fffffffu / (NTK * TG * 64) - N1 * P1W / NTK - 2) * (NTK * TG * 64) + first;
            tk = draw();
        }
        uint32_t wa[8], wb[8], x2[4];
        x2[0] = mul_bf2(r.g[0].x, f2); x2[1] = mul_bf2(r.g[0].y, f2);
        x2[2] = mul_bf2(r.g[1].x, f2); x2[3] = mul_bf2(r.g[1].y, f2);
        const uint32_t mx = maxabs_bf2(maxabs_bf2(x2[0], x2[1]), maxabs_bf2(x2[2], x2[3]));
        const bool fast = __all_sync(0xffffffffu, cur + 64 <= p.n4 && ((mx & 0x7fffu) <= 0x4300u) && ((mx & 0x7fff0000u) <= 0x43000000u));
        {
            const uint32_t in[8] = {r.a[0].x, r.a[0].y, r.a[0].z, r.a[0].w, r.a[1].x, r.a[1].y, r.a[1].z, r.a[1].w};
            const uint32_t ou[8] = {r.o[0].x, r.o[0].y, r.o[0].z, r.o[0].w, r.o[1].x, r.o[1].y, r.o[1].z, r.o[1].w};
#pragma unroll
            for (int j = 0; j < 8; j += 2) {
                const uint32_t ch = mul_h2(pack_h2(__cosf(bflo(x2[j >> 1])), __cosf(bfhi(x2[j >> 1]))), 0x24002400u);
#pragma unroll
                for (int k = j; k < j + 2; k++) {
                    const uint32_t blk = __umulhi(in[k], p.magic2), il = imad(blk, p.nrows2, in[k]);
                    wa[k] = k & 1 ? bitsel(ch, il, 0xffff0000u) : imad(ch, 65536u, il);
                    wb[k] = imad(blk, 1u << 21, imad(ou[k] >> 5, 1u - (1u << 21), ou[k] << 16));
                }
            }
        }
        p1_load(p, r, i4 + lane);
        if (fast) {
            uint32_t old[8], any = 0;
#pragma unroll
            for (int j = 0; j < 8; j++) old[j] = atoms_add(dp2(wb[j], 0x400u, 0u) + (sb + A_CNT), 0x80001u);
#pragma unroll
            for (int j = 0; j < 8; j++) any |= old[j];
            if (!__any_sync(0xffffffffu, any & 0xffe0u)) {
#pragma unroll
                for (int j = 0; j < 8; j++) p1_put(sb, wa[j], wb[j], old[j], true);
            } else {
                uint32_t pend = 0;
#pragma unroll
                for (int j = 0; j < 8; j++) { p1_put(sb, wa[j], wb[j], old[j], !(old[j] & 0xffe0u)); if (old[j] & 0xffe0u) pend |= 1u << j; }
                ACC(0, 1)
                for (int guard = 0; __any_sync(0xffffffffu, pend); guard++) {
                    __nanosleep(CFG_BSLEEP);
                    ACC(1, 1)
#pragma unroll
                    for (int j = 0; j < 8; j++) {
                        if (__any_sync(0xffffffffu, pend >> j & 1)) {
                            const uint32_t c = lds32v(sb + A_CNT + (pend >> j & 1 ? wb[j] >> 16 : 0) * 4);
                            const bool go = (pend >> j & 1) && (((old[j] >> 19) - (c >> 19) + c) & 8191u) < 32u;
                            p1_put(sb, wa[j], wb[j], old[j], go);
                            if (go) pend &= ~(1u << j);
                        }
                    }
                    if (guard > GUARD) __trap();
                }
            }
        } else {
            p1_slow_tile(p, sb, cur + lane);
            __syncwarp();
        }
    }
    __syncwarp();
    mbar_arrive_if(sb + SM_DONE, lane == 0);
    ACC_SAVE
}

__device__ __forceinline__ void role_flush(const Params& p, uint32_t sb, int id, int f, int lane) {
    lane = keep32(lane);
    const int half = lane >> 4, o = lane >> 2, q = lane & 3;
    const uint32_t hm = keep32(half ? 0xffff0000u : 0xffffu), lth = keep32(((1u << lane) - 1) & hm);
    const uint32_t list = sb + A_LIST + f * LISTB, cnt = keep32(sb + A_CNT + (f * GPW * 32 + lane) * 4);
    const uint32_t cred = opaque32(sb + SM_CRED + (half * 32 + f * GPW) * 4);
    const uint32_t pa = opaque32(p.ring_lo + (id >> 1) * 8192 + (id & 1) * 2048 + q * 16);
    const uint32_t ph = opaque32(p.ring_lo + (32 + (id >> 2)) * 8192 + (id & 3) * 1024 + q * 8 - 2048);
    const uint32_t sa = q * 16 + (o & 1) * 64;
    uint32_t qo[GPW], hs[GPW], cr[4] = {0, 0, 0, 0};
#pragma unroll
    for (int g = 0; g < GPW; g++) {
        const int blk = f * GPW + g;
        qo[g] = 32u << 25;
        const uint32_t sa = sel_of(sb, 2 * blk + half, id >> 1, half), sh = sel_of(sb, 2 * blk + half, 32 + (id >> 2), half);
        hs[g] = sa << 31 | (2 * sh + 1 - sa) << 22 | 1u << 24 | (lane & 15) << 15 | (blk * 32 + lane) * 2;
    }
    uint4 x[KR] = {}, y[KR] = {};
    uint32_t c[GPW] = {};
    auto scan = [&]() {
#pragma unroll
        for (int g = 0; g < GPW; g++) c[g] = lds32v(cnt + g * 128);
    };
    auto credits = [&]() {
        if (GPW == 4) { const uint4 v = lds128(cred); cr[0] = v.x; cr[1] = v.y; cr[2] = v.z; cr[3] = v.w; }
        else { const uint2 v = lds64v(cred); cr[0] = v.x; cr[1] = v.y; }
    };
    ACC_DECL
    int guard = 0;
    bool idle = false, done = false;
    while (true) {
        uint32_t fr[GPW], rank[GPW], num = 0, left = 0;
        bool ok[GPW];
        if (idle && !done && __all_sync(0xffffffffu, mbar_test(sb + SM_DONE, 0))) {
            done = true;
            TR(17, f == 0 && lane == 0);
#pragma unroll
            for (int g = 0; g < GPW; g++) {
                const uint32_t u = lds32v(cnt + g * 128) & 31u, hd = hs[g] ^ (u & 16u ? imad(hs[g], 1u << 24, 1u) & 0x01000001u : 0u);
#pragma unroll 2
                for (uint32_t j = 0, k; k = (j + lane) & 15u, j < 16; j++)
                    sts64_if(sb + A_ST + ((hd & 0x7ffu) << 7) + k * 8, p.rows2, (lane * 16 + k) | (hd & 0x1000000u), (u & 15u) && k >= (u & 15u));
                reds_add(cnt + g * 128, ((0u - u) & 15u) * 0x80001u);
            }
            __syncwarp();
            scan();
        }
#pragma unroll
        for (int g = 0; g < GPW; g++) {
            const bool isfull = c[g] & 0xfff0u;
            rank[g] = __popc(__ballot_sync(0xffffffffu, isfull) & lth);
            ok[g] = isfull && (int)(rank[g] << 25) < (int)(cr[g] - qo[g] + (63u << 25));
            ACC(2, __popc(__ballot_sync(0xffffffffu, isfull && !ok[g])))
        }
#pragma unroll
        for (int g = 0; g < GPW; g++) {
            const uint32_t m = __ballot_sync(0xffffffffu, ok[g]), n = __popc(m & hm), all = __popc(m), e = num + rank[g] + (half ? all - n : 0u);
            sts32_if(KR == 2 ? list + (e & 48u) * 4 + (e & 7u) * 8 + (e >> 1 & 4u) : imad(e, 4u, list), bitsel(imad(rank[g], 1u << 25, qo[g]), hs[g], 0x7e000000u), ok[g]);
            if (ok[g]) hs[g] ^= imad(hs[g], 1u << 24, 1u) & 0x01000001u;
            fr[g] = ok[g] ? 0u - 16u : 0u;
            left |= c[g] + fr[g];
            qo[g] = imad(n, 1u << 25, qo[g]);
            num += all;
        }
        __syncwarp();
        ACC(0, 1) ACC(1, num)
        if (num) {
            uint32_t la = list + o * (KR == 2 ? 8 : 4);
            int todo = (int)num - o, rest = num;
            do {
                uint32_t d[KR];
                if (KR == 2) { const uint2 v = lds64v(la); d[0] = v.x; d[KR - 1] = v.y; }
                else {
#pragma unroll
                    for (int k = 0; k < KR; k++) d[k] = lds32v(la + 32 * k);
                }
                while (true) {
                    uint32_t bad = 0;
#pragma unroll
                    for (int k = 0; k < KR; k++) {
                        const uint32_t m = d[k] & 0x7ffu;
                        lds128_keep(x[k], imad(m, 128u, sa) + (sb + A_ST), todo > 8 * k);
                        lds128_keep(y[k], imad(m, 128u, sa ^ 64) + (sb + A_ST), todo > 8 * k);
                    }
#pragma unroll
                    for (int k = 0; k < KR; k++)
                        or3_if(bad, lop3<0x7e>(x[k].y, x[k].w, d[k]), lop3<0x7e>(y[k].y, y[k].w, d[k]), todo > 8 * k);
                    if (!__any_sync(0xffffffffu, (int)imad(bad, 128u, 0u) < 0)) break;
                    if (++guard > GUARD) __trap();
                }
#pragma unroll
                for (int k = 0; k < KR; k++) {
                    const uint32_t mi = d[k] & 0x7e0u, dm = d[k] & 0xbec00000u;
                    x[k].x = bitsel(d[k], x[k].x, 0x40078000u);
                    x[k].y = prmt(x[k].y, x[k].w, 0x5410);
                    x[k].w = prmt(y[k].y, y[k].w, 0x5410);
                    y[k].x = bitsel(d[k], y[k].x, 0x40000000u);
                    y[k].y = y[k].z;
                    stg_q128(ring_ptr(p, dp4(dm, 0x20000000u, imad(mi, WIN / 32, pa))), x[k].x, x[k].y, x[k].z, x[k].w, X_ST1 todo > 8 * k);
                    stg_q64(ring_ptr(p, dp4(dm, 0x10200000u, imad(mi, WIN / 32, ph))), y[k].x, y[k].y, X_ST1 todo > 8 * k);
                }
                la += 32 * KR;
                todo -= 8 * KR;
                rest -= 8 * KR;
            } while (rest > 0);
#pragma unroll
            for (int g = 0; g < GPW; g++) c[g] = atoms_add(cnt + g * 128, fr[g]) + fr[g];
            credits();
            idle = num <= CFG_TH;
            if (done && !__any_sync(0xffffffffu, left & 0xffffu)) break;
            if (idle) { __nanosleep(CFG_TS); scan(); credits(); }
        } else {
            if (done && !__any_sync(0xffffffffu, left & 0xffffu)) break;
            idle = true;
            __nanosleep(CFG_FSLEEP);
            scan();
            credits();
            if (++guard > GUARD) __trap();
        }
    }
#pragma unroll
    for (int g = 0; g < GPW; g++) st_rlx_if(fin1_of(p, sb, half * H2 + f * GPW + g) + id, qo[g] - (32u << 25) + 1u, (lane & 15) == 0 && f * GPW + g < NI);
    mbar_arrive_if(sb + SM_DONE2, lane == 0);
    TR(18, f == 0 && lane == 0);
    ACC_SAVE
}
__device__ __forceinline__ void role_credit1(const Params& p, uint32_t sb, int id, int lane) {
    const uint32_t* const cred = cred1_of(p, sb, id) + lane * 2;
    for (int guard = 0; !__all_sync(0xffffffffu, mbar_test(sb + SM_DONE2, 0)); guard++) {
        const uint2 v = ldg_q64(cred);
        sts64(sb + SM_CRED + lane * 8, v.x, v.y);
        __nanosleep(CFG_C1SLEEP);
        if (guard > GUARD) __trap();
    }
}

__device__ __forceinline__ float h2f(uint32_t h) {
    float f;
    asm("{.reg .b16 t; cvt.u16.u32 t, %1; cvt.f32.f16 %0, t;}" : "=f"(f) : "r"(h));
    return f;
}
__device__ __forceinline__ void p2_slow(const Params& p, uint32_t sb, const uint32_t* tmp, int row0, uint32_t dst) {
#pragma unroll 1
    for (int j = 0; j < 4; j++)
        if (tmp[8 + j] & 0x40u) slow_add(p.m, sb, row0 + (tmp[j] & 0x7fffu), (tmp[4 + j] & 0x7fffu) * 32 + dst, h2f(tmp[j] >> 16) * 64.0f);
}
__device__ __forceinline__ uint32_t mul_h2_hi(uint32_t a, uint32_t b) {
    uint32_t r;
    asm("{.reg .b16 l, h; .reg .b32 t; mov.b32 {l, h}, %2; mov.b32 t, {h, h}; mul.rn.f16x2 %0, %1, t;}" : "=r"(r) : "r"(a), "r"(b));
    return r;
}
template <bool CHECK>
__device__ __forceinline__ void role_p2(const Params& p, uint32_t sb, int id, int w, int lane) {
    lane = keep32(lane);
    const int part = id / H2, blk = id - part * H2, row0 = blk * p.rows2;
    const int o = lane >> 2, q = lane & 3;
    uint32_t* const cbase = (uint32_t*)(p.ring + (CWIN + lds32(sb + SM_MISC + 16)) * WIN);
    const uint32_t cred = opaque32((uint32_t)(uintptr_t)(cbase + part * 32 + blk));
    const uint32_t pa = opaque32(p.ring_lo + (2 * blk + part) * WIN + q * 16), ph = opaque32(pa - q * 8);
    const uint32_t po = opaque32(p.ring_lo + (q2_off(sb, blk, part * H3) & ~4096u) + q * 16 + (o & 1) * 64);
    const uint32_t sel = __ballot_sync(0xffffffffu, q2_off(sb, blk, part * H3 + (lane & 15)) & 4096u) << 12;
    const uint32_t* const fins = fin1_of(p, sb, id);
    uint32_t st[QPW] = {}, sq[QPW] = {};
    uint4 qa[NBT];
    uint2 qh[NBT];
    auto load = [&](int k) {
        qa[k] = ldg_q128(ring_ptr(p, pa + (bitsel(sq[k], st[k] >> 19, 0x7f800u) & 0x7ffc0u)));
        qh[k] = ldg_q64(ring_ptr(p, ph + (bitsel(sq[k] >> 9, st[k] >> 20, 0x7fc00u) & 0x7ffe0u)));
    };
#pragma unroll
    for (int k = 0; k < QPW; k++) {
        const int src = w * QPW + k;
        st[k] = o << 25 | (src < N1 ? 1u : 5u);
        sq[k] = src < N1 ? q1h_off(sb, src, blk, part) << 9 | q1a_off(sb, src, blk, part) | (uint32_t)(cred1_of(p, sb, src) - cbase) / 8 : 0x7e000u * 513u;
    }
#pragma unroll
    for (int k = 0; k < NBT; k++) load(k);
    ACC_DECL
    int guard = 0;
    uint32_t streak = 0;
    while (true) {
        uint32_t nn[NBT], xx[NBT][4], hh[NBT][2], dd[NBT], any = 0;
        bool last = false;
#pragma unroll
        for (int k = 0; k < NBT; k++) {
            const uint4 a = qa[k];
            const uint2 h = qh[k];
            uint32_t n = 8;
            const uint32_t miss = __ballot_sync(0xffffffffu, (int)imad((a.x ^ st[k]) & (h.x ^ st[k]), 2u, 0u) >= 0);
            if (miss) {
                n = (__ffs(miss) - 1) >> 2;
                if (!__any_sync(0xffffffffu, st[k] & 8u)) { if (streak < CFG_PSTREAK) n &= CFG_PMASK; }
                else if (!__any_sync(0xffffffffu, ((st[k] >> 6) + ((n - o) << 19) ^ st[k]) & 0x1f80000u)) { st[k] |= 4u; last = true; }
            }
            ACC(1, n == 0) ACC(2, n != 0) ACC(3, n)
            st[k] = imad(n, 1u << 25, st[k]);
            st_rlx_if((uint32_t*)ring_ptr(p, imad(sq[k] & 0x7f0u, 32u, cred)), st[k], X_CR1 lane == 0 && n);
            xx[k][0] = bitsel(a.x, 0x00040000u, 0xbff87fffu); xx[k][1] = a.z; xx[k][2] = h.x & 0xbfffffffu; xx[k][3] = h.y;
            hh[k][0] = a.y; hh[k][1] = a.w; dd[k] = a.x >> 13 & 0x3cu; nn[k] = n;
            any |= n;
        }
        if (!any) {
#pragma unroll
            for (int k = 0; k < QPW; k++) {
                const uint32_t fin = ld_rlx(fins + ((sq[k] >> 12 & 62u) | (sq[k] >> 11 & 1u)));
                if (fin & 1u) st[k] |= (fin >> 6 & 0x1f80000u) | 8u;
            }
            if (++guard > GUARD) __trap();
            streak++;
        } else streak = 0;
        if (last) {
            uint32_t all = 4u;
#pragma unroll
            for (int k = 0; k < QPW; k++) all &= st[k];
            last = __all_sync(0xffffffffu, all);
        }
        {
            uint32_t t[QPW], u[QPW];
#pragma unroll
            for (int k = 0; k < QPW; k++) { t[k] = st[(k + NBT) % QPW]; u[k] = sq[(k + NBT) % QPW]; }
#pragma unroll
            for (int k = 0; k < QPW; k++) { st[k] = t[k]; sq[k] = u[k]; }
        }
#pragma unroll
        for (int k = 0; k < NBT; k++) load(k);
#pragma unroll
      for (int k = 0; k < NBT; k++) {
        if (nn[k]) {
            const uint32_t* const x = xx[k];
            const uint32_t h0 = hh[k][0], h1 = hh[k][1], d4 = dd[k];
            const bool v = o < nn[k];
            uint32_t old = 0, ta[4], tb[4], w0[4], w1[4];
            atoms_add_keep(old, sb + SM_CNT2 + d4, 0x10001u, q == 0 && v);
#pragma unroll
            for (int j = 0; j < 4; j++) {
                ta[j] = lds32nv(dp2(x[j], 4u, 0u) + (sb + B_TA));
                tb[j] = lds16nv(dp2(x[j], 2u, 0u) + (sb + B_TB));
            }
            old = __shfl_sync(0xffffffffu, old, lane & 28);
            const uint32_t tag = old << 8 & 0x40000000u;
#pragma unroll
            for (int j = 0; j < 4; j++) {
                const uint32_t z = prmt(j & 2 ? h1 : h0, 0, j & 1 ? 0x4342 : 0x4140);
                const uint32_t t23 = prmt((ta[j] & 0x60076007u) * 2050u, tb[j], 0x5341) & 0xfffcffffu;
                w0[j] = (imad(z, 128u, j & 1 ? 0u : tag) & 0x78007800u) | mul_h2_hi(ta[j] & 0x9ff89ff8u, x[j]);
                w1[j] = (imad(z, 2048u, 0u) & 0x78007800u) | mul_h2_hi(t23, x[j]);
            }
            if (CHECK && v && ((tb[0] | tb[1] | tb[2] | tb[3]) & 0x40u)) {
                uint32_t tmp[12];
#pragma unroll
                for (int j = 0; j < 4; j++) {
                    tmp[j] = x[j]; tmp[4 + j] = (j & 2 ? h1 : h0) >> (j & 1 ? 16 : 0); tmp[8 + j] = tb[j];
                    if (tb[j] & 0x40u) { w0[j] &= 0x78007800u; w1[j] &= 0x78007800u; }
                }
                p2_slow(p, sb, tmp, row0, part * H3 + d4 / 4);
            }
            const uint32_t off = (bitsel(old >> 9, old >> 7, 0x0f80u) & 0x4f80u) + imad(d4, WIN / 4, (sel >> (d4 / 4) & 4096u) + po);
            bool wait = old & (0x10000u - NQ2);
            if (!__any_sync(0xffffffffu, wait)) {
                stg_q128(ring_ptr(p, off), w0[0], w1[0], w0[1], w1[1], X_ST2 v);
                stg_q128(ring_ptr(p, off ^ 64u), w0[2], w1[2], w0[3], w1[3], X_ST2 v);
            } else {
                bool pend = v;
                ACC(0, 1)
                for (int g2 = 0;; g2++) {
                    stg_q128(ring_ptr(p, off), w0[0], w1[0], w0[1], w1[1], pend && !wait);
                    stg_q128(ring_ptr(p, off ^ 64u), w0[2], w1[2], w0[3], w1[3], pend && !wait);
                    pend = wait;
                    if (!__any_sync(0xffffffffu, pend)) break;
                    __nanosleep(CFG_BSLEEP);
                    const uint32_t c = lds32v(sb + SM_CNT2 + d4);
                    wait = pend && (((old >> 16) - (c >> 16) + c) & 0xffffu) >= NQ2;
                    if (g2 > GUARD) __trap();
                }
            }
        }
      }
        if (last) break;
    }
    TR(17, w == 0 && lane == 0);
    __syncwarp();
    uint32_t rank = 0;
    if (lane == 0) { __threadfence_block(); rank = atoms_add(sb + SM_FIN, 1u); __threadfence_block(); }
    if (__shfl_sync(0xffffffffu, rank, 0) == P2W - 1 && lane < 16)
        st_rlx(fin2_of(p, sb, part * H3 + lane) + blk, FIN | (((lds32v(sb + SM_CNT2 + lane * 4) >> 16) - NQ2) & 0xffffu));
    __syncwarp();
    mbar_arrive_if(sb + SM_DONE, lane == 0);
    ACC_SAVE
}
__device__ __forceinline__ void role_credit(const Params& p, uint32_t sb, int id, int lane) {
    const uint32_t* const cred = cred2_of(p, sb, id) + (lane & 15);
    uint32_t last = 0;
    for (int guard = 0;; guard++) {
        if (__all_sync(0xffffffffu, mbar_test(sb + SM_DONE, 0))) break;
        const uint32_t c = ld_rlx(cred);
        if (lane < 16 && c != last) reds_add(sb + SM_CNT2 + lane * 4, 0u - ((c - last) & 0xffffu));
        last = c;
        __nanosleep(CFG_CSLEEP);
        if (guard > GUARD) __trap();
    }
}

__device__ __forceinline__ void p3_wrap(uint32_t sb, int id, const uint32_t* tmp) {
    const Scale sc = get_scale(sb);
#pragma unroll 1
    for (int j = 0; j < 8; j++) {
        const uint32_t old = tmp[4 + j], v = tmp[12 + j], nw = old + v, t = (old ^ nw) & (v ^ nw);
        if (t & 0x80008000u) {
            const float k = (t & 0x8000u) ? ((v & 0x8000u) ? -1.0f : 1.0f) : 0.0f;
            const float q = (t & 0x80000000u) ? ((int)v < 0 ? -65536.0f : 65536.0f) : 0.0f;
            const uint32_t e0 = (j & 1) ? sc.eb[2] : sc.eb[0], e1 = (j & 1) ? sc.eb[3] : sc.eb[1];
            const float lo = k * 65536.0f * __uint_as_float((e0 - 10) << 23), hi = (q - k) * __uint_as_float((e1 - 10) << 23);
            if (j & 1) sg_add(tmp[j >> 1] * 32 + id, 0.f, 0.f, lo, hi);
            else sg_add(tmp[j >> 1] * 32 + id, lo, hi, 0.f, 0.f);
        }
    }
}
__device__ __forceinline__ uint32_t p3_val(uint32_t w) {
    const uint32_t mk = prmt(w, 0, 0xBB99);
    return ((w & 0x07ff07ffu) ^ mk) - mk;
}
__device__ __forceinline__ void role_p3(const Params& p, uint32_t sb, int id, int w, int lane) {
    lane = keep32(lane);
    uint32_t* const cred = opaque(cred2_of(p, sb, id / H3 * H2 + w) + id % H3);
    const uint32_t pq = opaque32(p.ring_lo + q2_off(sb, w, id) + lane * 16);
    auto off = [&](uint32_t n) { return (n & 1u) << 11 | (n & 2u) << 13; };
    const uint32_t pp = opaque32(pq - lane * 16 + 112);
    auto tag_of = [&](uint32_t n) { return ~n << 28; };
    uint32_t n = 0, fin = 0, pr = 0, pk = 0;
    uint4 v[4] = {};
    bool have = false, last = false;
    ACC_DECL
    int guard = 0;
    while (true) {
        const uint32_t ex = tag_of(n);
        const bool ok = have && !__any_sync(0xffffffffu, ((v[0].x ^ ex) | (v[1].x ^ ex) | (v[2].x ^ ex) | (v[3].x ^ ex)) & 0x40000000u);
        if (ok) n++;
        const bool ready = (ok || !have) && __all_sync(0xffffffffu, !((pr ^ tag_of(n)) & 0x40000000u));
        st_rlx_if(cred, n * 16, X_CR2 lane == 0 && ok);
        if (!ok && !ready && __all_sync(0xffffffffu, fin & FIN)) {
            const uint32_t left = __shfl_sync(0xffffffffu, (fin - n * 16) & 0xffffu, 0);
            if (left - 1u > 0x8000u) break;
            if (left < 16u) {
#pragma unroll
                for (int u = 0; u < 4; u++) {
                    v[u] = make_uint4(ex & 0x40000000u, 0, 0, 0);
                    ldq128_keep(v[u], ring_ptr(p, pq + off(n)) + u * 512, u * 4 + (lane >> 3) < left);
                }
                have = last = !__any_sync(0xffffffffu, ((v[0].x ^ ex) | (v[1].x ^ ex) | (v[2].x ^ ex) | (v[3].x ^ ex)) & 0x40000000u);
                pr = ~tag_of(n + have);
                if (++guard > GUARD) __trap();
                continue;
            }
        }
        uint32_t row[8], val[16];
#pragma unroll
        for (int u = 0; u < 4; u++) {
            const uint4 x = v[u];
            row[2 * u] = prmt(bitsel(x.x << 1, x.y >> 3, 0x7000f000u), 0, 0x4431);
            row[2 * u + 1] = prmt(bitsel(x.z << 1, x.w >> 3, 0x7000f000u), 0, 0x4431);
            val[4 * u] = p3_val(x.x); val[4 * u + 1] = p3_val(x.y);
            val[4 * u + 2] = p3_val(x.z); val[4 * u + 3] = p3_val(x.w);
        }
#pragma unroll
        for (int u = 0; u < 4; u++) ldq128_keep(v[u], ring_ptr(p, pq + off(n)) + u * 512, ready);
        pk = ready ? CFG_PK1 * 128 : ok ? CFG_PK2 * 128 : have ? 15 * 128 : max(pk, CFG_PK3 * 128u);
        pr = ld_rlx((const uint32_t*)ring_ptr(p, pp + off(n + ready) + pk));
        ACC(2, have && !ok)
        have = ready;
        if (!ok) {
            ACC(1, 1)
            fin = ld_rlx(fin2_of(p, sb, id) + w);
            if (++guard > GUARD) __trap();
        } else {
#pragma unroll
            for (int u = 0; u < 4; u += 2) {
                uint32_t old[8], chk = 0;
#pragma unroll
                for (int j = 0; j < 4; j++) {
                    old[2 * j] = atoms_add(sb + C_S + row[2 * u + j] * 4, val[4 * u + 2 * j]);
                    old[2 * j + 1] = atoms_add(sb + C_S + ROWS3_MAX * 4 + row[2 * u + j] * 4, val[4 * u + 2 * j + 1]);
                }
#pragma unroll
                for (int j = 0; j < 8; j++) {
                    const uint32_t nw = old[j] + val[4 * u + j];
                    chk |= (old[j] ^ nw) & (val[4 * u + j] ^ nw);
                }
                if (chk & 0x80008000u) {
                    uint32_t tmp[20];
#pragma unroll
                    for (int j = 0; j < 8; j++) { tmp[j >> 1] = row[2 * u + (j >> 1)]; tmp[4 + j] = old[j]; tmp[12 + j] = val[4 * u + j]; }
                    p3_wrap(sb, id, tmp);
                }
            }
            __syncwarp();
            if (last) break;
        }
    }
    ACC_SAVE
}

__device__ __forceinline__ void row_gates(const float* sw, const uint32_t* c2, uint32_t dbits, float4& gs, float4& gr) {
    const uint32_t d2 = dbits * 0x10001u;
    gs = gr = make_float4(0.f, 0.f, 0.f, 0.f);
#pragma unroll
    for (int r2 = 0; r2 < 4; r2++) {
        uint32_t df = sub_bf2(d2, c2[r2]);
        uint32_t ar = mul_bf2(mul_bf2(df, df), 0xC120C120u);
        uint32_t rb = pack_bf2(__expf(bflo(ar)), __expf(bfhi(ar)));
        const float r0 = bflo(rb), r1 = bfhi(rb);
        const float4 s0 = *(const float4*)(sw + r2 * 8), s1 = *(const float4*)(sw + r2 * 8 + 4);
        const float4 q0 = *(const float4*)(sw + 32 + r2 * 8), q1 = *(const float4*)(sw + 32 + r2 * 8 + 4);
        gs.x += r0 * s0.x + r1 * s1.x; gs.y += r0 * s0.y + r1 * s1.y;
        gs.z += r0 * s0.z + r1 * s1.z; gs.w += r0 * s0.w + r1 * s1.w;
        gr.x += r0 * q0.x + r1 * q1.x; gr.y += r0 * q0.y + r1 * q1.y;
        gr.z += r0 * q0.z + r1 * q1.z; gr.w += r0 * q0.w + r1 * q1.w;
    }
}
__device__ __forceinline__ uint2 finish_row(const float* wu, const float4& gs, const float4& gr, const float S[4], uint2 mrow) {
    const float a[4] = {S[0] * gs.x, S[1] * gs.y, S[2] * gs.z, S[3] * gs.w};
    float u[4] = {0, 0, 0, 0};
#pragma unroll
    for (int k = 0; k < 4; k++) {
        u[0] += a[k] * wu[4 * k]; u[1] += a[k] * wu[4 * k + 1]; u[2] += a[k] * wu[4 * k + 2]; u[3] += a[k] * wu[4 * k + 3];
    }
    return make_uint2(pack_bf2(bflo(mrow.x) + u[0] * gr.x, bfhi(mrow.x) + u[1] * gr.y),
                      pack_bf2(bflo(mrow.y) + u[2] * gr.z, bfhi(mrow.y) + u[3] * gr.w));
}
__device__ __forceinline__ void load_tail_weights(const Params& p, float* sw, int tid) {
    if (tid < 32) sw[tid] = __bfloat162float(p.w_sbf[tid]);
    else if (tid < 64) sw[tid] = __bfloat162float(p.w_rbf[tid - 32]);
    else if (tid < 80) sw[tid] = __bfloat162float(p.w_up[tid - 64]);
    else if (tid < 96) sw[tid] = __bfloat162float(p.w_down[tid - 80]);
}
__device__ __forceinline__ float exp_ftz(float x) {
    float r;
    asm("ex2.approx.ftz.f32 %0, %1;" : "=f"(r) : "f"(x * 1.4426950408889634f));
    return r;
}
__device__ __forceinline__ void tail_rows(const Params& p, int tidx, int w, int lane) {
    constexpr uint32_t sb = SB;
    if (w == NW - 1 && lane < 2) {
        fence_gpu();
        red_rlx(rdy_of(p, sb, 320, lane), 1u);
    }
    if (w >= NPC * WPP) return;
    const int pc = w / WPP, r0 = pc * RPC + (tidx * WPP + w - pc * WPP) * 8, e0 = r0 * 32;
    const uint32_t G = sb + T_G + w * TWB, M = G + 4096, D = M + 2048;
    cp16z(D + lane * 16, p.dist + e0 + lane * 8, min(max(p.E - e0 - lane * 8, 0), 8) * 2);
#pragma unroll
    for (int k = 0; k < 4; k++) cp16(M + (k * 32 + lane) * 16, p.m + e0 + (k * 32 + lane) * 2, e0 + (k * 32 + lane) * 2 < p.E);
    cp_commit();
    const Scale sc = get_scale(sb);
    const float lsb[4] = {__uint_as_float((sc.eb[0] - 10) << 23), __uint_as_float((sc.eb[1] - 10) << 23),
                          __uint_as_float((sc.eb[2] - 10) << 23), __uint_as_float((sc.eb[3] - 10) << 23)};
    {
        const int g = lane >> 2, t = lane & 3;
        const uint32_t c2 = ((const uint32_t*)p.centers)[t];
        const unsigned short* wg = (const unsigned short*)(g < 4 ? p.w_sbf : p.w_rbf) + t * 8 + (g & 3);
        const uint32_t b = wg[0] | (uint32_t)wg[4] << 16;
        cp_wait<0>();
        __syncwarp();
        TR(19, w == 0 && lane == 0 && b + c2 != 0x12345);
#pragma unroll 2
        for (int k = 0; k < 16; k++) {
            const uint32_t dv = lds32(D + (k * 8 + g) * 4);
            uint32_t a[2];
#pragma unroll
            for (int h = 0; h < 2; h++) {
                const uint32_t df = sub_bf2(prmt(dv, 0, h ? 0x3232 : 0x1010), c2);
                const uint32_t ar = mul_bf2(mul_bf2(df, df), 0xC120C120u);
                a[h] = pack_bf2(exp_ftz(bflo(ar)), exp_ftz(bfhi(ar)));
            }
            float d[4];
            asm("mma.sync.aligned.m16n8k8.row.col.f32.bf16.bf16.f32 {%0,%1,%2,%3}, {%4,%5}, {%6}, {%7,%7,%7,%7};"
                : "=f"(d[0]), "=f"(d[1]), "=f"(d[2]), "=f"(d[3]) : "r"(a[0]), "r"(a[1]), "r"(b), "f"(0.f));
            const uint32_t at = G + (k * 16 + g * 2) * 16 + t * 4;
            sts32(at, pack_bf2(d[0], d[1]));
            sts32(at + 16, pack_bf2(d[2], d[3]));
        }
    }
    __syncwarp();
    TR(2, w == 0 && lane == 0);
    float wu[16];
#pragma unroll
    for (int k = 0; k < 4; k++) *(uint4*)(wu + 4 * k) = lds128(sb + SM_W + 256 + 16 * k);
    uint32_t dirty = 0;
#pragma unroll 1
    for (int pass = CFG_DRY ? 0 : 1; pass < 2; pass++) {
        if (pass) {
            if (w == pc * WPP && lane < 2) spin_ge(rdy_of(p, sb, lane ? 320 : 160 + 32 * pc, lds32(sb + SM_MISC + 20)), lane ? NTAIL : N3);
            __syncwarp();
            bar_sync(1 + pc, WPP * 32);
            TR(3, w == 0 && lane == 0);
            TR(10, w == NPC * WPP - 1 && lane == 0);
            if (r0 >= (int)p.rows3) return;
        }
        uint4 sv[4] = {};
#pragma unroll
        for (int u = 0; u < 4; u++) ldq128_keep(sv[u], &g_S[0][u * 16 + (lane >> 1)][r0 + (lane & 1) * 4], pass);
        if (pass && lane < 8 && (r0 + lane) * 32 < p.E && (dirty = ld_rlx(g_dirty + r0 + lane))) st_rlx(g_dirty + r0 + lane, 0u);
        dirty = __ballot_sync(0xffffffffu, dirty != 0);
        uint32_t xs[8] = {sv[0].x, sv[0].y, sv[0].z, sv[0].w, sv[1].x, sv[1].y, sv[1].z, sv[1].w};
        uint32_t ys[8] = {sv[2].x, sv[2].y, sv[2].z, sv[2].w, sv[3].x, sv[3].y, sv[3].z, sv[3].w};
        asm volatile("" : "+r"(lane));
        auto finish = [&](int k, uint32_t x, uint32_t y, bool extra) {
            const int i = (lane & 1) * 128 + (lane >> 1) + (k & 3) * 32 + (k >> 2) * 16, e = e0 + i;
            float S[4];
            const uint32_t tx = x + 0x80008000u, ty = y + 0x80008000u;
            S[0] = (__uint_as_float(prmt(tx, 0x4b000000u, 0x7610)) - 8421376.0f) * lsb[0];
            S[1] = (__uint_as_float(prmt(tx, 0x4b000000u, 0x7632)) - 8421376.0f) * lsb[1];
            S[2] = (__uint_as_float(prmt(ty, 0x4b000000u, 0x7610)) - 8421376.0f) * lsb[2];
            S[3] = (__uint_as_float(prmt(ty, 0x4b000000u, 0x7632)) - 8421376.0f) * lsb[3];
            if (extra && e < p.E) {
                const float4 g = __ldcg(g_Sg + e);
                S[0] += g.x; S[1] += g.y; S[2] += g.z; S[3] += g.w;
                __stcg(g_Sg + e, make_float4(0.f, 0.f, 0.f, 0.f));
            }
            const uint4 g = lds128(G + i * 16);
            const uint2 o = finish_row(wu, make_float4(bflo(g.x), bfhi(g.x), bflo(g.y), bfhi(g.y)), make_float4(bflo(g.z), bfhi(g.z), bflo(g.w), bfhi(g.w)), S,
                                       lds64v(M + i * 8));
            asm volatile("{.reg .pred q; setp.ne.u32 q, %3, 0; @q st.global.v2.u32 [%0], {%1,%2};}"
                         ::"l"(p.out + e), "r"(o.x), "r"(o.y), "r"((uint32_t)(pass && e < p.E)));
        };
        if (!dirty) {
#pragma unroll
            for (int k = 0; k < 8; k++) finish(k, xs[k], ys[k], false);
        } else {
#pragma unroll 1
            for (int k = 0; k < 8; k++) {
                finish(k, xs[0], ys[0], dirty >> ((lane & 1) * 4 + (k & 3)) & 1);
#pragma unroll
                for (int j = 0; j < 7; j++) { xs[j] = xs[j + 1]; ys[j] = ys[j + 1]; }
            }
        }
    }
    TR(9, w == 0 && lane == 0);
    TR(11, w == NPC * WPP - 1 && lane == 0);
}

#define CFG_MAP1 1
__global__ void __launch_bounds__(NT, 1) k_main(const __grid_constant__ Params p) {
    extern __shared__ __align__(1024) unsigned char smem[];
    constexpr uint32_t sb = SB;
    if ((uint32_t)__cvta_generic_to_shared(smem) != SB) __trap();
    const int tid = threadIdx.x, w = __shfl_sync(0xffffffffu, tid >> 5, 0), lane = tid & 31;
    if (w < NPROBE) probe(p, sb, w, lane);
    else {
        if (tid == NT - 1) sts32(sb + SM_MISC + 16, ld_rlx(&g_epoch) & 1);
        if (tid >= NT - 32 && lane < 12) sts32(sb + SM_FIN + lane * 4, 0u);
        load_tail_weights(p, (float*)(smem + SM_W), tid - NPROBE * 32);
        const int k = blockIdx.x % (NCTA / 2) * 14 + lane;
        if (w == NW - 2 && lane < 14 && k < NT - 32) asm volatile("prefetch.global.L2 [%0];" ::"l"((const uint4*)p.m + k * (p.E / 2 / (NT - 32))));
    }
    cta_sync();
    if (w) {
        const uint4 in = __ldg((const uint4*)p.m + (tid - 32) * (p.E / 2 / (NT - 32)));
        const Mat4 wd = load_mat4(p.w_down, lane);
        for (int i = SM_DATA / 16 + tid - 32; i < ZEND / 16; i += NT - 32) ((uint4*)smem)[i] = make_uint4(0, 0, 0, 0);
        if (tid - 32 < 256) ((uint4*)(smem + SM_ZERO))[tid - 32] = make_uint4(0, 0, 0, 0);
        if (tid < 48) sts32(sb + SM_CNT2 + (tid - 32) * 4, NQ2 << 16);
        __syncwarp();
        if (CFG_PFD && tid == NT - 1) {
            __nanosleep(CFG_PFD);
            const uint32_t n = (p.E / 2 + NCTA - 1) / NCTA, o = blockIdx.x * n;
            if (o < (uint32_t)p.E / 2) asm volatile("cp.async.bulk.prefetch.L2.global [%0], %1;" ::"l"((const uint4*)p.m + o), "r"(min(n, p.E / 2 - o) * 16) : "memory");
        }
        __syncwarp();
        md_stats(in, wd, lane);
    } else assign_role(p, sb, lane);
    if (tid == 0) {
        mbar_init(sb + SM_DONE, lds32(sb + SM_MISC) >> 8 ? P2W : P1W);
        mbar_init(sb + SM_DONE2, NF);
    }
    cta_sync();
    const uint32_t rid = __shfl_sync(0xffffffffu, lds32(sb + SM_MISC), 0);
    const int role = rid >> 8, id = rid & 255;
    TR(5, tid == 0);
    if (role == 0) {
        const int ww = CFG_MAP1 == 0 ? ((w & 3) == 3 ? NW : (w >> 2) * 3 + (w & 3)) : CFG_MAP1 == 1 ? (w & 2 ? NW : (w >> 2) * 2 + (w & 1)) : w;
        const int sw = CFG_MAP1 == 0 ? ((w & 3) == 3 ? w >> 2 : NW) : CFG_MAP1 == 1 ? (w & 2 ? (w >> 2) * 2 + (w & 1) : NW) : w - P1W;
        static_assert(CFG_MAP1 == 0 ? (P1W <= NW / 4 * 3 && NF + 2 <= NW / 4) : CFG_MAP1 == 1 ? (P1W <= NW / 2 && NF + 2 <= NW / 2) : true, "warp map");
        for (int i = tid; i < NF * GPW * 32; i += NT) sts32(sb + A_CNT + i * 4, 1u << 24);
        if (tid < 64) sts32(sb + SM_CRED + tid * 4, 0u);
        cta_sync();
        TR(1, tid == 0);
        if (ww < P1W) role_p1(p, sb, id, ww, lane);
        else if (sw < NF) role_flush(p, sb, id, sw, lane);
        else if (sw == NF) role_credit1(p, sb, id, lane);
        else if (w == NW - 1) {
            uint4* owin = (uint4*)(p.ring + (CWIN + (lds32(sb + SM_MISC + 16) ^ 1)) * WIN);
            for (int i = id * 32 + lane; i < CPAIRS * 512; i += N1 * 32) __stcg(owin + i, make_uint4(0, 0, 0, 0));
            __syncwarp();
        }
    } else if (role == 1) {
        const int row0 = id % H2 * p.rows2;
        const int nrows = min((int)p.rows2, p.E - row0);
        constexpr int NTB = NT - 32, TBD = CFG_TBD;
        bool flagged = false;
        if (w < NW - 1) {
            const Scale sc = get_scale(sb);
            const Mat4 wd = load_mat4(p.w_down, lane);
            Mat4 ws;
#pragma unroll
            for (int k = 0; k < 4; k++) ws.b[k] = mul_bf2(wd.b[k], ((246u - (lane & 4 ? sc.eb[(k & 2) + 1] : sc.eb[k & 2])) << 7) * 0x10001u);
            const uint4* const src = (const uint4*)(p.m + row0);
            uint4 r2[TBD], nx[TBD];
            auto fetch = [&](int i) {
#pragma unroll
                for (int k = 0; k < TBD; k++)
                    asm volatile("ld.global.nc.v4.u32 {%0,%1,%2,%3}, [%4];" : "=r"(nx[k].x), "=r"(nx[k].y), "=r"(nx[k].z), "=r"(nx[k].w) : "l"(src + min(i + k * NTB, nrows / 2 - 1)));
            };
            fetch(tid);
#pragma unroll 1
            for (int i0 = tid; 2 * (i0 - lane) < nrows; i0 += TBD * NTB) {
#pragma unroll
                for (int k = 0; k < TBD; k++) r2[k] = make_uint4(nx[k].x, nx[k].z, nx[k].y, nx[k].w);
                fetch(i0 + TBD * NTB);
#pragma unroll
                for (int k = 0; k < TBD; k++) {
                    const int i = i0 + k * NTB;
                    float y[8];
                    mul4(make_uint4(r2[k].x, r2[k].z, r2[k].y, r2[k].w), ws, y);
                    uint32_t a[4], h[4], ta[2];
#pragma unroll
                    for (int j = 0; j < 4; j++) { a[j] = pack_h2(y[2 * j], y[2 * j + 1]); h[j] = a[j] + 0x00040004u; }
#pragma unroll
                    for (int j = 0; j < 2; j++) ta[j] = bitsel(h[2 * j], bitsel(h[2 * j + 1] >> 3, h[2 * j + 1] << 7, 0x00070007u), 0x9ff89ff8u);
                    uint32_t tb = prmt(h[1], h[3], 0x7531);
                    const uint32_t b0 = a[0] | a[1] | h[0] | h[1], b1 = a[2] | a[3] | h[2] | h[3];
                    if (__any_sync(0xffffffffu, ((b0 | b1) & 0x60006000u) || sc.allslow)) {
                        if ((b0 & 0x60006000u) || sc.allslow) { ta[0] = 0; tb = (tb & 0xffff0000u) | 0x40u; }
                        if ((b1 & 0x60006000u) || sc.allslow) { ta[1] = 0; tb = (tb & 0xffffu) | 0x400000u; }
                        flagged = true;
                    }
                    sts64_if(sb + B_TA + i * 8, ta[0], ta[1], 2 * i < nrows);
                    sts32_if(sb + B_TB + i * 4, tb, 2 * i < nrows);
                }
            }
            if (tid == 0) {
                sts32(sb + B_TA + p.rows2 * 4, 0u);
                sts16(sb + B_TB + p.rows2 * 2, 0u);
            }
            TR(8, tid == 0);
        } else if (lane == 0) spin_ge(rdy_of(p, sb, id, id / H2), H3);
        __syncwarp();
        flagged = __any_sync(0xffffffffu, __syncthreads_or(flagged));
        TR(1, tid == 0);
        if (w < P2W) {
            if (flagged) role_p2<true>(p, sb, id, w, lane);
            else role_p2<false>(p, sb, id, w, lane);
        } else if (w == P2W) role_credit(p, sb, id, lane);
    } else {
        if (w == 0) clear_queues<false>(p, sb, id, lane);
        if (tid >= 32 && tid < 33 + NPC) mbar_init(sb + SM_CNT2 + (tid - 32) * 8, 1);
        cta_sync();
        TR(1, tid == 0);
        if (w < P3W) role_p3(p, sb, id, w, lane);
        cta_sync();
        TR(2, tid == 0);
        if (w < NPC && lane == 0) {
            fence_async_smem();
            const int n = min(((int)p.rows3 + 7) / 8 * 8 - w * RPC, RPC);
            if (w) mbar_wait(sb + SM_CNT2 + w * 8, 0);
            if (n > 0) {
                bulk_store(g_S[0][id] + w * RPC, sb + C_S + w * RPC * 4, n * 4);
                bulk_store(g_S[1][id] + w * RPC, sb + C_S + (ROWS3_MAX + w * RPC) * 4, n * 4);
            }
            asm volatile("cp.async.bulk.commit_group;" ::: "memory");
            asm volatile("cp.async.bulk.wait_group.read 0;" ::: "memory");
            mbar_arrive(sb + SM_CNT2 + w * 8 + 8);
            asm volatile("cp.async.bulk.wait_group 0;" ::: "memory");
            fence_gpu();
            red_rlx(rdy_of(p, sb, 160 + 32 * w, 0), 1u);
            red_rlx(rdy_of(p, sb, 160 + 32 * w, 1), 1u);
            if (id == 0 && w == 0) red_rlx(&g_epoch, 1u);
            TR(12 + w, true);
        }
        return;
    }
    cta_sync();
    TR(18, tid == 0 && role == 1);
    if (role == 0 && w == NW - 2) clear_queues<true>(p, sb, id, lane);
    tail_rows(p, role * N1 + id, w, lane);
}

__global__ void k_direct(const Params p, long long T) {
    float wd[16];
#pragma unroll
    for (int i = 0; i < 16; i++) wd[i] = __bfloat162float(p.w_down[i]);
    const float f = __bfloat162float(p.freq[0]);
    for (long long t = blockIdx.x * (long long)blockDim.x + threadIdx.x; t < T; t += (long long)gridDim.x * blockDim.x) {
        float x = __bfloat162float(__float2bfloat16(f * __bfloat162float(p.angle[t])));
        float c = __bfloat162float(__float2bfloat16(cosf(x)));
        uint2 md = down_row(__ldg(p.m + p.idx_in[t]), wd);
        red_v4(g_Sg + p.idx_out[t], c * bflo(md.x), c * bfhi(md.x), c * bflo(md.y), c * bfhi(md.y));
    }
}
__global__ void k_direct_tail(const Params p) {
    __shared__ __align__(16) float sw[96];
    load_tail_weights(p, sw, threadIdx.x);
    __syncthreads();
    uint32_t c2[4];
#pragma unroll
    for (int i = 0; i < 4; i++) c2[i] = ((const uint32_t*)p.centers)[i];
    for (int e = blockIdx.x * blockDim.x + threadIdx.x; e < p.E; e += gridDim.x * blockDim.x) {
        float4 g = __ldcg(g_Sg + e);
        __stcg(g_Sg + e, make_float4(0.f, 0.f, 0.f, 0.f));
        const float Sv[4] = {g.x, g.y, g.z, g.w};
        float4 gs, gr;
        row_gates(sw, c2, __bfloat16_as_ushort(p.dist[e]), gs, gr);
        p.out[e] = finish_row(sw + 64, gs, gr, Sv, __ldg(p.m + e));
    }
}

static bool pick_rows(int E, int n, int rows_max, int mult, uint32_t* rows, uint32_t* magic) {
    for (uint32_t r = (E + n - 1) / n; r <= (uint32_t)rows_max; r++) {
        if (r < 2 || r % mult) continue;
        uint64_t mg = ((1ull << 32) + r - 1) / r;
        uint64_t err = mg * r - (1ull << 32);
        if (err * (uint64_t)n < mg) { *rows = r; *magic = (uint32_t)mg; return true; }
    }
    return false;
}

}

extern "C" void kernel_launch(void* const* d_in, const int* in_sizes, int n_in, void* d_out, int out_size) {
    using namespace gs;
    (void)n_in; (void)out_size;
    Params p;
    p.m = (const uint2*)d_in[0];
    p.idx_in = (const int*)d_in[1];
    p.idx_out = (const int*)d_in[2];
    p.dist = (const __nv_bfloat16*)d_in[3];
    p.angle = (const __nv_bfloat16*)d_in[4];
    p.centers = (const __nv_bfloat16*)d_in[5];
    p.freq = (const __nv_bfloat16*)d_in[6];
    p.w_rbf = (const __nv_bfloat16*)d_in[7];
    p.w_sbf = (const __nv_bfloat16*)d_in[8];
    p.w_down = (const __nv_bfloat16*)d_in[9];
    p.w_up = (const __nv_bfloat16*)d_in[10];
    p.out = (uint2*)d_out;
    p.E = in_sizes[3];
    const long long T = in_sizes[1];
    p.n4 = (int)(T / 4);
    p.rows2 = p.magic2 = 0;
    p.ring = nullptr;

    static int sms = 0, rsv = 0;
    if (!sms) {
        int dev = 0;
        cudaGetDevice(&dev);
        cudaDeviceGetAttribute(&rsv, cudaDevAttrReservedSharedMemoryPerBlock, dev);
        cudaDeviceGetAttribute(&sms, cudaDevAttrMultiProcessorCount, dev);
        cudaFuncSetAttribute(k_main, cudaFuncAttributeMaxDynamicSharedMemorySize, SMEM_BYTES);
    }
    cudaStream_t st = cudaStreamPerThread;
    bool fast = (T % 4 == 0) && T > 0 && sms >= NCTA && rsv == (int)SB && p.E >= 65536 && p.E <= E_MAX &&
                p.E % 4 == 0 && (((uintptr_t)p.m | (uintptr_t)p.idx_in | (uintptr_t)p.idx_out | (uintptr_t)p.angle) & 15) == 0 &&
                pick_rows(p.E, NI, ROWS2_MAX, 2, &p.rows2, &p.magic2);
    p.c1 = 1;
    p.nrows2 = 0u - p.rows2;
    p.rows3 = (p.E + 31) / 32;
    fast = fast && (p.rows2 * (NI - 1) + 2 <= (uint32_t)p.E);
    static const void* tkey[3] = {nullptr, nullptr, nullptr};
    static cudaTextureObject_t tex[3] = {0, 0, 0};
    static long long tlen = -1;
    const void* tptr[3] = {p.idx_in, p.idx_out, p.angle};
    for (int k = 0; fast && k < 3; k++) {
        if (tkey[k] == tptr[k] && tlen == T) continue;
        if (tkey[k]) cudaDestroyTextureObject(tex[k]);
        tkey[k] = nullptr;
        cudaResourceDesc rd = {};
        rd.resType = cudaResourceTypeLinear;
        rd.res.linear.devPtr = (void*)tptr[k];
        rd.res.linear.desc = cudaCreateChannelDesc(32, 32, k < 2 ? 32 : 0, k < 2 ? 32 : 0, cudaChannelFormatKindUnsigned);
        rd.res.linear.sizeInBytes = (size_t)T * (k < 2 ? 4 : 2);
        cudaTextureDesc td = {};
        td.readMode = cudaReadModeElementType;
        if (cudaCreateTextureObject(&tex[k], &rd, &td, nullptr) == cudaSuccess) tkey[k] = tptr[k];
        else { (void)cudaGetLastError(); fast = false; }
    }
    if (fast) tlen = T;
    p.t_in = tex[0]; p.t_out = tex[1]; p.t_ang = tex[2];
    if (fast) {
        void* ring = nullptr;
        cudaGetSymbolAddress(&ring, g_ring);
        uintptr_t a = ((uintptr_t)ring + WIN - 1) & ~(uintptr_t)(WIN - 1);
        if (a >> 32 != (a + RING_BYTES - 1) >> 32) a += RING_BYTES;
        p.ring = (unsigned char*)a;
        p.ring_lo = (uint32_t)a;
        p.ring_hi = (uint32_t)(a >> 32);
        k_main<<<NCTA, NT, SMEM_BYTES, st>>>(p);
    } else {
        k_direct<<<sms * 8, 256, 0, st>>>(p, T);
        k_direct_tail<<<sms * 4, 256, 0, st>>>(p);
    }
}
```

```cpp
#include <cuda_runtime.h>
#include <cuda_bf16.h>
#include <stdint.h>

#define CFG_N1 56
#define CFG_NI 22
#define CFG_NW 28
#define CFG_P1W 14
#define CFG_GPW 2
#define CFG_KR 1
#define CFG_SMPAD 0
#define CFG_QPW 3
#define CFG_TG 2
#define CFG_PMASK 8
#define CFG_PSTREAK 1
#define CFG_NBT 1
#define CFG_KM 5
#define CFG_KN 9
#define CFG_TBD 4
#define CFG_P0 500
#define CFG_PFD 200
#define CFG_C1SLEEP 200
#define CFG_PK1 6
#define CFG_PK2 8
#define CFG_PK3 11
#define CFG_CLN 2
#define CFG_CLS 300
#define CFG_DOUT 2
#define CFG_TH 14
#define CFG_TS 200
#define CFG_POLL 64
#define CFG_HINT 20000
#define CFG_BSLEEP 100
#define CFG_CSLEEP 200
#define CFG_FSLEEP 100
#define CFG_PSLEEP 100
#define CFG_DRY 1
#define CFG_PROBES 4

namespace gs {

constexpr int E_MAX = 640000;
constexpr int N1 = CFG_N1, NI = CFG_NI, N2 = 2 * NI, N3 = 32, NCTA = N1 + N2 + N3;
constexpr int H2 = NI, H3 = N3 / 2;
constexpr int NB = NI * N3;
constexpr int NW = CFG_NW, NT = NW * 32;
constexpr int GPW = CFG_GPW, NF = (NI + GPW - 1) / GPW;
constexpr int QPW = CFG_QPW, NBT = CFG_NBT;
constexpr int P1W = CFG_P1W, P2W = (N1 + QPW - 1) / QPW, P3W = NI;
constexpr int NQ1 = 32, NQ2 = 64;
constexpr int ROWS2_MAX = ((E_MAX + NI - 1) / NI + 31) / 8 * 8;
constexpr int ROWS3_MAX = (E_MAX / 32 + 31) / 32 * 32;
constexpr int NTAIL = N1 + N2;
constexpr int NPC = 5, WPP = 5, RPC = NTAIL * WPP * 8;
constexpr int GUARD = 1 << 26;
static_assert(NCTA % 4 == 0 && NCTA <= 192, "roles come in CTA pairs, per partition");
static_assert((GPW == 2 || GPW == 4) && QPW >= NBT && QPW <= 4 && NI <= 32 && N1 <= 62, "queue ownership");
static_assert(P1W + NF + 2 <= NW && P2W + 2 <= NW && P3W + 1 <= NW && P1W * 256 + 64 < 8192, "warp roles");
static_assert(ROWS2_MAX + 8 <= 32768 && ROWS3_MAX <= 32768, "index bits");

constexpr uint32_t SB = 1024;
constexpr int SM_DONE = 0, SM_DONE2 = 8;
constexpr int SM_MISC = 16;
constexpr int SM_FIN = 48;
constexpr int SM_STAT = 64;
constexpr int SM_CNT2 = 128;
constexpr int SM_W = 256;
constexpr int SM_PUB = SM_W + 384;
constexpr int SM_PROBE = SM_PUB + 768;
constexpr int SM_CRED = 1792;
constexpr int SM_DATA = 2048;
constexpr int cmax(int a, int b) { return a > b ? a : b; }
constexpr int A_CNT = SM_DATA;
constexpr int A_LIST = A_CNT + NF * GPW * 128;
constexpr int KR = CFG_KR, LISTB = (GPW * 32 + 8 * KR) * 4;
constexpr int A_ST = (A_LIST + NF * LISTB + 127) / 128 * 128;
constexpr int A_END = A_ST + NB * 256;
constexpr int B_TA = SM_DATA;
constexpr int B_TB = B_TA + (ROWS2_MAX + 8) * 4;
constexpr int B_END = B_TB + (ROWS2_MAX + 8) * 2;
constexpr int C_S = SM_DATA;
constexpr int C_END = C_S + ROWS3_MAX * 8;
constexpr int T_G = SM_DATA, TWB = 4096 + 2048 + 512, T_END = T_G + NPC * WPP * TWB;
constexpr int ZEND = cmax(A_END, C_END);
constexpr int SM_ZERO = (cmax(C_END, T_END) + 127) / 128 * 128;
constexpr int SMEM_BYTES = cmax(cmax(A_END, B_END), SM_ZERO + 4096) + CFG_SMPAD;
static_assert(SMEM_BYTES <= 232448 && SM_PROBE + 128 <= SM_CRED, "shared memory");
static_assert(NPC * RPC >= ROWS3_MAX && NPC * WPP + 2 <= NW, "tail");

constexpr uint32_t FIN = 0x80000000u;

constexpr uint32_t WIN = 524288;
constexpr int CWIN = N2 + N3, NWIN = CWIN + 2, CPAIRS = 31;
constexpr uint32_t PROBE_OFF = (uint32_t)NWIN * WIN;
constexpr int NPROBE = 16;
static_assert(NWIN <= NCTA && NPROBE <= NW, "windows");
constexpr size_t RING_BYTES = (size_t)PROBE_OFF + WIN;
__device__ __align__(128) unsigned char g_ring[2 * RING_BYTES + WIN];
__device__ __align__(128) uint32_t g_S[2][32][ROWS3_MAX];
__device__ __align__(128) float4 g_Sg[E_MAX];
__device__ uint32_t g_dirty[E_MAX / 32];
__device__ uint32_t g_epoch;

#define TR(ev, on)
#define ACC_DECL
#define ACC(i, n)
#define ACC_SAVE

struct Params {
    const uint2* m;
    const int* idx_in;
    const int* idx_out;
    const __nv_bfloat16* dist;
    const __nv_bfloat16* angle;
    const __nv_bfloat16* centers;
    const __nv_bfloat16* freq;
    const __nv_bfloat16* w_rbf;
    const __nv_bfloat16* w_sbf;
    const __nv_bfloat16* w_down;
    const __nv_bfloat16* w_up;
    uint2* out;
    unsigned char* ring;
    cudaTextureObject_t t_in, t_out, t_ang;
    int E, n4;
    uint32_t rows2, nrows2, magic2, rows3;
    uint32_t ring_lo, ring_hi, c1;
};

__device__ __forceinline__ float bflo(uint32_t w) { return __uint_as_float(w << 16); }
__device__ __forceinline__ float bfhi(uint32_t w) { return __uint_as_float(w & 0xffff0000u); }
__device__ __forceinline__ uint32_t pack_bf2(float lo, float hi) {
    uint32_t r;
    asm("cvt.rn.bf16x2.f32 %0, %1, %2;" : "=r"(r) : "f"(hi), "f"(lo));
    return r;
}
__device__ __forceinline__ uint32_t mul_bf2(uint32_t a, uint32_t b) {
    uint32_t r;
    asm("mul.rn.bf16x2 %0, %1, %2;" : "=r"(r) : "r"(a), "r"(b));
    return r;
}
__device__ __forceinline__ uint32_t sub_bf2(uint32_t a, uint32_t b) {
    uint32_t r;
    asm("sub.rn.bf16x2 %0, %1, %2;" : "=r"(r) : "r"(a), "r"(b));
    return r;
}
__device__ __forceinline__ uint32_t maxabs_bf2(uint32_t a, uint32_t b) {
    uint32_t r;
    asm("max.NaN.xorsign.abs.bf16x2 %0, %1, %2;" : "=r"(r) : "r"(a), "r"(b));
    return r;
}
__device__ __forceinline__ void mbar_init(uint32_t a, uint32_t n) {
    asm volatile("mbarrier.init.shared::cta.b64 [%0], %1;" ::"r"(a), "r"(n) : "memory");
}
__device__ __forceinline__ void mbar_arrive(uint32_t a) {
    asm volatile("mbarrier.arrive.shared::cta.b64 _, [%0];" ::"r"(a) : "memory");
}
__device__ __forceinline__ void mbar_arrive_n(uint32_t a, uint32_t n) {
    asm volatile("mbarrier.arrive.shared::cta.b64 _, [%0], %1;" ::"r"(a), "r"(n) : "memory");
}
__device__ __forceinline__ void mbar_arrive_if(uint32_t a, bool on) {
    asm volatile("{.reg .pred q; setp.ne.u32 q, %1, 0; @q mbarrier.arrive.shared::cta.b64 _, [%0];}" ::"r"(a), "r"((uint32_t)on) : "memory");
}
__device__ __forceinline__ void mbar_wait(uint32_t a, uint32_t parity) {
    uint32_t ok;
    int guard = 0;
    do {
        asm volatile("{.reg .pred p; mbarrier.try_wait.parity.shared::cta.b64 p, [%1], %2, %3; selp.u32 %0, 1, 0, p;}"
                     : "=r"(ok) : "r"(a), "r"(parity), "r"(CFG_HINT) : "memory");
        if (!ok) {
            if (++guard > GUARD) __trap();
        }
    } while (!ok);
}
__device__ __forceinline__ void cta_sync() { __syncwarp(); __syncthreads(); }
__device__ __forceinline__ void bar_sync(int id, int n) { asm volatile("bar.sync %0, %1;" ::"r"(id), "r"(n) : "memory"); }
__device__ __forceinline__ void bar_arrive(int id, int n) { asm volatile("bar.arrive %0, %1;" ::"r"(id), "r"(n) : "memory"); }
__device__ __forceinline__ bool mbar_test(uint32_t a, uint32_t parity) {
    uint32_t ok;
    asm volatile("{.reg .pred p; mbarrier.test_wait.parity.shared::cta.b64 p, [%1], %2; selp.u32 %0, 1, 0, p;}"
                 : "=r"(ok) : "r"(a), "r"(parity) : "memory");
    return ok;
}
__device__ __forceinline__ uint32_t ld_acq(const uint32_t* p) {
    uint32_t v;
    asm volatile("ld.acquire.gpu.global.u32 %0, [%1];" : "=r"(v) : "l"(p) : "memory");
    return v;
}
__device__ __forceinline__ uint32_t ld_rlx(const uint32_t* p) {
    uint32_t v;
    asm volatile("ld.relaxed.gpu.global.u32 %0, [%1];" : "=r"(v) : "l"(p) : "memory");
    return v;
}
__device__ __forceinline__ void st_rlx(uint32_t* p, uint32_t v) {
    asm volatile("st.relaxed.gpu.global.u32 [%0], %1;" ::"l"(p), "r"(v) : "memory");
}
__device__ __forceinline__ void red_rlx(uint32_t* p, uint32_t v) {
    asm volatile("red.relaxed.gpu.global.add.u32 [%0], %1;" ::"l"(p), "r"(v) : "memory");
}
__device__ __forceinline__ bool elect_one() {
    uint32_t p;
    asm volatile("{.reg .pred P; elect.sync _|P, 0xffffffff; selp.u32 %0, 1, 0, P;}" : "=r"(p));
    return p;
}
__device__ __forceinline__ uint32_t spin_ge(const uint32_t* p, uint32_t target) {
    int guard = 0;
    while (ld_rlx(p) < target) {
        __nanosleep(CFG_POLL);
        if (++guard > GUARD) __trap();
    }
    return ld_acq(p);
}
__device__ __forceinline__ void fence_gpu() { asm volatile("fence.acq_rel.gpu;" ::: "memory"); }
__device__ __forceinline__ void fence_async_smem() { asm volatile("fence.proxy.async.shared::cta;" ::: "memory"); }
__device__ __forceinline__ void fence_async_all() { asm volatile("fence.proxy.async;" ::: "memory"); }
__device__ __forceinline__ void bulk_store(void* g, uint32_t s, uint32_t bytes) {
    asm volatile("cp.async.bulk.global.shared::cta.bulk_group [%0], [%1], %2;" ::"l"(g), "r"(s), "r"(bytes) : "memory");
}
__device__ __forceinline__ void cp16(uint32_t s, const void* g, bool on) {
    asm volatile("{.reg .pred q; setp.ne.u32 q, %2, 0; @q cp.async.cg.shared.global [%0], [%1], 16;}" ::"r"(s), "l"(g), "r"((uint32_t)on) : "memory");
}
__device__ __forceinline__ void cp16z(uint32_t s, const void* g, int bytes) {
    asm volatile("cp.async.cg.shared.global [%0], [%1], 16, %2;" ::"r"(s), "l"(g), "r"(bytes) : "memory");
}
__device__ __forceinline__ void cp_commit() { asm volatile("cp.async.commit_group;" ::: "memory"); }
template <int N> __device__ __forceinline__ void cp_wait() { asm volatile("cp.async.wait_group %0;" ::"n"(N) : "memory"); }
__device__ __forceinline__ uint32_t atoms_add(uint32_t a, uint32_t v) {
    uint32_t o;
    asm volatile("atom.shared.add.u32 %0, [%1], %2;" : "=r"(o) : "r"(a), "r"(v) : "memory");
    return o;
}
__device__ __forceinline__ void sts32(uint32_t a, uint32_t v) { asm volatile("st.shared.u32 [%0], %1;" ::"r"(a), "r"(v) : "memory"); }
__device__ __forceinline__ void sts16(uint32_t a, uint32_t v) { asm volatile("st.shared.u16 [%0], %1;" ::"r"(a), "h"((uint16_t)v) : "memory"); }
__device__ __forceinline__ void sts64(uint32_t a, uint32_t x, uint32_t y) { asm volatile("st.shared.v2.u32 [%0], {%1,%2};" ::"r"(a), "r"(x), "r"(y) : "memory"); }
__device__ __forceinline__ uint32_t lds32(uint32_t a) {
    uint32_t v;
    asm volatile("ld.shared.u32 %0, [%1];" : "=r"(v) : "r"(a) : "memory");
    return v;
}
__device__ __forceinline__ uint2 lds64(uint32_t a) {
    uint2 v;
    asm volatile("ld.shared.v2.u32 {%0,%1}, [%2];" : "=r"(v.x), "=r"(v.y) : "r"(a));
    return v;
}
__device__ __forceinline__ uint2 lds64v(uint32_t a) {
    uint2 v;
    asm volatile("ld.volatile.shared.v2.u32 {%0,%1}, [%2];" : "=r"(v.x), "=r"(v.y) : "r"(a) : "memory");
    return v;
}
__device__ __forceinline__ uint32_t lds32v(uint32_t a) {
    uint32_t v;
    asm volatile("ld.volatile.shared.u32 %0, [%1];" : "=r"(v) : "r"(a) : "memory");
    return v;
}
__device__ __forceinline__ uint4 lds128(uint32_t a) {
    uint4 v;
    asm volatile("ld.shared.v4.u32 {%0,%1,%2,%3}, [%4];" : "=r"(v.x), "=r"(v.y), "=r"(v.z), "=r"(v.w) : "r"(a) : "memory");
    return v;
}
__device__ __forceinline__ void sts128(uint32_t a, uint4 v) {
    asm volatile("st.shared.v4.u32 [%0], {%1,%2,%3,%4};" ::"r"(a), "r"(v.x), "r"(v.y), "r"(v.z), "r"(v.w) : "memory");
}
#define LD_Q "ld.relaxed.gpu.global"
__device__ __forceinline__ uint4 ldg_q128(const void* p) {
    uint4 v;
    asm volatile(LD_Q ".v4.u32 {%0,%1,%2,%3}, [%4];"
                 : "=r"(v.x), "=r"(v.y), "=r"(v.z), "=r"(v.w) : "l"(p) : "memory");
    return v;
}
__device__ __forceinline__ uint2 ldg_q64(const void* p) {
    uint2 v;
    asm volatile(LD_Q ".v2.u32 {%0,%1}, [%2];" : "=r"(v.x), "=r"(v.y) : "l"(p) : "memory");
    return v;
}
__device__ __forceinline__ void red_v4(float4* p, float a, float b, float c, float d) {
    asm volatile("red.global.add.v4.f32 [%0], {%1,%2,%3,%4};" ::"l"(p), "f"(a), "f"(b), "f"(c), "f"(d) : "memory");
}
__device__ __forceinline__ uint2 down_row(uint2 r, const float* wd) {
    float x0 = bflo(r.x), x1 = bfhi(r.x), x2 = bflo(r.y), x3 = bfhi(r.y);
    float y[4];
#pragma unroll
    for (int j = 0; j < 4; j++) y[j] = x0 * wd[j] + x1 * wd[4 + j] + x2 * wd[8 + j] + x3 * wd[12 + j];
    return make_uint2(pack_bf2(y[0], y[1]), pack_bf2(y[2], y[3]));
}
__device__ __forceinline__ uint32_t prmt(uint32_t a, uint32_t b, uint32_t s) {
    uint32_t r;
    asm("prmt.b32 %0, %1, %2, %3;" : "=r"(r) : "r"(a), "r"(b), "r"(s));
    return r;
}
__device__ __forceinline__ uint32_t bitsel(uint32_t a, uint32_t b, uint32_t m) {
    uint32_t r;
    asm("lop3.b32 %0, %1, %2, %3, 0xE4;" : "=r"(r) : "r"(a), "r"(b), "r"(m));
    return r;
}
__device__ __forceinline__ uint32_t pack_h2(float lo, float hi) {
    uint32_t r;
    asm("cvt.rn.f16x2.f32 %0, %1, %2;" : "=r"(r) : "f"(hi), "f"(lo));
    return r;
}
__device__ __forceinline__ uint32_t mul_h2(uint32_t a, uint32_t b) {
    uint32_t r;
    asm("mul.rn.f16x2 %0, %1, %2;" : "=r"(r) : "r"(a), "r"(b));
    return r;
}
__device__ __forceinline__ uint32_t lds32nv(uint32_t a) {
    uint32_t v;
    asm volatile("ld.shared.u32 %0, [%1];" : "=r"(v) : "r"(a));
    return v;
}
__device__ __forceinline__ uint32_t lds16nv(uint32_t a) {
    uint32_t v;
    asm volatile("ld.shared.u16 %0, [%1];" : "=r"(v) : "r"(a));
    return v;
}
#define X_CR1
#define X_CR2
#define X_ST1
#define X_ST2
#define ST_Q "st.relaxed.gpu.global"
__device__ __forceinline__ void stg_q128(void* p, uint32_t a, uint32_t b, uint32_t c, uint32_t d, bool on) {
    asm volatile("{.reg .pred q; setp.ne.u32 q, %5, 0; @q " ST_Q ".v4.u32 [%0], {%1,%2,%3,%4};}"
                 ::"l"(p), "r"(a), "r"(b), "r"(c), "r"(d), "r"((uint32_t)on) : "memory");
}
__device__ __forceinline__ void stg_q64(void* p, uint32_t a, uint32_t b, bool on) {
    asm volatile("{.reg .pred q; setp.ne.u32 q, %3, 0; @q " ST_Q ".v2.u32 [%0], {%1,%2};}"
                 ::"l"(p), "r"(a), "r"(b), "r"((uint32_t)on) : "memory");
}
__device__ __forceinline__ void st_rlx_if(uint32_t* p, uint32_t v, bool on) {
    asm volatile("{.reg .pred q; setp.ne.u32 q, %2, 0; @q st.relaxed.gpu.global.u32 [%0], %1;}" ::"l"(p), "r"(v), "r"((uint32_t)on) : "memory");
}
__device__ __forceinline__ uint32_t ld_rlx_if(const uint32_t* p, bool on) {
    uint32_t v;
    asm volatile("{.reg .pred q; setp.ne.u32 q, %2, 0; mov.b32 %0, 0; @q ld.relaxed.gpu.global.u32 %0, [%1];}" : "=&r"(v) : "l"(p), "r"((uint32_t)on) : "memory");
    return v;
}
__device__ __forceinline__ void ldq128_keep(uint4& v, const void* p, bool on) {
    asm volatile("{.reg .pred q; setp.ne.u32 q, %5, 0; @q ld.relaxed.gpu.global.v4.u32 {%0,%1,%2,%3}, [%4];}"
                 : "+r"(v.x), "+r"(v.y), "+r"(v.z), "+r"(v.w) : "l"(p), "r"((uint32_t)on) : "memory");
}
__device__ __forceinline__ void ldq64_keep(uint2& v, const void* p, bool on) {
    asm volatile("{.reg .pred q; setp.ne.u32 q, %3, 0; @q ld.relaxed.gpu.global.v2.u32 {%0,%1}, [%2];}"
                 : "+r"(v.x), "+r"(v.y) : "l"(p), "r"((uint32_t)on) : "memory");
}
__device__ __forceinline__ void atoms_add_keep(uint32_t& o, uint32_t a, uint32_t v, bool on) {
    asm volatile("{.reg .pred q; setp.ne.u32 q, %3, 0; @q atom.shared.add.u32 %0, [%1], %2;}" : "+r"(o) : "r"(a), "r"(v), "r"((uint32_t)on) : "memory");
}
__device__ __forceinline__ void reds_add(uint32_t a, uint32_t v) { asm volatile("red.shared.add.u32 [%0], %1;" ::"r"(a), "r"(v) : "memory"); }
__device__ __forceinline__ void sts32_if(uint32_t a, uint32_t v, bool on) {
    asm volatile("{.reg .pred q; setp.ne.u32 q, %2, 0; @q st.shared.u32 [%0], %1;}" ::"r"(a), "r"(v), "r"((uint32_t)on) : "memory");
}
__device__ __forceinline__ void sts64_if(uint32_t a, uint32_t x, uint32_t y, bool on) {
    asm volatile("{.reg .pred q; setp.ne.u32 q, %3, 0; @q st.shared.v2.u32 [%0], {%1,%2};}" ::"r"(a), "r"(x), "r"(y), "r"((uint32_t)on) : "memory");
}
__device__ __forceinline__ void lds128_keep(uint4& v, uint32_t a, bool on) {
    asm volatile("{.reg .pred q; setp.ne.u32 q, %5, 0; @q ld.volatile.shared.v4.u32 {%0,%1,%2,%3}, [%4];}"
                 : "+r"(v.x), "+r"(v.y), "+r"(v.z), "+r"(v.w) : "r"(a), "r"((uint32_t)on) : "memory");
}
__device__ __forceinline__ void or3_if(uint32_t& x, uint32_t a, uint32_t b, bool on) {
    asm("{.reg .pred q; setp.ne.u32 q, %3, 0; @q lop3.b32 %0, %0, %1, %2, 0xfe;}" : "+r"(x) : "r"(a), "r"(b), "r"((uint32_t)on));
}
__device__ __forceinline__ uint32_t clk() {
    uint32_t t;
    asm volatile("mov.u32 %0, %%clock;" : "=r"(t) :: "memory");
    return t;
}
__device__ __forceinline__ void sg_add(int row, float a, float b, float c, float d) {
    red_v4(g_Sg + row, a, b, c, d);
    st_rlx(g_dirty + (row >> 5), 1u);
}
__device__ __forceinline__ void slow_add(const uint2* m, uint32_t sb, int in, int out, float c) {
    const uint2 r = __ldg(m + in);
    const float x[4] = {bflo(r.x), bfhi(r.x), bflo(r.y), bfhi(r.y)};
    float y[4] = {0.f, 0.f, 0.f, 0.f};
#pragma unroll
    for (int k = 0; k < 4; k++) {
        const uint4 q = lds128(sb + SM_W + 320 + k * 16);
        y[0] = k ? y[0] + x[k] * __uint_as_float(q.x) : x[k] * __uint_as_float(q.x);
        y[1] = k ? y[1] + x[k] * __uint_as_float(q.y) : x[k] * __uint_as_float(q.y);
        y[2] = k ? y[2] + x[k] * __uint_as_float(q.z) : x[k] * __uint_as_float(q.z);
        y[3] = k ? y[3] + x[k] * __uint_as_float(q.w) : x[k] * __uint_as_float(q.w);
    }
    const uint32_t lo = pack_bf2(y[0], y[1]), hi = pack_bf2(y[2], y[3]);
    sg_add(out, c * bflo(lo), c * bfhi(lo), c * bflo(hi), c * bfhi(hi));
}

struct Mat4 { uint32_t b[4]; };
__device__ __forceinline__ Mat4 load_mat4(const __nv_bfloat16* w, int lane) {
    const unsigned short* u = (const unsigned short*)w + (lane >> 2 & 1);
    const bool on = lane >> 3 == (lane & 3);
    Mat4 m;
#pragma unroll
    for (int k = 0; k < 4; k++) m.b[k] = on ? u[(k & 1) * 8 + (k & 2)] | (uint32_t)u[(k & 1) * 8 + 4 + (k & 2)] << 16 : 0u;
    return m;
}
__device__ __forceinline__ void mul4(const uint4& x, const Mat4& m, float (&y)[8]) {
#pragma unroll
    for (int h = 0; h < 2; h++)
        asm("mma.sync.aligned.m16n8k16.row.col.f32.bf16.bf16.f32 {%0,%1,%2,%3}, {%4,%5,%6,%7}, {%8,%9}, {%10,%10,%10,%10};"
            : "=f"(y[2 * h]), "=f"(y[2 * h + 1]), "=f"(y[4 + 2 * h]), "=f"(y[5 + 2 * h])
            : "r"(x.x), "r"(x.z), "r"(x.y), "r"(x.w), "r"(m.b[2 * h]), "r"(m.b[2 * h + 1]), "f"(0.f));
}

struct Scale { uint32_t eb[4]; bool allslow; };
__device__ __forceinline__ void md_stats(const uint4& in, const Mat4& wd, int lane) {
    float y[8];
    mul4(in, wd, y);
    uint32_t mx[4], se[4];
#pragma unroll
    for (int c = 0; c < 4; c++) {
        uint32_t a = __float_as_uint(y[c]) & 0x7fffffffu, b = __float_as_uint(y[4 + c]) & 0x7fffffffu;
        if (a >= 0x7f800000u) a = 0;
        if (b >= 0x7f800000u) b = 0;
        mx[c] = __reduce_max_sync(0xffffffffu, max(a, b));
        se[c] = __reduce_add_sync(0xffffffffu, (a >> 23) + (b >> 23) + (a ? 1u << 20 : 0u) + (b ? 1u << 20 : 0u));
    }
    if (lane < 4) {
        asm volatile("red.shared.max.u32 [%0], %1;" ::"r"(SB + SM_STAT + lane * 4), "r"(lane == 0 ? mx[0] : lane == 1 ? mx[1] : lane == 2 ? mx[2] : mx[3]) : "memory");
        reds_add(SB + SM_STAT + 16 + lane * 4, lane == 0 ? se[0] : lane == 1 ? se[1] : lane == 2 ? se[2] : se[3]);
    }
}
__device__ __forceinline__ Scale get_scale(uint32_t sb) {
    Scale s;
    s.allslow = false;
#pragma unroll
    for (int k = 0; k < 4; k++) {
        const uint32_t mx = lds32(sb + SM_STAT + 4 * k), se = lds32(sb + SM_STAT + 16 + 4 * k);
        const uint32_t mean = (uint32_t)__fdividef((float)(se & 0xfffffu), (float)max(se >> 20, 1u));
        uint32_t eb = min(min((mx + 0x6e0000u) >> 23, mean + 5u), 227u);
        if (eb < 27u) { s.allslow = s.allslow || mx != 0; eb = 27u; }
        if (eb > 170u) s.allslow = true;
        s.eb[k] = eb;
    }
    return s;
}

__device__ __forceinline__ uint32_t probe_rt(uint32_t* p) {
    uint32_t best = 0xffffffffu;
#pragma unroll 1
    for (int r = 0; r < CFG_PROBES; r++) {
        const uint32_t t0 = clock();
        uint32_t v;
        asm volatile("atom.relaxed.gpu.global.add.u32 %0, [%1], 1;" : "=r"(v) : "l"(p) : "memory");
        if (v > 100000u) __trap();
        const uint32_t t1 = clock();
        best = min(best, t1 - t0);
    }
    return best;
}
__device__ __forceinline__ uint32_t* pub_ptr(const Params& p, int blk, uint32_t sel) {
    const int pr = blk / 44;
    return (uint32_t*)(p.ring + PROBE_OFF + (pr ? 4096u << pr : 0u) + (sel << 12) + 2176 + (blk - pr * 44) * 32);
}
__device__ __forceinline__ void probe(const Params& p, uint32_t sb, int w, int lane) {
    const int blk = blockIdx.x, pr = w >> 1;
    uint32_t off = PROBE_OFF + blk * 16 + (pr ? 4096u << pr : 0u);
    if (pr == 7) off = blk < NWIN ? blk * WIN + 4064 : PROBE_OFF + 3584 + blk % 16 * 32;
    off += (w & 1) * 4096;
    if (lane < 8) st_rlx((uint32_t*)(p.ring + (off & ~31u)) + lane, 0u);
    if (lane == 0) sts32(sb + SM_PROBE + w * 4, probe_rt((uint32_t*)(p.ring + off)));
}
__device__ __forceinline__ void assign_role(const Params& p, uint32_t sb, int lane) {
    {
        const bool x = lane < 8 && lds32(sb + SM_PROBE + lane * 8 + 4) < lds32(sb + SM_PROBE + lane * 8);
        const uint32_t near = __ballot_sync(0xffffffffu, x), bits = near & 1 ? ~near | 1u : near;
        const uint32_t tag = (lds32(sb + SM_MISC + 16) + 1) << 30;
        if (lane < 16) st_rlx(pub_ptr(p, blockIdx.x, lane >> 3) + (lane & 7), tag | (bits & 0xffu));
        constexpr int K = (NCTA + 31) / 32;
        __nanosleep(CFG_P0);
        uint32_t v[K], bad;
        int guard = 0;
        do {
            bad = 0;
#pragma unroll
            for (int k = 0; k < K; k++) {
                const int b = min(lane + 32 * k, NCTA - 1);
                v[k] = ld_rlx(pub_ptr(p, b, near >> (b / 44) & 1));
                bad |= v[k] ^ tag;
            }
            bad = __any_sync(0xffffffffu, bad >> 30);
            if (bad) __nanosleep(CFG_PSLEEP);
            if (++guard > GUARD) __trap();
        } while (bad);
#pragma unroll
        for (int k = 0; k < K; k++) sts32(sb + SM_PUB + (lane + 32 * k) * 4, v[k]);
    }
    __syncwarp();
    constexpr int NP = NCTA / 2, NTAB = H2 + H3;
    const int me = blockIdx.x >> 1, odd = blockIdx.x & 1;
    uint32_t pp[3], key[3];
    int n1 = 0;
#pragma unroll
    for (int k = 0; k < 3; k++) {
        const int i = lane + 32 * k;
        pp[k] = lds32(sb + SM_PUB + min(i, NP - 1) * 8) & 1;
        key[k] = (i * CFG_KM % CFG_KN) << 8 | i;
        n1 += 2 * __popc(__ballot_sync(0xffffffffu, i < NP && pp[k]));
    }
    bool fixed = n1 < NTAB || NCTA - n1 < NTAB;
    if (fixed) {
        n1 = NP / 2 * 2;
        pp[0] = pp[1] = pp[2] = lane & 1;
    }
    const uint32_t mine = __shfl_sync(0xffffffffu, (me < 32 ? key[0] : me < 64 ? key[1] : key[2]) * 2 + (me < 32 ? pp[0] : me < 64 ? pp[1] : pp[2]), me & 31);
    const int part = mine & 1;
    int pos = odd;
#pragma unroll
    for (int k = 0; k < 3; k++) pos += 2 * __popc(__ballot_sync(0xffffffffu, lane + 32 * k < NP && pp[k] == (uint32_t)part && key[k] < mine / 2));
    const int role = pos < H2 ? 1 : pos < NTAB ? 2 : 0;
    const int id = pos < H2 ? part * H2 + pos : pos < NTAB ? part * H3 + pos - H2 : (part ? NCTA - n1 - NTAB : 0) + pos - NTAB;
    const uint32_t v = lds32(sb + SM_PUB + lane * 4);
    uint32_t lin = 0;
#pragma unroll
    for (int b = 0; b < 6; b++) lin |= (__popc(__ballot_sync(0xffffffffu, (v >> (b + 1)) & 1)) > 16 ? 1u : 0u) << b;
    if (lane == 0) {
        sts32(sb + SM_MISC, role << 8 | id);
        sts32(sb + SM_MISC + 4, lin);
        sts32(sb + SM_MISC + 8, NCTA - n1 - NTAB);
        sts32(sb + SM_MISC + 20, part);
        sts32(sb + SM_MISC + 12, role == 0 ? id : role == 1 ? N1 + id : N1 + N2 + id);
    }
}
__device__ __forceinline__ uint32_t sel_of(uint32_t sb, int widx, uint32_t k, int part) {
    return (__popc(k & lds32(sb + SM_MISC + 4)) ^ (lds32(sb + SM_PUB + widx * 4) >> 7) ^ part) & 1;
}
__device__ __forceinline__ uint32_t gran_off(uint32_t sb, int widx, int k, int part) { return (2 * k + sel_of(sb, widx, k, part)) << 12; }
__device__ __forceinline__ uint32_t q1a_off(uint32_t sb, int src, int blk, int part) { return gran_off(sb, 2 * blk + part, src >> 1, part) + (src & 1) * 2048; }
__device__ __forceinline__ uint32_t q1h_off(uint32_t sb, int src, int blk, int part) { return gran_off(sb, 2 * blk + part, 32 + (src >> 2), part) + (src & 3) * 1024; }
__device__ __forceinline__ uint32_t* ctl_word(const Params& p, uint32_t sb, int k, int word, int part) {
    const int widx = CWIN + lds32(sb + SM_MISC + 16);
    return (uint32_t*)(p.ring + (widx * WIN + ((2 * k + sel_of(sb, widx, k, part)) << 12))) + word;
}
__device__ __forceinline__ uint32_t* cred1_of(const Params& p, uint32_t sb, int src) { return ctl_word(p, sb, src >> 3, (src & 7) * 128, src >= (int)lds32(sb + SM_MISC + 8)); }
__device__ __forceinline__ uint32_t* fin1_of(const Params& p, uint32_t sb, int dst) { return ctl_word(p, sb, 8 + (dst >> 3), (dst & 7) * 128, dst / H2); }
__device__ __forceinline__ uint32_t* cred2_of(const Params& p, uint32_t sb, int src) { return ctl_word(p, sb, 16 + (src >> 3), (src & 7) * 128, src / H2); }
__device__ __forceinline__ uint32_t* fin2_of(const Params& p, uint32_t sb, int dst) { return ctl_word(p, sb, 24 + (dst >> 3), (dst & 7) * 128, dst / H3); }
__device__ __forceinline__ uint32_t* rdy_of(const Params& p, uint32_t sb, int word, int part) { return ctl_word(p, sb, 28, word, part); }
__device__ __forceinline__ uint32_t q2_off(uint32_t sb, int blk, int dst) {
    return (N2 + dst) * WIN + gran_off(sb, N2 + dst, (blk >> 1) * 4 + (blk & 1), dst / H3);
}
template <bool IS1>
__device__ __forceinline__ void clear_queues(const Params& p, uint32_t sb, int id, int lane) {
    constexpr int NA = (N1 + 1) / 2, NG = NA + (N1 + 3) / 4, N = IS1 ? NG * N2 : NI * 2;
    if (IS1) {
#pragma unroll 1
        for (int k = 0; k < 8; k++) sts128(sb + SM_ZERO + (k * 32 + lane) * 16, make_uint4(0, 0, 0, 0));
        if (lane == 0) spin_ge(rdy_of(p, sb, 320, lds32(sb + SM_MISC + 20)), NTAIL);
    }
    __syncwarp();
    fence_async_smem();
    for (int k = IS1 ? id + (lane < CFG_CLN ? lane : N) * N1 : lane; k < N; k += IS1 ? CFG_CLN * N1 : 32) {
        if (IS1 && k >= CFG_CLN * N1) __nanosleep(CFG_CLS);
        const int wi = k / NG, g = k - wi * NG;
        const uint32_t off = IS1 ? wi * WIN + gran_off(sb, wi, g < NA ? g : 32 + g - NA, wi & 1) : q2_off(sb, k >> 1, id) + (k & 1) * 16384;
        bulk_store(p.ring + off, sb + SM_ZERO, 4096);
    }
    asm volatile("cp.async.bulk.commit_group;" ::: "memory");
    asm volatile("cp.async.bulk.wait_group 0;" ::: "memory");
    TR(21, IS1 && lane == 0);
    if (!IS1) {
        fence_async_all();
        __syncwarp();
        fence_gpu();
        if (lane < NI) red_rlx(rdy_of(p, sb, id / H3 * H2 + lane, id / H3), 1u);
    }
    __syncwarp();
}

struct In8 { uint4 a[2], o[2]; uint2 g[2]; };
__device__ __forceinline__ void p1_load(const Params& p, In8& r, int i4) {
#pragma unroll
    for (int u = 0; u < 2; u++) {
        [[maybe_unused]] uint32_t x, y;
        asm volatile("tex.1d.v4.u32.s32 {%0,%1,%2,%3}, [%4, {%5}];" : "=r"(r.a[u].x), "=r"(r.a[u].y), "=r"(r.a[u].z), "=r"(r.a[u].w) : "l"(p.t_in), "r"(i4 + u * 32));
        asm volatile("tex.1d.v4.u32.s32 {%0,%1,%2,%3}, [%4, {%5}];" : "=r"(r.o[u].x), "=r"(r.o[u].y), "=r"(r.o[u].z), "=r"(r.o[u].w) : "l"(p.t_out), "r"(i4 + u * 32));
        asm volatile("tex.1d.v4.u32.s32 {%0,%1,%2,%3}, [%4, {%5}];" : "=r"(r.g[u].x), "=r"(r.g[u].y), "=r"(x), "=r"(y) : "l"(p.t_ang), "r"(i4 + u * 32));
    }
}
__device__ __forceinline__ uint32_t imad(uint32_t a, uint32_t b, uint32_t c) {
    uint32_t r;
    asm("mad.lo.u32 %0, %1, %2, %3;" : "=r"(r) : "r"(a), "r"(b), "r"(c));
    return r;
}
__device__ __forceinline__ unsigned char* ring_ptr(const Params& p, uint32_t lo) {
    uint64_t r;
    asm("mov.b64 %0, {%1, %2};" : "=l"(r) : "r"(lo), "r"(p.ring_hi));
    return (unsigned char*)r;
}
__device__ __forceinline__ uint32_t keep32(uint32_t x) {
    return __shfl_sync(0xffffffffu, x, threadIdx.x & 31);
}
__device__ __forceinline__ uint32_t opaque32(uint32_t x) {
    asm volatile("" : "+r"(x));
    return x;
}
template <typename T> __device__ __forceinline__ T* opaque(T* p) {
    asm volatile("" : "+l"(p));
    return p;
}
template <int LUT> __device__ __forceinline__ uint32_t lop3(uint32_t a, uint32_t b, uint32_t c) {
    uint32_t r;
    asm("lop3.b32 %0, %1, %2, %3, %4;" : "=r"(r) : "r"(a), "r"(b), "r"(c), "n"(LUT));
    return r;
}
__device__ __forceinline__ uint32_t dp4(uint32_t a, uint32_t b, uint32_t c) {
    uint32_t r;
    asm("dp4a.u32.u32 %0, %1, %2, %3;" : "=r"(r) : "r"(a), "r"(b), "r"(c));
    return r;
}
__device__ __forceinline__ uint32_t dp2(uint32_t a, uint32_t b, uint32_t c) {
    uint32_t r;
    asm("dp2a.lo.u32.u32 %0, %1, %2, %3;" : "=r"(r) : "r"(a), "r"(b), "r"(c));
    return r;
}
__device__ __forceinline__ void p1_put(uint32_t sb, uint32_t wa, uint32_t wb, uint32_t old, bool on) {
    asm volatile("{.reg .pred q; setp.ne.u32 q, %3, 0; @q st.shared.v2.u32 [%0], {%1,%2};}"
                 ::"r"(sb + A_ST + prmt(old, wb, 0xf762)), "r"(wa), "r"(prmt(wb, old, 0x7210)), "r"((uint32_t)on) : "memory");
}
__device__ __forceinline__ void p1_slow_tile(const Params& p, uint32_t sb, int i4) {
    const float f = __bfloat162float(p.freq[0]);
#pragma unroll 1
    for (int u = 0; u < 8; u++) {
        const int k4 = i4 + (u >> 2) * 32;
        if (k4 < p.n4) {
            const size_t t = (size_t)k4 * 4 + (u & 3);
            const float x = __bfloat162float(__float2bfloat16(f * __bfloat162float(p.angle[t])));
            slow_add(p.m, sb, p.idx_in[t], p.idx_out[t], __bfloat162float(__float2bfloat16(cosf(x))));
        }
    }
}
__device__ __forceinline__ void role_p1(const Params& p, uint32_t sb, int id, int w, int lane) {
    lane = keep32(lane);
    const uint32_t f2 = (uint32_t)__bfloat16_as_ushort(p.freq[0]) * 0x10001u;
    constexpr int TG = CFG_TG, NTK = P1W;
    static_assert(NTK <= 16, "tickets");
    const int tc = (w + id) % NTK, first = (N1 * P1W + tc) * (TG * 64);
    uint32_t* const tickets = opaque(ctl_word(p, sb, 29 + tc / 8, tc % 8 * 128 + lane, tc & 1));
    auto draw = [&]() {
        uint32_t t = 0;
        asm volatile("{.reg .pred q; setp.eq.u32 q, %2, 0; @q atom.relaxed.gpu.global.add.u32 %0, [%1], 1;}" : "+r"(t) : "l"(tickets), "r"(lane) : "memory");
        return t;
    };
    int i4 = (id * P1W + w) * (TG * 64);
    In8 r;
    ACC_DECL
    uint32_t tk = draw();
    p1_load(p, r, i4 + lane);
    while (i4 < p.n4) {
        const int cur = i4;
        i4 += 64;
        if (i4 % (TG * 64) == 0) {
            i4 = min(__shfl_sync(0xffffffffu, tk, 0), 0x7fffffffu / (NTK * TG * 64) - N1 * P1W / NTK - 2) * (NTK * TG * 64) + first;
            tk = draw();
        }
        uint32_t wa[8], wb[8], x2[4];
        x2[0] = mul_bf2(r.g[0].x, f2); x2[1] = mul_bf2(r.g[0].y, f2);
        x2[2] = mul_bf2(r.g[1].x, f2); x2[3] = mul_bf2(r.g[1].y, f2);
        const uint32_t mx = maxabs_bf2(maxabs_bf2(x2[0], x2[1]), maxabs_bf2(x2[2], x2[3]));
        const bool fast = __all_sync(0xffffffffu, cur + 64 <= p.n4 && ((mx & 0x7fffu) <= 0x4300u) && ((mx & 0x7fff0000u) <= 0x43000000u));
        {
            const uint32_t in[8] = {r.a[0].x, r.a[0].y, r.a[0].z, r.a[0].w, r.a[1].x, r.a[1].y, r.a[1].z, r.a[1].w};
            const uint32_t ou[8] = {r.o[0].x, r.o[0].y, r.o[0].z, r.o[0].w, r.o[1].x, r.o[1].y, r.o[1].z, r.o[1].w};
#pragma unroll
            for (int j = 0; j < 8; j += 2) {
                const uint32_t ch = mul_h2(pack_h2(__cosf(bflo(x2[j >> 1])), __cosf(bfhi(x2[j >> 1]))), 0x24002400u);
#pragma unroll
                for (int k = j; k < j + 2; k++) {
                    const uint32_t blk = __umulhi(in[k], p.magic2), il = imad(blk, p.nrows2, in[k]);
                    wa[k] = k & 1 ? bitsel(ch, il, 0xffff0000u) : imad(ch, 65536u, il);
                    wb[k] = imad(blk, 1u << 21, imad(ou[k] >> 5, 1u - (1u << 21), ou[k] << 16));
                }
            }
        }
        p1_load(p, r, i4 + lane);
        if (fast) {
            uint32_t old[8], any = 0;
#pragma unroll
            for (int j = 0; j < 8; j++) old[j] = atoms_add(dp2(wb[j], 0x400u, 0u) + (sb + A_CNT), 0x80001u);
#pragma unroll
            for (int j = 0; j < 8; j++) any |= old[j];
            if (!__any_sync(0xffffffffu, any & 0xffe0u)) {
#pragma unroll
                for (int j = 0; j < 8; j++) p1_put(sb, wa[j], wb[j], old[j], true);
            } else {
                uint32_t pend = 0;
#pragma unroll
                for (int j = 0; j < 8; j++) { p1_put(sb, wa[j], wb[j], old[j], !(old[j] & 0xffe0u)); if (old[j] & 0xffe0u) pend |= 1u << j; }
                ACC(0, 1)
                for (int guard = 0; __any_sync(0xffffffffu, pend); guard++) {
                    __nanosleep(CFG_BSLEEP);
                    ACC(1, 1)
#pragma unroll
                    for (int j = 0; j < 8; j++) {
                        if (__any_sync(0xffffffffu, pend >> j & 1)) {
                            const uint32_t c = lds32v(sb + A_CNT + (pend >> j & 1 ? wb[j] >> 16 : 0) * 4);
                            const bool go = (pend >> j & 1) && (((old[j] >> 19) - (c >> 19) + c) & 8191u) < 32u;
                            p1_put(sb, wa[j], wb[j], old[j], go);
                            if (go) pend &= ~(1u << j);
                        }
                    }
                    if (guard > GUARD) __trap();
                }
            }
        } else {
            p1_slow_tile(p, sb, cur + lane);
            __syncwarp();
        }
    }
    __syncwarp();
    mbar_arrive_if(sb + SM_DONE, lane == 0);
    ACC_SAVE
}

__device__ __forceinline__ void role_flush(const Params& p, uint32_t sb, int id, int f, int lane) {
    lane = keep32(lane);
    const int half = lane >> 4, o = lane >> 2, q = lane & 3;
    const uint32_t hm = keep32(half ? 0xffff0000u : 0xffffu), lth = keep32(((1u << lane) - 1) & hm);
    const uint32_t list = sb + A_LIST + f * LISTB, cnt = keep32(sb + A_CNT + (f * GPW * 32 + lane) * 4);
    const uint32_t cred = opaque32(sb + SM_CRED + (half * 32 + f * GPW) * 4);
    const uint32_t pa = opaque32(p.ring_lo + (id >> 1) * 8192 + (id & 1) * 2048 + q * 16);
    const uint32_t ph = opaque32(p.ring_lo + (32 + (id >> 2)) * 8192 + (id & 3) * 1024 + q * 8 - 2048);
    const uint32_t sa = q * 16 + (o & 1) * 64;
    uint32_t qo[GPW], hs[GPW], cr[4] = {0, 0, 0, 0};
#pragma unroll
    for (int g = 0; g < GPW; g++) {
        const int blk = f * GPW + g;
        qo[g] = 32u << 25;
        const uint32_t sa = sel_of(sb, 2 * blk + half, id >> 1, half), sh = sel_of(sb, 2 * blk + half, 32 + (id >> 2), half);
        hs[g] = sa << 31 | (2 * sh + 1 - sa) << 22 | 1u << 24 | (lane & 15) << 15 | (blk * 32 + lane) * 2;
    }
    uint4 x[KR] = {}, y[KR] = {};
    uint32_t c[GPW] = {};
    auto scan = [&]() {
#pragma unroll
        for (int g = 0; g < GPW; g++) c[g] = lds32v(cnt + g * 128);
    };
    auto credits = [&]() {
        if (GPW == 4) { const uint4 v = lds128(cred); cr[0] = v.x; cr[1] = v.y; cr[2] = v.z; cr[3] = v.w; }
        else { const uint2 v = lds64v(cred); cr[0] = v.x; cr[1] = v.y; }
    };
    ACC_DECL
    int guard = 0;
    bool idle = false, done = false;
    while (true) {
        uint32_t fr[GPW], rank[GPW], num = 0, left = 0;
        bool ok[GPW];
        if (idle && !done && __all_sync(0xffffffffu, mbar_test(sb + SM_DONE, 0))) {
            done = true;
            TR(17, f == 0 && lane == 0);
#pragma unroll
            for (int g = 0; g < GPW; g++) {
                const uint32_t u = lds32v(cnt + g * 128) & 31u, hd = hs[g] ^ (u & 16u ? imad(hs[g], 1u << 24, 1u) & 0x01000001u : 0u);
#pragma unroll 2
                for (uint32_t j = 0, k; k = (j + lane) & 15u, j < 16; j++)
                    sts64_if(sb + A_ST + ((hd & 0x7ffu) << 7) + k * 8, p.rows2, (lane * 16 + k) | (hd & 0x1000000u), (u & 15u) && k >= (u & 15u));
                reds_add(cnt + g * 128, ((0u - u) & 15u) * 0x80001u);
            }
            __syncwarp();
            scan();
        }
#pragma unroll
        for (int g = 0; g < GPW; g++) {
            const bool isfull = c[g] & 0xfff0u;
            rank[g] = __popc(__ballot_sync(0xffffffffu, isfull) & lth);
            ok[g] = isfull && (int)(rank[g] << 25) < (int)(cr[g] - qo[g] + (63u << 25));
            ACC(2, __popc(__ballot_sync(0xffffffffu, isfull && !ok[g])))
        }
#pragma unroll
        for (int g = 0; g < GPW; g++) {
            const uint32_t m = __ballot_sync(0xffffffffu, ok[g]), n = __popc(m & hm), all = __popc(m), e = num + rank[g] + (half ? all - n : 0u);
            sts32_if(KR == 2 ? list + (e & 48u) * 4 + (e & 7u) * 8 + (e >> 1 & 4u) : imad(e, 4u, list), bitsel(imad(rank[g], 1u << 25, qo[g]), hs[g], 0x7e000000u), ok[g]);
            if (ok[g]) hs[g] ^= imad(hs[g], 1u << 24, 1u) & 0x01000001u;
            fr[g] = ok[g] ? 0u - 16u : 0u;
            left |= c[g] + fr[g];
            qo[g] = imad(n, 1u << 25, qo[g]);
            num += all;
        }
        __syncwarp();
        ACC(0, 1) ACC(1, num)
        if (num) {
            uint32_t la = list + o * (KR == 2 ? 8 : 4);
            int todo = (int)num - o, rest = num;
            do {
                uint32_t d[KR];
                if (KR == 2) { const uint2 v = lds64v(la); d[0] = v.x; d[KR - 1] = v.y; }
                else {
#pragma unroll
                    for (int k = 0; k < KR; k++) d[k] = lds32v(la + 32 * k);
                }
                while (true) {
                    uint32_t bad = 0;
#pragma unroll
                    for (int k = 0; k < KR; k++) {
                        const uint32_t m = d[k] & 0x7ffu;
                        lds128_keep(x[k], imad(m, 128u, sa) + (sb + A_ST), todo > 8 * k);
                        lds128_keep(y[k], imad(m, 128u, sa ^ 64) + (sb + A_ST), todo > 8 * k);
                    }
#pragma unroll
                    for (int k = 0; k < KR; k++)
                        or3_if(bad, lop3<0x7e>(x[k].y, x[k].w, d[k]), lop3<0x7e>(y[k].y, y[k].w, d[k]), todo > 8 * k);
                    if (!__any_sync(0xffffffffu, (int)imad(bad, 128u, 0u) < 0)) break;
                    if (++guard > GUARD) __trap();
                }
#pragma unroll
                for (int k = 0; k < KR; k++) {
                    const uint32_t mi = d[k] & 0x7e0u, dm = d[k] & 0xbec00000u;
                    x[k].x = bitsel(d[k], x[k].x, 0x40078000u);
                    x[k].y = prmt(x[k].y, x[k].w, 0x5410);
                    x[k].w = prmt(y[k].y, y[k].w, 0x5410);
                    y[k].x = bitsel(d[k], y[k].x, 0x40000000u);
                    y[k].y = y[k].z;
                    stg_q128(ring_ptr(p, dp4(dm, 0x20000000u, imad(mi, WIN / 32, pa))), x[k].x, x[k].y, x[k].z, x[k].w, X_ST1 todo > 8 * k);
                    stg_q64(ring_ptr(p, dp4(dm, 0x10200000u, imad(mi, WIN / 32, ph))), y[k].x, y[k].y, X_ST1 todo > 8 * k);
                }
                la += 32 * KR;
                todo -= 8 * KR;
                rest -= 8 * KR;
            } while (rest > 0);
#pragma unroll
            for (int g = 0; g < GPW; g++) c[g] = atoms_add(cnt + g * 128, fr[g]) + fr[g];
            credits();
            idle = num <= CFG_TH;
            if (done && !__any_sync(0xffffffffu, left & 0xffffu)) break;
            if (idle) { __nanosleep(CFG_TS); scan(); credits(); }
        } else {
            if (done && !__any_sync(0xffffffffu, left & 0xffffu)) break;
            idle = true;
            __nanosleep(CFG_FSLEEP);
            scan();
            credits();
            if (++guard > GUARD) __trap();
        }
    }
#pragma unroll
    for (int g = 0; g < GPW; g++) st_rlx_if(fin1_of(p, sb, half * H2 + f * GPW + g) + id, qo[g] - (32u << 25) + 1u, (lane & 15) == 0 && f * GPW + g < NI);
    mbar_arrive_if(sb + SM_DONE2, lane == 0);
    TR(18, f == 0 && lane == 0);
    ACC_SAVE
}
__device__ __forceinline__ void role_credit1(const Params& p, uint32_t sb, int id, int lane) {
    const uint32_t* const cred = cred1_of(p, sb, id) + lane * 2;
    for (int guard = 0; !__all_sync(0xffffffffu, mbar_test(sb + SM_DONE2, 0)); guard++) {
        const uint2 v = ldg_q64(cred);
        sts64(sb + SM_CRED + lane * 8, v.x, v.y);
        __nanosleep(CFG_C1SLEEP);
        if (guard > GUARD) __trap();
    }
}

__device__ __forceinline__ float h2f(uint32_t h) {
    float f;
    asm("{.reg .b16 t; cvt.u16.u32 t, %1; cvt.f32.f16 %0, t;}" : "=f"(f) : "r"(h));
    return f;
}
__device__ __forceinline__ void p2_slow(const Params& p, uint32_t sb, const uint32_t* tmp, int row0, uint32_t dst) {
#pragma unroll 1
    for (int j = 0; j < 4; j++)
        if (tmp[8 + j] & 0x40u) slow_add(p.m, sb, row0 + (tmp[j] & 0x7fffu), (tmp[4 + j] & 0x7fffu) * 32 + dst, h2f(tmp[j] >> 16) * 64.0f);
}
__device__ __forceinline__ uint32_t mul_h2_hi(uint32_t a, uint32_t b) {
    uint32_t r;
    asm("{.reg .b16 l, h; .reg .b32 t; mov.b32 {l, h}, %2; mov.b32 t, {h, h}; mul.rn.f16x2 %0, %1, t;}" : "=r"(r) : "r"(a), "r"(b));
    return r;
}
template <bool CHECK>
__device__ __forceinline__ void role_p2(const Params& p, uint32_t sb, int id, int w, int lane) {
    lane = keep32(lane);
    const int part = id / H2, blk = id - part * H2, row0 = blk * p.rows2;
    const int o = lane >> 2, q = lane & 3;
    uint32_t* const cbase = (uint32_t*)(p.ring + (CWIN + lds32(sb + SM_MISC + 16)) * WIN);
    const uint32_t cred = opaque32((uint32_t)(uintptr_t)(cbase + part * 32 + blk));
    const uint32_t pa = opaque32(p.ring_lo + (2 * blk + part) * WIN + q * 16), ph = opaque32(pa - q * 8);
    const uint32_t po = opaque32(p.ring_lo + (q2_off(sb, blk, part * H3) & ~4096u) + q * 16 + (o & 1) * 64);
    const uint32_t sel = __ballot_sync(0xffffffffu, q2_off(sb, blk, part * H3 + (lane & 15)) & 4096u) << 12;
    const uint32_t* const fins = fin1_of(p, sb, id);
    uint32_t st[QPW] = {}, sq[QPW] = {};
    uint4 qa[NBT];
    uint2 qh[NBT];
    auto load = [&](int k) {
        qa[k] = ldg_q128(ring_ptr(p, pa + (bitsel(sq[k], st[k] >> 19, 0x7f800u) & 0x7ffc0u)));
        qh[k] = ldg_q64(ring_ptr(p, ph + (bitsel(sq[k] >> 9, st[k] >> 20, 0x7fc00u) & 0x7ffe0u)));
    };
#pragma unroll
    for (int k = 0; k < QPW; k++) {
        const int src = w * QPW + k;
        st[k] = o << 25 | (src < N1 ? 1u : 5u);
        sq[k] = src < N1 ? q1h_off(sb, src, blk, part) << 9 | q1a_off(sb, src, blk, part) | (uint32_t)(cred1_of(p, sb, src) - cbase) / 8 : 0x7e000u * 513u;
    }
#pragma unroll
    for (int k = 0; k < NBT; k++) load(k);
    ACC_DECL
    int guard = 0;
    uint32_t streak = 0;
    while (true) {
        uint32_t nn[NBT], xx[NBT][4], hh[NBT][2], dd[NBT], any = 0;
        bool last = false;
#pragma unroll
        for (int k = 0; k < NBT; k++) {
            const uint4 a = qa[k];
            const uint2 h = qh[k];
            uint32_t n = 8;
            const uint32_t miss = __ballot_sync(0xffffffffu, (int)imad((a.x ^ st[k]) & (h.x ^ st[k]), 2u, 0u) >= 0);
            if (miss) {
                n = (__ffs(miss) - 1) >> 2;
                if (!__any_sync(0xffffffffu, st[k] & 8u)) { if (streak < CFG_PSTREAK) n &= CFG_PMASK; }
                else if (!__any_sync(0xffffffffu, ((st[k] >> 6) + ((n - o) << 19) ^ st[k]) & 0x1f80000u)) { st[k] |= 4u; last = true; }
            }
            ACC(1, n == 0) ACC(2, n != 0) ACC(3, n)
            st[k] = imad(n, 1u << 25, st[k]);
            st_rlx_if((uint32_t*)ring_ptr(p, imad(sq[k] & 0x7f0u, 32u, cred)), st[k], X_CR1 lane == 0 && n);
            xx[k][0] = bitsel(a.x, 0x00040000u, 0xbff87fffu); xx[k][1] = a.z; xx[k][2] = h.x & 0xbfffffffu; xx[k][3] = h.y;
            hh[k][0] = a.y; hh[k][1] = a.w; dd[k] = a.x >> 13 & 0x3cu; nn[k] = n;
            any |= n;
        }
        if (!any) {
#pragma unroll
            for (int k = 0; k < QPW; k++) {
                const uint32_t fin = ld_rlx(fins + ((sq[k] >> 12 & 62u) | (sq[k] >> 11 & 1u)));
                if (fin & 1u) st[k] |= (fin >> 6 & 0x1f80000u) | ((fin ^ (st[k] - (o << 25))) >> 25 ? 8u : 12u);
            }
            last = true;
            if (++guard > GUARD) __trap();
            streak++;
        } else streak = 0;
        if (last) {
            uint32_t all = 4u;
#pragma unroll
            for (int k = 0; k < QPW; k++) all &= st[k];
            last = __all_sync(0xffffffffu, all);
        }
        {
            uint32_t t[QPW], u[QPW];
#pragma unroll
            for (int k = 0; k < QPW; k++) { t[k] = st[(k + NBT) % QPW]; u[k] = sq[(k + NBT) % QPW]; }
#pragma unroll
            for (int k = 0; k < QPW; k++) { st[k] = t[k]; sq[k] = u[k]; }
        }
#pragma unroll
        for (int k = 0; k < NBT; k++) load(k);
#pragma unroll
      for (int k = 0; k < NBT; k++) {
        if (nn[k]) {
            const uint32_t* const x = xx[k];
            const uint32_t h0 = hh[k][0], h1 = hh[k][1], d4 = dd[k];
            const bool v = o < nn[k];
            uint32_t old = 0, ta[4], tb[4], w0[4], w1[4];
            atoms_add_keep(old, sb + SM_CNT2 + d4, 0x10001u, q == 0 && v);
#pragma unroll
            for (int j = 0; j < 4; j++) {
                ta[j] = lds32nv(dp2(x[j], 4u, 0u) + (sb + B_TA));
                tb[j] = lds16nv(dp2(x[j], 2u, 0u) + (sb + B_TB));
            }
            old = __shfl_sync(0xffffffffu, old, lane & 28);
            const uint32_t tag = old << 8 & 0x40000000u;
#pragma unroll
            for (int j = 0; j < 4; j++) {
                const uint32_t z = prmt(j & 2 ? h1 : h0, 0, j & 1 ? 0x4342 : 0x4140);
                const uint32_t t23 = prmt((ta[j] & 0x60076007u) * 2050u, tb[j], 0x5341) & 0xfffcffffu;
                w0[j] = (imad(z, 128u, j & 1 ? 0u : tag) & 0x78007800u) | mul_h2_hi(ta[j] & 0x9ff89ff8u, x[j]);
                w1[j] = (imad(z, 2048u, 0u) & 0x78007800u) | mul_h2_hi(t23, x[j]);
            }
            if (CHECK && v && ((tb[0] | tb[1] | tb[2] | tb[3]) & 0x40u)) {
                uint32_t tmp[12];
#pragma unroll
                for (int j = 0; j < 4; j++) {
                    tmp[j] = x[j]; tmp[4 + j] = (j & 2 ? h1 : h0) >> (j & 1 ? 16 : 0); tmp[8 + j] = tb[j];
                    if (tb[j] & 0x40u) { w0[j] &= 0x78007800u; w1[j] &= 0x78007800u; }
                }
                p2_slow(p, sb, tmp, row0, part * H3 + d4 / 4);
            }
            const uint32_t off = (bitsel(old >> 9, old >> 7, 0x0f80u) & 0x4f80u) + imad(d4, WIN / 4, (sel >> (d4 / 4) & 4096u) + po);
            bool wait = old & (0x10000u - NQ2);
            if (!__any_sync(0xffffffffu, wait)) {
                stg_q128(ring_ptr(p, off), w0[0], w1[0], w0[1], w1[1], X_ST2 v);
                stg_q128(ring_ptr(p, off ^ 64u), w0[2], w1[2], w0[3], w1[3], X_ST2 v);
            } else {
                bool pend = v;
                ACC(0, 1)
                for (int g2 = 0;; g2++) {
                    stg_q128(ring_ptr(p, off), w0[0], w1[0], w0[1], w1[1], pend && !wait);
                    stg_q128(ring_ptr(p, off ^ 64u), w0[2], w1[2], w0[3], w1[3], pend && !wait);
                    pend = wait;
                    if (!__any_sync(0xffffffffu, pend)) break;
                    __nanosleep(CFG_BSLEEP);
                    const uint32_t c = lds32v(sb + SM_CNT2 + d4);
                    wait = pend && (((old >> 16) - (c >> 16) + c) & 0xffffu) >= NQ2;
                    if (g2 > GUARD) __trap();
                }
            }
        }
      }
        if (last) break;
    }
    TR(17, w == 0 && lane == 0);
    __syncwarp();
    uint32_t rank = 0;
    if (lane == 0) { __threadfence_block(); rank = atoms_add(sb + SM_FIN, 1u); __threadfence_block(); }
    if (__shfl_sync(0xffffffffu, rank, 0) == P2W - 1 && lane < 16)
        st_rlx(fin2_of(p, sb, part * H3 + lane) + blk, FIN | (((lds32v(sb + SM_CNT2 + lane * 4) >> 16) - NQ2) & 0xffffu));
    __syncwarp();
    mbar_arrive_if(sb + SM_DONE, lane == 0);
    ACC_SAVE
}
__device__ __forceinline__ void role_credit(const Params& p, uint32_t sb, int id, int lane) {
    const uint32_t* const cred = cred2_of(p, sb, id) + (lane & 15);
    uint32_t last = 0;
    for (int guard = 0;; guard++) {
        if (__all_sync(0xffffffffu, mbar_test(sb + SM_DONE, 0))) break;
        const uint32_t c = ld_rlx(cred);
        if (lane < 16 && c != last) reds_add(sb + SM_CNT2 + lane * 4, 0u - ((c - last) & 0xffffu));
        last = c;
        __nanosleep(CFG_CSLEEP);
        if (guard > GUARD) __trap();
    }
}

__device__ __forceinline__ void p3_wrap(uint32_t sb, int id, const uint32_t* tmp) {
    const Scale sc = get_scale(sb);
#pragma unroll 1
    for (int j = 0; j < 8; j++) {
        const uint32_t old = tmp[4 + j], v = tmp[12 + j], nw = old + v, t = (old ^ nw) & (v ^ nw);
        if (t & 0x80008000u) {
            const float k = (t & 0x8000u) ? ((v & 0x8000u) ? -1.0f : 1.0f) : 0.0f;
            const float q = (t & 0x80000000u) ? ((int)v < 0 ? -65536.0f : 65536.0f) : 0.0f;
            const uint32_t e0 = (j & 1) ? sc.eb[2] : sc.eb[0], e1 = (j & 1) ? sc.eb[3] : sc.eb[1];
            const float lo = k * 65536.0f * __uint_as_float((e0 - 10) << 23), hi = (q - k) * __uint_as_float((e1 - 10) << 23);
            if (j & 1) sg_add(tmp[j >> 1] * 32 + id, 0.f, 0.f, lo, hi);
            else sg_add(tmp[j >> 1] * 32 + id, lo, hi, 0.f, 0.f);
        }
    }
}
__device__ __forceinline__ uint32_t p3_val(uint32_t w) {
    const uint32_t mk = prmt(w, 0, 0xBB99);
    return ((w & 0x07ff07ffu) ^ mk) - mk;
}
__device__ __forceinline__ void role_p3(const Params& p, uint32_t sb, int id, int w, int lane) {
    lane = keep32(lane);
    uint32_t* const cred = opaque(cred2_of(p, sb, id / H3 * H2 + w) + id % H3);
    const uint32_t pq = opaque32(p.ring_lo + q2_off(sb, w, id) + lane * 16);
    auto off = [&](uint32_t n) { return (n & 1u) << 11 | (n & 2u) << 13; };
    const uint32_t pp = opaque32(pq - lane * 16 + 112);
    auto tag_of = [&](uint32_t n) { return ~n << 28; };
    uint32_t n = 0, fin = 0, pr = 0, pk = 0;
    uint4 v[4] = {};
    bool have = false, last = false;
    ACC_DECL
    int guard = 0;
    while (true) {
        const uint32_t ex = tag_of(n);
        const bool ok = have && !__any_sync(0xffffffffu, ((v[0].x ^ ex) | (v[1].x ^ ex) | (v[2].x ^ ex) | (v[3].x ^ ex)) & 0x40000000u);
        if (ok) n++;
        const bool ready = (ok || !have) && __all_sync(0xffffffffu, !((pr ^ tag_of(n)) & 0x40000000u));
        st_rlx_if(cred, n * 16, X_CR2 lane == 0 && ok);
        if (!ok && !ready && __all_sync(0xffffffffu, fin & FIN)) {
            const uint32_t left = __shfl_sync(0xffffffffu, (fin - n * 16) & 0xffffu, 0);
            if (left - 1u > 0x8000u) break;
            if (left < 16u) {
#pragma unroll
                for (int u = 0; u < 4; u++) {
                    v[u] = make_uint4(ex & 0x40000000u, 0, 0, 0);
                    ldq128_keep(v[u], ring_ptr(p, pq + off(n)) + u * 512, u * 4 + (lane >> 3) < left);
                }
                have = last = !__any_sync(0xffffffffu, ((v[0].x ^ ex) | (v[1].x ^ ex) | (v[2].x ^ ex) | (v[3].x ^ ex)) & 0x40000000u);
                pr = ~tag_of(n + have);
                if (++guard > GUARD) __trap();
                continue;
            }
        }
        uint32_t row[8], val[16];
#pragma unroll
        for (int u = 0; u < 4; u++) {
            const uint4 x = v[u];
            row[2 * u] = prmt(bitsel(x.x << 1, x.y >> 3, 0x7000f000u), 0, 0x4431);
            row[2 * u + 1] = prmt(bitsel(x.z << 1, x.w >> 3, 0x7000f000u), 0, 0x4431);
            val[4 * u] = p3_val(x.x); val[4 * u + 1] = p3_val(x.y);
            val[4 * u + 2] = p3_val(x.z); val[4 * u + 3] = p3_val(x.w);
        }
#pragma unroll
        for (int u = 0; u < 4; u++) ldq128_keep(v[u], ring_ptr(p, pq + off(n)) + u * 512, ready);
        pk = ready ? CFG_PK1 * 128 : ok ? CFG_PK2 * 128 : have ? 15 * 128 : max(pk, CFG_PK3 * 128u);
        pr = ld_rlx((const uint32_t*)ring_ptr(p, pp + off(n + ready) + pk));
        ACC(2, have && !ok)
        have = ready;
        if (!ok) {
            ACC(1, 1)
            fin = ld_rlx(fin2_of(p, sb, id) + w);
            if (++guard > GUARD) __trap();
        } else {
#pragma unroll
            for (int u = 0; u < 4; u += 2) {
                uint32_t old[8], chk = 0;
#pragma unroll
                for (int j = 0; j < 4; j++) {
                    old[2 * j] = atoms_add(sb + C_S + row[2 * u + j] * 4, val[4 * u + 2 * j]);
                    old[2 * j + 1] = atoms_add(sb + C_S + ROWS3_MAX * 4 + row[2 * u + j] * 4, val[4 * u + 2 * j + 1]);
                }
#pragma unroll
                for (int j = 0; j < 8; j++) {
                    const uint32_t nw = old[j] + val[4 * u + j];
                    chk |= (old[j] ^ nw) & (val[4 * u + j] ^ nw);
                }
                if (chk & 0x80008000u) {
                    uint32_t tmp[20];
#pragma unroll
                    for (int j = 0; j < 8; j++) { tmp[j >> 1] = row[2 * u + (j >> 1)]; tmp[4 + j] = old[j]; tmp[12 + j] = val[4 * u + j]; }
                    p3_wrap(sb, id, tmp);
                }
            }
            __syncwarp();
            if (last) break;
        }
    }
    ACC_SAVE
}

__device__ __forceinline__ void row_gates(const float* sw, const uint32_t* c2, uint32_t dbits, float4& gs, float4& gr) {
    const uint32_t d2 = dbits * 0x10001u;
    gs = gr = make_float4(0.f, 0.f, 0.f, 0.f);
#pragma unroll
    for (int r2 = 0; r2 < 4; r2++) {
        uint32_t df = sub_bf2(d2, c2[r2]);
        uint32_t ar = mul_bf2(mul_bf2(df, df), 0xC120C120u);
        uint32_t rb = pack_bf2(__expf(bflo(ar)), __expf(bfhi(ar)));
        const float r0 = bflo(rb), r1 = bfhi(rb);
        const float4 s0 = *(const float4*)(sw + r2 * 8), s1 = *(const float4*)(sw + r2 * 8 + 4);
        const float4 q0 = *(const float4*)(sw + 32 + r2 * 8), q1 = *(const float4*)(sw + 32 + r2 * 8 + 4);
        gs.x += r0 * s0.x + r1 * s1.x; gs.y += r0 * s0.y + r1 * s1.y;
        gs.z += r0 * s0.z + r1 * s1.z; gs.w += r0 * s0.w + r1 * s1.w;
        gr.x += r0 * q0.x + r1 * q1.x; gr.y += r0 * q0.y + r1 * q1.y;
        gr.z += r0 * q0.z + r1 * q1.z; gr.w += r0 * q0.w + r1 * q1.w;
    }
}
__device__ __forceinline__ uint2 finish_row(const float* wu, const float4& gs, const float4& gr, const float S[4], uint2 mrow) {
    const float a[4] = {S[0] * gs.x, S[1] * gs.y, S[2] * gs.z, S[3] * gs.w};
    float u[4] = {0, 0, 0, 0};
#pragma unroll
    for (int k = 0; k < 4; k++) {
        u[0] += a[k] * wu[4 * k]; u[1] += a[k] * wu[4 * k + 1]; u[2] += a[k] * wu[4 * k + 2]; u[3] += a[k] * wu[4 * k + 3];
    }
    return make_uint2(pack_bf2(bflo(mrow.x) + u[0] * gr.x, bfhi(mrow.x) + u[1] * gr.y),
                      pack_bf2(bflo(mrow.y) + u[2] * gr.z, bfhi(mrow.y) + u[3] * gr.w));
}
__device__ __forceinline__ void load_tail_weights(const Params& p, float* sw, int tid) {
    if (tid < 32) sw[tid] = __bfloat162float(p.w_sbf[tid]);
    else if (tid < 64) sw[tid] = __bfloat162float(p.w_rbf[tid - 32]);
    else if (tid < 80) sw[tid] = __bfloat162float(p.w_up[tid - 64]);
    else if (tid < 96) sw[tid] = __bfloat162float(p.w_down[tid - 80]);
}
__device__ __forceinline__ float exp_ftz(float x) {
    float r;
    asm("ex2.approx.ftz.f32 %0, %1;" : "=f"(r) : "f"(x * 1.4426950408889634f));
    return r;
}
__device__ __forceinline__ void tail_rows(const Params& p, int tidx, int w, int lane) {
    constexpr uint32_t sb = SB;
    if (w == NW - 1 && lane < 2) {
        fence_gpu();
        red_rlx(rdy_of(p, sb, 320, lane), 1u);
    }
    if (w >= NPC * WPP) return;
    const int pc = w / WPP, r0 = pc * RPC + (tidx * WPP + w - pc * WPP) * 8, e0 = r0 * 32;
    const uint32_t G = sb + T_G + w * TWB, M = G + 4096, D = M + 2048;
    cp16z(D + lane * 16, p.dist + e0 + lane * 8, min(max(p.E - e0 - lane * 8, 0), 8) * 2);
#pragma unroll
    for (int k = 0; k < 4; k++) cp16(M + (k * 32 + lane) * 16, p.m + e0 + (k * 32 + lane) * 2, e0 + (k * 32 + lane) * 2 < p.E);
    cp_commit();
    const Scale sc = get_scale(sb);
    const float lsb[4] = {__uint_as_float((sc.eb[0] - 10) << 23), __uint_as_float((sc.eb[1] - 10) << 23),
                          __uint_as_float((sc.eb[2] - 10) << 23), __uint_as_float((sc.eb[3] - 10) << 23)};
    {
        const int g = lane >> 2, t = lane & 3;
        const uint32_t c2 = ((const uint32_t*)p.centers)[t];
        const unsigned short* wg = (const unsigned short*)(g < 4 ? p.w_sbf : p.w_rbf) + t * 8 + (g & 3);
        const uint32_t b = wg[0] | (uint32_t)wg[4] << 16;
        cp_wait<0>();
        __syncwarp();
        TR(19, w == 0 && lane == 0 && b + c2 != 0x12345);
#pragma unroll 2
        for (int k = 0; k < 16; k++) {
            const uint32_t dv = lds32(D + (k * 8 + g) * 4);
            uint32_t a[2];
#pragma unroll
            for (int h = 0; h < 2; h++) {
                const uint32_t df = sub_bf2(prmt(dv, 0, h ? 0x3232 : 0x1010), c2);
                const uint32_t ar = mul_bf2(mul_bf2(df, df), 0xC120C120u);
                a[h] = pack_bf2(exp_ftz(bflo(ar)), exp_ftz(bfhi(ar)));
            }
            float d[4];
            asm("mma.sync.aligned.m16n8k8.row.col.f32.bf16.bf16.f32 {%0,%1,%2,%3}, {%4,%5}, {%6}, {%7,%7,%7,%7};"
                : "=f"(d[0]), "=f"(d[1]), "=f"(d[2]), "=f"(d[3]) : "r"(a[0]), "r"(a[1]), "r"(b), "f"(0.f));
            const uint32_t at = G + (k * 16 + g * 2) * 16 + t * 4;
            sts32(at, pack_bf2(d[0], d[1]));
            sts32(at + 16, pack_bf2(d[2], d[3]));
        }
    }
    __syncwarp();
    TR(2, w == 0 && lane == 0);
    float wu[16];
#pragma unroll
    for (int k = 0; k < 4; k++) *(uint4*)(wu + 4 * k) = lds128(sb + SM_W + 256 + 16 * k);
    uint32_t dirty = 0;
#pragma unroll 1
    for (int pass = CFG_DRY ? 0 : 1; pass < 2; pass++) {
        if (pass) {
            if (w == pc * WPP && lane < 2) spin_ge(rdy_of(p, sb, lane ? 320 : 160 + 32 * pc, lds32(sb + SM_MISC + 20)), lane ? NTAIL : N3);
            __syncwarp();
            bar_sync(1 + pc, WPP * 32);
            TR(3, w == 0 && lane == 0);
            TR(10, w == NPC * WPP - 1 && lane == 0);
            if (r0 >= (int)p.rows3) return;
        }
        uint4 sv[4] = {};
#pragma unroll
        for (int u = 0; u < 4; u++) ldq128_keep(sv[u], &g_S[0][u * 16 + (lane >> 1)][r0 + (lane & 1) * 4], pass);
        if (pass && lane < 8 && (r0 + lane) * 32 < p.E && (dirty = ld_rlx(g_dirty + r0 + lane))) st_rlx(g_dirty + r0 + lane, 0u);
        dirty = __ballot_sync(0xffffffffu, dirty != 0);
        uint32_t xs[8] = {sv[0].x, sv[0].y, sv[0].z, sv[0].w, sv[1].x, sv[1].y, sv[1].z, sv[1].w};
        uint32_t ys[8] = {sv[2].x, sv[2].y, sv[2].z, sv[2].w, sv[3].x, sv[3].y, sv[3].z, sv[3].w};
        asm volatile("" : "+r"(lane));
        auto finish = [&](int k, uint32_t x, uint32_t y, bool extra) {
            const int i = (lane & 1) * 128 + (lane >> 1) + (k & 3) * 32 + (k >> 2) * 16, e = e0 + i;
            float S[4];
            const uint32_t tx = x + 0x80008000u, ty = y + 0x80008000u;
            S[0] = (__uint_as_float(prmt(tx, 0x4b000000u, 0x7610)) - 8421376.0f) * lsb[0];
            S[1] = (__uint_as_float(prmt(tx, 0x4b000000u, 0x7632)) - 8421376.0f) * lsb[1];
            S[2] = (__uint_as_float(prmt(ty, 0x4b000000u, 0x7610)) - 8421376.0f) * lsb[2];
            S[3] = (__uint_as_float(prmt(ty, 0x4b000000u, 0x7632)) - 8421376.0f) * lsb[3];
            if (extra && e < p.E) {
                const float4 g = __ldcg(g_Sg + e);
                S[0] += g.x; S[1] += g.y; S[2] += g.z; S[3] += g.w;
                __stcg(g_Sg + e, make_float4(0.f, 0.f, 0.f, 0.f));
            }
            const uint4 g = lds128(G + i * 16);
            const uint2 o = finish_row(wu, make_float4(bflo(g.x), bfhi(g.x), bflo(g.y), bfhi(g.y)), make_float4(bflo(g.z), bfhi(g.z), bflo(g.w), bfhi(g.w)), S,
                                       lds64v(M + i * 8));
            asm volatile("{.reg .pred q; setp.ne.u32 q, %3, 0; @q st.global.v2.u32 [%0], {%1,%2};}"
                         ::"l"(p.out + e), "r"(o.x), "r"(o.y), "r"((uint32_t)(pass && e < p.E)));
        };
        if (!dirty) {
#pragma unroll
            for (int k = 0; k < 8; k++) finish(k, xs[k], ys[k], false);
        } else {
#pragma unroll 1
            for (int k = 0; k < 8; k++) {
                finish(k, xs[0], ys[0], dirty >> ((lane & 1) * 4 + (k & 3)) & 1);
#pragma unroll
                for (int j = 0; j < 7; j++) { xs[j] = xs[j + 1]; ys[j] = ys[j + 1]; }
            }
        }
    }
    TR(9, w == 0 && lane == 0);
    TR(11, w == NPC * WPP - 1 && lane == 0);
}

#define CFG_MAP1 1
__global__ void __launch_bounds__(NT, 1) k_main(const __grid_constant__ Params p) {
    extern __shared__ __align__(1024) unsigned char smem[];
    constexpr uint32_t sb = SB;
    if ((uint32_t)__cvta_generic_to_shared(smem) != SB) __trap();
    const int tid = threadIdx.x, w = __shfl_sync(0xffffffffu, tid >> 5, 0), lane = tid & 31;
    if (w < NPROBE) probe(p, sb, w, lane);
    else {
        if (tid == NT - 1) sts32(sb + SM_MISC + 16, ld_rlx(&g_epoch) & 1);
        if (tid >= NT - 32 && lane < 12) sts32(sb + SM_FIN + lane * 4, 0u);
        load_tail_weights(p, (float*)(smem + SM_W), tid - NPROBE * 32);
        const int k = blockIdx.x % (NCTA / 2) * 14 + lane;
        if (w == NW - 2 && lane < 14 && k < NT - 32) asm volatile("prefetch.global.L2 [%0];" ::"l"((const uint4*)p.m + k * (p.E / 2 / (NT - 32))));
    }
    cta_sync();
    if (w) {
        const uint4 in = __ldg((const uint4*)p.m + (tid - 32) * (p.E / 2 / (NT - 32)));
        const Mat4 wd = load_mat4(p.w_down, lane);
        for (int i = SM_DATA / 16 + tid - 32; i < ZEND / 16; i += NT - 32) ((uint4*)smem)[i] = make_uint4(0, 0, 0, 0);
        if (tid - 32 < 256) ((uint4*)(smem + SM_ZERO))[tid - 32] = make_uint4(0, 0, 0, 0);
        if (tid < 48) sts32(sb + SM_CNT2 + (tid - 32) * 4, NQ2 << 16);
        __syncwarp();
        if (CFG_PFD && tid == NT - 1) {
            __nanosleep(CFG_PFD);
            const uint32_t n = (p.E / 2 + NCTA - 1) / NCTA, o = blockIdx.x * n;
            if (o < (uint32_t)p.E / 2) asm volatile("cp.async.bulk.prefetch.L2.global [%0], %1;" ::"l"((const uint4*)p.m + o), "r"(min(n, p.E / 2 - o) * 16) : "memory");
        }
        __syncwarp();
        md_stats(in, wd, lane);
    } else assign_role(p, sb, lane);
    if (tid == 0) {
        mbar_init(sb + SM_DONE, lds32(sb + SM_MISC) >> 8 ? P2W : P1W);
        mbar_init(sb + SM_DONE2, NF);
    }
    cta_sync();
    const uint32_t rid = __shfl_sync(0xffffffffu, lds32(sb + SM_MISC), 0);
    const int role = rid >> 8, id = rid & 255;
    TR(5, tid == 0);
    if (role == 0) {
        const int ww = CFG_MAP1 == 0 ? ((w & 3) == 3 ? NW : (w >> 2) * 3 + (w & 3)) : CFG_MAP1 == 1 ? (w & 2 ? NW : (w >> 2) * 2 + (w & 1)) : w;
        const int sw = CFG_MAP1 == 0 ? ((w & 3) == 3 ? w >> 2 : NW) : CFG_MAP1 == 1 ? (w & 2 ? (w >> 2) * 2 + (w & 1) : NW) : w - P1W;
        static_assert(CFG_MAP1 == 0 ? (P1W <= NW / 4 * 3 && NF + 2 <= NW / 4) : CFG_MAP1 == 1 ? (P1W <= NW / 2 && NF + 2 <= NW / 2) : true, "warp map");
        for (int i = tid; i < NF * GPW * 32; i += NT) sts32(sb + A_CNT + i * 4, 1u << 24);
        if (tid < 64) sts32(sb + SM_CRED + tid * 4, 0u);
        cta_sync();
        TR(1, tid == 0);
        if (ww < P1W) role_p1(p, sb, id, ww, lane);
        else if (sw < NF) role_flush(p, sb, id, sw, lane);
        else if (sw == NF) role_credit1(p, sb, id, lane);
        else if (w == NW - 1) {
            uint4* owin = (uint4*)(p.ring + (CWIN + (lds32(sb + SM_MISC + 16) ^ 1)) * WIN);
            for (int i = id * 32 + lane; i < CPAIRS * 512; i += N1 * 32) __stcg(owin + i, make_uint4(0, 0, 0, 0));
            __syncwarp();
        }
    } else if (role == 1) {
        const int row0 = id % H2 * p.rows2;
        const int nrows = min((int)p.rows2, p.E - row0);
        constexpr int NTB = NT - 32, TBD = CFG_TBD;
        bool flagged = false;
        if (w < NW - 1) {
            const Scale sc = get_scale(sb);
            const Mat4 wd = load_mat4(p.w_down, lane);
            Mat4 ws;
#pragma unroll
            for (int k = 0; k < 4; k++) ws.b[k] = mul_bf2(wd.b[k], ((246u - (lane & 4 ? sc.eb[(k & 2) + 1] : sc.eb[k & 2])) << 7) * 0x10001u);
            const uint4* const src = (const uint4*)(p.m + row0);
            uint4 r2[TBD], nx[TBD];
            auto fetch = [&](int i) {
#pragma unroll
                for (int k = 0; k < TBD; k++)
                    asm volatile("ld.global.nc.v4.u32 {%0,%1,%2,%3}, [%4];" : "=r"(nx[k].x), "=r"(nx[k].y), "=r"(nx[k].z), "=r"(nx[k].w) : "l"(src + min(i + k * NTB, nrows / 2 - 1)));
            };
            fetch(tid);
#pragma unroll 1
            for (int i0 = tid; 2 * (i0 - lane) < nrows; i0 += TBD * NTB) {
#pragma unroll
                for (int k = 0; k < TBD; k++) r2[k] = make_uint4(nx[k].x, nx[k].z, nx[k].y, nx[k].w);
                fetch(i0 + TBD * NTB);
#pragma unroll
                for (int k = 0; k < TBD; k++) {
                    const int i = i0 + k * NTB;
                    float y[8];
                    mul4(make_uint4(r2[k].x, r2[k].z, r2[k].y, r2[k].w), ws, y);
                    uint32_t a[4], h[4], ta[2];
#pragma unroll
                    for (int j = 0; j < 4; j++) { a[j] = pack_h2(y[2 * j], y[2 * j + 1]); h[j] = a[j] + 0x00040004u; }
#pragma unroll
                    for (int j = 0; j < 2; j++) ta[j] = bitsel(h[2 * j], bitsel(h[2 * j + 1] >> 3, h[2 * j + 1] << 7, 0x00070007u), 0x9ff89ff8u);
                    uint32_t tb = prmt(h[1], h[3], 0x7531);
                    const uint32_t b0 = a[0] | a[1] | h[0] | h[1], b1 = a[2] | a[3] | h[2] | h[3];
                    if (__any_sync(0xffffffffu, ((b0 | b1) & 0x60006000u) || sc.allslow)) {
                        if ((b0 & 0x60006000u) || sc.allslow) { ta[0] = 0; tb = (tb & 0xffff0000u) | 0x40u; }
                        if ((b1 & 0x60006000u) || sc.allslow) { ta[1] = 0; tb = (tb & 0xffffu) | 0x400000u; }
                        flagged = true;
                    }
                    sts64_if(sb + B_TA + i * 8, ta[0], ta[1], 2 * i < nrows);
                    sts32_if(sb + B_TB + i * 4, tb, 2 * i < nrows);
                }
            }
            if (tid == 0) {
                sts32(sb + B_TA + p.rows2 * 4, 0u);
                sts16(sb + B_TB + p.rows2 * 2, 0u);
            }
            TR(8, tid == 0);
        } else if (lane == 0) spin_ge(rdy_of(p, sb, id, id / H2), H3);
        __syncwarp();
        flagged = __any_sync(0xffffffffu, __syncthreads_or(flagged));
        TR(1, tid == 0);
        if (w < P2W) {
            if (flagged) role_p2<true>(p, sb, id, w, lane);
            else role_p2<false>(p, sb, id, w, lane);
        } else if (w == P2W) role_credit(p, sb, id, lane);
    } else {
        if (w == 0) clear_queues<false>(p, sb, id, lane);
        if (tid >= 32 && tid < 33 + NPC) mbar_init(sb + SM_CNT2 + (tid - 32) * 8, 1);
        cta_sync();
        TR(1, tid == 0);
        if (w < P3W) role_p3(p, sb, id, w, lane);
        cta_sync();
        TR(2, tid == 0);
        if (w < NPC && lane == 0) {
            fence_async_smem();
            const int n = min(((int)p.rows3 + 7) / 8 * 8 - w * RPC, RPC);
            if (w >= CFG_DOUT) mbar_wait(sb + SM_CNT2 + (w + 1 - CFG_DOUT) * 8, 0);
            if (n > 0) {
                bulk_store(g_S[0][id] + w * RPC, sb + C_S + w * RPC * 4, n * 4);
                bulk_store(g_S[1][id] + w * RPC, sb + C_S + (ROWS3_MAX + w * RPC) * 4, n * 4);
            }
            asm volatile("cp.async.bulk.commit_group;" ::: "memory");
            asm volatile("cp.async.bulk.wait_group.read 0;" ::: "memory");
            mbar_arrive(sb + SM_CNT2 + w * 8 + 8);
            asm volatile("cp.async.bulk.wait_group 0;" ::: "memory");
            fence_gpu();
            red_rlx(rdy_of(p, sb, 160 + 32 * w, 0), 1u);
            red_rlx(rdy_of(p, sb, 160 + 32 * w, 1), 1u);
            if (id == 0 && w == 0) red_rlx(&g_epoch, 1u);
            TR(12 + w, true);
        }
        return;
    }
    cta_sync();
    TR(18, tid == 0 && role == 1);
    if (role == 0 && w == NW - 2) clear_queues<true>(p, sb, id, lane);
    tail_rows(p, role * N1 + id, w, lane);
}

__global__ void k_direct(const Params p, long long T) {
    float wd[16];
#pragma unroll
    for (int i = 0; i < 16; i++) wd[i] = __bfloat162float(p.w_down[i]);
    const float f = __bfloat162float(p.freq[0]);
    for (long long t = blockIdx.x * (long long)blockDim.x + threadIdx.x; t < T; t += (long long)gridDim.x * blockDim.x) {
        float x = __bfloat162float(__float2bfloat16(f * __bfloat162float(p.angle[t])));
        float c = __bfloat162float(__float2bfloat16(cosf(x)));
        uint2 md = down_row(__ldg(p.m + p.idx_in[t]), wd);
        red_v4(g_Sg + p.idx_out[t], c * bflo(md.x), c * bfhi(md.x), c * bflo(md.y), c * bfhi(md.y));
    }
}
__global__ void k_direct_tail(const Params p) {
    __shared__ __align__(16) float sw[96];
    load_tail_weights(p, sw, threadIdx.x);
    __syncthreads();
    uint32_t c2[4];
#pragma unroll
    for (int i = 0; i < 4; i++) c2[i] = ((const uint32_t*)p.centers)[i];
    for (int e = blockIdx.x * blockDim.x + threadIdx.x; e < p.E; e += gridDim.x * blockDim.x) {
        float4 g = __ldcg(g_Sg + e);
        __stcg(g_Sg + e, make_float4(0.f, 0.f, 0.f, 0.f));
        const float Sv[4] = {g.x, g.y, g.z, g.w};
        float4 gs, gr;
        row_gates(sw, c2, __bfloat16_as_ushort(p.dist[e]), gs, gr);
        p.out[e] = finish_row(sw + 64, gs, gr, Sv, __ldg(p.m + e));
    }
}

static bool pick_rows(int E, int n, int rows_max, int mult, uint32_t* rows, uint32_t* magic) {
    for (uint32_t r = (E + n - 1) / n; r <= (uint32_t)rows_max; r++) {
        if (r < 2 || r % mult) continue;
        uint64_t mg = ((1ull << 32) + r - 1) / r;
        uint64_t err = mg * r - (1ull << 32);
        if (err * (uint64_t)n < mg) { *rows = r; *magic = (uint32_t)mg; return true; }
    }
    return false;
}

}

extern "C" void kernel_launch(void* const* d_in, const int* in_sizes, int n_in, void* d_out, int out_size) {
    using namespace gs;
    (void)n_in; (void)out_size;
    Params p;
    p.m = (const uint2*)d_in[0];
    p.idx_in = (const int*)d_in[1];
    p.idx_out = (const int*)d_in[2];
    p.dist = (const __nv_bfloat16*)d_in[3];
    p.angle = (const __nv_bfloat16*)d_in[4];
    p.centers = (const __nv_bfloat16*)d_in[5];
    p.freq = (const __nv_bfloat16*)d_in[6];
    p.w_rbf = (const __nv_bfloat16*)d_in[7];
    p.w_sbf = (const __nv_bfloat16*)d_in[8];
    p.w_down = (const __nv_bfloat16*)d_in[9];
    p.w_up = (const __nv_bfloat16*)d_in[10];
    p.out = (uint2*)d_out;
    p.E = in_sizes[3];
    const long long T = in_sizes[1];
    p.n4 = (int)(T / 4);
    p.rows2 = p.magic2 = 0;
    p.ring = nullptr;

    static int sms = 0, rsv = 0;
    if (!sms) {
        int dev = 0;
        cudaGetDevice(&dev);
        cudaDeviceGetAttribute(&rsv, cudaDevAttrReservedSharedMemoryPerBlock, dev);
        cudaDeviceGetAttribute(&sms, cudaDevAttrMultiProcessorCount, dev);
        cudaFuncSetAttribute(k_main, cudaFuncAttributeMaxDynamicSharedMemorySize, SMEM_BYTES);
    }
    cudaStream_t st = cudaStreamPerThread;
    bool fast = (T % 4 == 0) && T > 0 && sms >= NCTA && rsv == (int)SB && p.E >= 65536 && p.E <= E_MAX &&
                p.E % 4 == 0 && (((uintptr_t)p.m | (uintptr_t)p.idx_in | (uintptr_t)p.idx_out | (uintptr_t)p.angle) & 15) == 0 &&
                pick_rows(p.E, NI, ROWS2_MAX, 2, &p.rows2, &p.magic2);
    p.c1 = 1;
    p.nrows2 = 0u - p.rows2;
    p.rows3 = (p.E + 31) / 32;
    fast = fast && (p.rows2 * (NI - 1) + 2 <= (uint32_t)p.E);
    static const void* tkey[3] = {nullptr, nullptr, nullptr};
    static cudaTextureObject_t tex[3] = {0, 0, 0};
    static long long tlen = -1;
    const void* tptr[3] = {p.idx_in, p.idx_out, p.angle};
    for (int k = 0; fast && k < 3; k++) {
        if (tkey[k] == tptr[k] && tlen == T) continue;
        if (tkey[k]) cudaDestroyTextureObject(tex[k]);
        tkey[k] = nullptr;
        cudaResourceDesc rd = {};
        rd.resType = cudaResourceTypeLinear;
        rd.res.linear.devPtr = (void*)tptr[k];
        rd.res.linear.desc = cudaCreateChannelDesc(32, 32, k < 2 ? 32 : 0, k < 2 ? 32 : 0, cudaChannelFormatKindUnsigned);
        rd.res.linear.sizeInBytes = (size_t)T * (k < 2 ? 4 : 2);
        cudaTextureDesc td = {};
        td.readMode = cudaReadModeElementType;
        if (cudaCreateTextureObject(&tex[k], &rd, &td, nullptr) == cudaSuccess) tkey[k] = tptr[k];
        else { (void)cudaGetLastError(); fast = false; }
    }
    if (fast) tlen = T;
    p.t_in = tex[0]; p.t_out = tex[1]; p.t_ang = tex[2];
    if (fast) {
        void* ring = nullptr;
        cudaGetSymbolAddress(&ring, g_ring);
        uintptr_t a = ((uintptr_t)ring + WIN - 1) & ~(uintptr_t)(WIN - 1);
        if (a >> 32 != (a + RING_BYTES - 1) >> 32) a += RING_BYTES;
        p.ring = (unsigned char*)a;
        p.ring_lo = (uint32_t)a;
        p.ring_hi = (uint32_t)(a >> 32);
        k_main<<<NCTA, NT, SMEM_BYTES, st>>>(p);
    } else {
        k_direct<<<sms * 8, 256, 0, st>>>(p, T);
        k_direct_tail<<<sms * 4, 256, 0, st>>>(p);
    }
}
```

```cpp
#include <cuda_runtime.h>
#include <cuda_bf16.h>
#include <stdint.h>

#define CFG_N1 56
#define CFG_NI 22
#define CFG_NW 28
#define CFG_P1W 14
#define CFG_GPW 2
#define CFG_KR 1
#define CFG_SMPAD 0
#define CFG_QPW 3
#define CFG_TG 2
#define CFG_PMASK 8
#define CFG_PSTREAK 1
#define CFG_NBT 1
#define CFG_KM 5
#define CFG_KN 9
#define CFG_TBD 4
#define CFG_P0 500
#define CFG_PFD 200
#define CFG_C1SLEEP 200
#define CFG_PK1 6
#define CFG_PK2 8
#define CFG_PK3 11
#define CFG_CLN 2
#define CFG_CLS 300
#define CFG_DOUT 2
#define CFG_TBLOW 1
#define CFG_LLOW 1
#define CFG_CRM 0
#define CFG_TH 14
#define CFG_TS 200
#define CFG_POLL 64
#define CFG_HINT 20000
#define CFG_BSLEEP 100
#define CFG_CSLEEP 200
#define CFG_FSLEEP 100
#define CFG_PSLEEP 100
#define CFG_DRY 1
#define CFG_PROBES 4

namespace gs {

constexpr int E_MAX = 640000;
constexpr int N1 = CFG_N1, NI = CFG_NI, N2 = 2 * NI, N3 = 32, NCTA = N1 + N2 + N3;
constexpr int H2 = NI, H3 = N3 / 2;
constexpr int NB = NI * N3;
constexpr int NW = CFG_NW, NT = NW * 32;
constexpr int GPW = CFG_GPW, NF = (NI + GPW - 1) / GPW;
constexpr int QPW = CFG_QPW, NBT = CFG_NBT;
constexpr int P1W = CFG_P1W, P2W = (N1 + QPW - 1) / QPW, P3W = NI;
constexpr int NQ1 = 32, NQ2 = 64;
constexpr int ROWS2_MAX = ((E_MAX + NI - 1) / NI + 31) / 8 * 8;
constexpr int ROWS3_MAX = (E_MAX / 32 + 31) / 32 * 32;
constexpr int NTAIL = N1 + N2;
constexpr int NPC = 5, WPP = 5, RPC = NTAIL * WPP * 8;
constexpr int GUARD = 1 << 26;
static_assert(NCTA % 4 == 0 && NCTA <= 192, "roles come in CTA pairs, per partition");
static_assert((GPW == 2 || GPW == 4) && QPW >= NBT && QPW <= 4 && NI <= 32 && N1 <= 62, "queue ownership");
static_assert(P1W + NF + 2 <= NW && P2W + 2 <= NW && P3W + 1 <= NW && P1W * 256 + 64 < 8192, "warp roles");
static_assert(ROWS2_MAX + 8 <= 32768 && ROWS3_MAX <= 32768, "index bits");

constexpr uint32_t SB = 1024;
constexpr int SM_DONE = 0, SM_DONE2 = 8;
constexpr int SM_MISC = 16;
constexpr int SM_FIN = 48;
constexpr int SM_STAT = 64;
constexpr int SM_CNT2 = 128;
constexpr int SM_W = 256;
constexpr int SM_PUB = SM_W + 384;
constexpr int SM_PROBE = SM_PUB + 768;
constexpr int SM_CRED = 1792;
constexpr int SM_DATA = 2048;
constexpr int cmax(int a, int b) { return a > b ? a : b; }
constexpr int A_CNT = SM_DATA;
constexpr int KR = CFG_KR, LISTB = (GPW * 32 + 8 * KR) * 4;
constexpr int A_ST = A_CNT + NF * GPW * 128 + (CFG_LLOW ? (NF * LISTB + 127) / 128 * 128 : 0);
constexpr int A_LIST = CFG_LLOW ? A_CNT + NF * GPW * 128 : A_ST + NB * 256;
constexpr int A_END = A_ST + NB * 256 + (CFG_LLOW ? 0 : NF * LISTB);
constexpr int B_TB = CFG_TBLOW ? SM_DATA : SM_DATA + (ROWS2_MAX + 8) * 4;
constexpr int B_TA = CFG_TBLOW ? SM_DATA + (ROWS2_MAX + 8) * 2 : SM_DATA;
constexpr int B_END = SM_DATA + (ROWS2_MAX + 8) * 6;
constexpr int C_S = SM_DATA;
constexpr int C_END = C_S + ROWS3_MAX * 8;
constexpr int T_G = SM_DATA, TWB = 4096 + 2048 + 512, T_END = T_G + NPC * WPP * TWB;
constexpr int ZEND = cmax(A_END, C_END);
constexpr int SM_ZERO = (cmax(C_END, T_END) + 127) / 128 * 128;
constexpr int SMEM_BYTES = cmax(cmax(A_END, B_END), SM_ZERO + 4096) + CFG_SMPAD;
static_assert(SMEM_BYTES <= 232448 && SM_PROBE + 128 <= SM_CRED, "shared memory");
static_assert(NPC * RPC >= ROWS3_MAX && NPC * WPP + 2 <= NW, "tail");

constexpr uint32_t FIN = 0x80000000u;

constexpr uint32_t WIN = 524288;
constexpr int CWIN = N2 + N3, NWIN = CWIN + 2, CPAIRS = 31;
constexpr uint32_t PROBE_OFF = (uint32_t)NWIN * WIN;
constexpr int NPROBE = 16;
static_assert(NWIN <= NCTA && NPROBE <= NW, "windows");
constexpr size_t RING_BYTES = (size_t)PROBE_OFF + WIN;
__device__ __align__(128) unsigned char g_ring[2 * RING_BYTES + WIN];
__device__ __align__(128) uint32_t g_S[2][32][ROWS3_MAX];
__device__ __align__(128) float4 g_Sg[E_MAX];
__device__ uint32_t g_dirty[E_MAX / 32];
__device__ uint32_t g_epoch;

#define TR(ev, on)
#define ACC_DECL
#define ACC(i, n)
#define ACC_SAVE

struct Params {
    const uint2* m;
    const int* idx_in;
    const int* idx_out;
    const __nv_bfloat16* dist;
    const __nv_bfloat16* angle;
    const __nv_bfloat16* centers;
    const __nv_bfloat16* freq;
    const __nv_bfloat16* w_rbf;
    const __nv_bfloat16* w_sbf;
    const __nv_bfloat16* w_down;
    const __nv_bfloat16* w_up;
    uint2* out;
    unsigned char* ring;
    cudaTextureObject_t t_in, t_out, t_ang;
    int E, n4;
    uint32_t rows2, nrows2, magic2, rows3;
    uint32_t ring_lo, ring_hi, c1;
};

__device__ __forceinline__ float bflo(uint32_t w) { return __uint_as_float(w << 16); }
__device__ __forceinline__ float bfhi(uint32_t w) { return __uint_as_float(w & 0xffff0000u); }
__device__ __forceinline__ uint32_t pack_bf2(float lo, float hi) {
    uint32_t r;
    asm("cvt.rn.bf16x2.f32 %0, %1, %2;" : "=r"(r) : "f"(hi), "f"(lo));
    return r;
}
__device__ __forceinline__ uint32_t mul_bf2(uint32_t a, uint32_t b) {
    uint32_t r;
    asm("mul.rn.bf16x2 %0, %1, %2;" : "=r"(r) : "r"(a), "r"(b));
    return r;
}
__device__ __forceinline__ uint32_t sub_bf2(uint32_t a, uint32_t b) {
    uint32_t r;
    asm("sub.rn.bf16x2 %0, %1, %2;" : "=r"(r) : "r"(a), "r"(b));
    return r;
}
__device__ __forceinline__ uint32_t maxabs_bf2(uint32_t a, uint32_t b) {
    uint32_t r;
    asm("max.NaN.xorsign.abs.bf16x2 %0, %1, %2;" : "=r"(r) : "r"(a), "r"(b));
    return r;
}
__device__ __forceinline__ void mbar_init(uint32_t a, uint32_t n) {
    asm volatile("mbarrier.init.shared::cta.b64 [%0], %1;" ::"r"(a), "r"(n) : "memory");
}
__device__ __forceinline__ void mbar_arrive(uint32_t a) {
    asm volatile("mbarrier.arrive.shared::cta.b64 _, [%0];" ::"r"(a) : "memory");
}
__device__ __forceinline__ void mbar_arrive_n(uint32_t a, uint32_t n) {
    asm volatile("mbarrier.arrive.shared::cta.b64 _, [%0], %1;" ::"r"(a), "r"(n) : "memory");
}
__device__ __forceinline__ void mbar_arrive_if(uint32_t a, bool on) {
    asm volatile("{.reg .pred q; setp.ne.u32 q, %1, 0; @q mbarrier.arrive.shared::cta.b64 _, [%0];}" ::"r"(a), "r"((uint32_t)on) : "memory");
}
__device__ __forceinline__ void mbar_wait(uint32_t a, uint32_t parity) {
    uint32_t ok;
    int guard = 0;
    do {
        asm volatile("{.reg .pred p; mbarrier.try_wait.parity.shared::cta.b64 p, [%1], %2, %3; selp.u32 %0, 1, 0, p;}"
                     : "=r"(ok) : "r"(a), "r"(parity), "r"(CFG_HINT) : "memory");
        if (!ok) {
            if (++guard > GUARD) __trap();
        }
    } while (!ok);
}
__device__ __forceinline__ void cta_sync() { __syncwarp(); __syncthreads(); }
__device__ __forceinline__ void bar_sync(int id, int n) { asm volatile("bar.sync %0, %1;" ::"r"(id), "r"(n) : "memory"); }
__device__ __forceinline__ void bar_arrive(int id, int n) { asm volatile("bar.arrive %0, %1;" ::"r"(id), "r"(n) : "memory"); }
__device__ __forceinline__ bool mbar_test(uint32_t a, uint32_t parity) {
    uint32_t ok;
    asm volatile("{.reg .pred p; mbarrier.test_wait.parity.shared::cta.b64 p, [%1], %2; selp.u32 %0, 1, 0, p;}"
                 : "=r"(ok) : "r"(a), "r"(parity) : "memory");
    return ok;
}
__device__ __forceinline__ uint32_t ld_acq(const uint32_t* p) {
    uint32_t v;
    asm volatile("ld.acquire.gpu.global.u32 %0, [%1];" : "=r"(v) : "l"(p) : "memory");
    return v;
}
__device__ __forceinline__ uint32_t ld_rlx(const uint32_t* p) {
    uint32_t v;
    asm volatile("ld.relaxed.gpu.global.u32 %0, [%1];" : "=r"(v) : "l"(p) : "memory");
    return v;
}
__device__ __forceinline__ void st_rlx(uint32_t* p, uint32_t v) {
    asm volatile("st.relaxed.gpu.global.u32 [%0], %1;" ::"l"(p), "r"(v) : "memory");
}
__device__ __forceinline__ void red_rlx(uint32_t* p, uint32_t v) {
    asm volatile("red.relaxed.gpu.global.add.u32 [%0], %1;" ::"l"(p), "r"(v) : "memory");
}
__device__ __forceinline__ bool elect_one() {
    uint32_t p;
    asm volatile("{.reg .pred P; elect.sync _|P, 0xffffffff; selp.u32 %0, 1, 0, P;}" : "=r"(p));
    return p;
}
__device__ __forceinline__ uint32_t spin_ge(const uint32_t* p, uint32_t target) {
    int guard = 0;
    while (ld_rlx(p) < target) {
        __nanosleep(CFG_POLL);
        if (++guard > GUARD) __trap();
    }
    return ld_acq(p);
}
__device__ __forceinline__ void fence_gpu() { asm volatile("fence.acq_rel.gpu;" ::: "memory"); }
__device__ __forceinline__ void fence_async_smem() { asm volatile("fence.proxy.async.shared::cta;" ::: "memory"); }
__device__ __forceinline__ void fence_async_all() { asm volatile("fence.proxy.async;" ::: "memory"); }
__device__ __forceinline__ void bulk_store(void* g, uint32_t s, uint32_t bytes) {
    asm volatile("cp.async.bulk.global.shared::cta.bulk_group [%0], [%1], %2;" ::"l"(g), "r"(s), "r"(bytes) : "memory");
}
__device__ __forceinline__ void cp16(uint32_t s, const void* g, bool on) {
    asm volatile("{.reg .pred q; setp.ne.u32 q, %2, 0; @q cp.async.cg.shared.global [%0], [%1], 16;}" ::"r"(s), "l"(g), "r"((uint32_t)on) : "memory");
}
__device__ __forceinline__ void cp16z(uint32_t s, const void* g, int bytes) {
    asm volatile("cp.async.cg.shared.global [%0], [%1], 16, %2;" ::"r"(s), "l"(g), "r"(bytes) : "memory");
}
__device__ __forceinline__ void cp_commit() { asm volatile("cp.async.commit_group;" ::: "memory"); }
template <int N> __device__ __forceinline__ void cp_wait() { asm volatile("cp.async.wait_group %0;" ::"n"(N) : "memory"); }
__device__ __forceinline__ uint32_t atoms_add(uint32_t a, uint32_t v) {
    uint32_t o;
    asm volatile("atom.shared.add.u32 %0, [%1], %2;" : "=r"(o) : "r"(a), "r"(v) : "memory");
    return o;
}
__device__ __forceinline__ void sts32(uint32_t a, uint32_t v) { asm volatile("st.shared.u32 [%0], %1;" ::"r"(a), "r"(v) : "memory"); }
__device__ __forceinline__ void sts16(uint32_t a, uint32_t v) { asm volatile("st.shared.u16 [%0], %1;" ::"r"(a), "h"((uint16_t)v) : "memory"); }
__device__ __forceinline__ void sts64(uint32_t a, uint32_t x, uint32_t y) { asm volatile("st.shared.v2.u32 [%0], {%1,%2};" ::"r"(a), "r"(x), "r"(y) : "memory"); }
__device__ __forceinline__ uint32_t lds32(uint32_t a) {
    uint32_t v;
    asm volatile("ld.shared.u32 %0, [%1];" : "=r"(v) : "r"(a) : "memory");
    return v;
}
__device__ __forceinline__ uint2 lds64(uint32_t a) {
    uint2 v;
    asm volatile("ld.shared.v2.u32 {%0,%1}, [%2];" : "=r"(v.x), "=r"(v.y) : "r"(a));
    return v;
}
__device__ __forceinline__ uint2 lds64v(uint32_t a) {
    uint2 v;
    asm volatile("ld.volatile.shared.v2.u32 {%0,%1}, [%2];" : "=r"(v.x), "=r"(v.y) : "r"(a) : "memory");
    return v;
}
__device__ __forceinline__ uint32_t lds32v(uint32_t a) {
    uint32_t v;
    asm volatile("ld.volatile.shared.u32 %0, [%1];" : "=r"(v) : "r"(a) : "memory");
    return v;
}
__device__ __forceinline__ uint4 lds128(uint32_t a) {
    uint4 v;
    asm volatile("ld.shared.v4.u32 {%0,%1,%2,%3}, [%4];" : "=r"(v.x), "=r"(v.y), "=r"(v.z), "=r"(v.w) : "r"(a) : "memory");
    return v;
}
__device__ __forceinline__ void sts128(uint32_t a, uint4 v) {
    asm volatile("st.shared.v4.u32 [%0], {%1,%2,%3,%4};" ::"r"(a), "r"(v.x), "r"(v.y), "r"(v.z), "r"(v.w) : "memory");
}
#define LD_Q "ld.relaxed.gpu.global"
__device__ __forceinline__ uint4 ldg_q128(const void* p) {
    uint4 v;
    asm volatile(LD_Q ".v4.u32 {%0,%1,%2,%3}, [%4];"
                 : "=r"(v.x), "=r"(v.y), "=r"(v.z), "=r"(v.w) : "l"(p) : "memory");
    return v;
}
__device__ __forceinline__ uint2 ldg_q64(const void* p) {
    uint2 v;
    asm volatile(LD_Q ".v2.u32 {%0,%1}, [%2];" : "=r"(v.x), "=r"(v.y) : "l"(p) : "memory");
    return v;
}
__device__ __forceinline__ void red_v4(float4* p, float a, float b, float c, float d) {
    asm volatile("red.global.add.v4.f32 [%0], {%1,%2,%3,%4};" ::"l"(p), "f"(a), "f"(b), "f"(c), "f"(d) : "memory");
}
__device__ __forceinline__ uint2 down_row(uint2 r, const float* wd) {
    float x0 = bflo(r.x), x1 = bfhi(r.x), x2 = bflo(r.y), x3 = bfhi(r.y);
    float y[4];
#pragma unroll
    for (int j = 0; j < 4; j++) y[j] = x0 * wd[j] + x1 * wd[4 + j] + x2 * wd[8 + j] + x3 * wd[12 + j];
    return make_uint2(pack_bf2(y[0], y[1]), pack_bf2(y[2], y[3]));
}
__device__ __forceinline__ uint32_t prmt(uint32_t a, uint32_t b, uint32_t s) {
    uint32_t r;
    asm("prmt.b32 %0, %1, %2, %3;" : "=r"(r) : "r"(a), "r"(b), "r"(s));
    return r;
}
__device__ __forceinline__ uint32_t bitsel(uint32_t a, uint32_t b, uint32_t m) {
    uint32_t r;
    asm("lop3.b32 %0, %1, %2, %3, 0xE4;" : "=r"(r) : "r"(a), "r"(b), "r"(m));
    return r;
}
__device__ __forceinline__ uint32_t pack_h2(float lo, float hi) {
    uint32_t r;
    asm("cvt.rn.f16x2.f32 %0, %1, %2;" : "=r"(r) : "f"(hi), "f"(lo));
    return r;
}
__device__ __forceinline__ uint32_t mul_h2(uint32_t a, uint32_t b) {
    uint32_t r;
    asm("mul.rn.f16x2 %0, %1, %2;" : "=r"(r) : "r"(a), "r"(b));
    return r;
}
__device__ __forceinline__ uint32_t lds32nv(uint32_t a) {
    uint32_t v;
    asm volatile("ld.shared.u32 %0, [%1];" : "=r"(v) : "r"(a));
    return v;
}
__device__ __forceinline__ uint32_t lds16nv(uint32_t a) {
    uint32_t v;
    asm volatile("ld.shared.u16 %0, [%1];" : "=r"(v) : "r"(a));
    return v;
}
#define X_CR1
#define X_CR2
#define X_ST1
#define X_ST2
#define ST_Q "st.relaxed.gpu.global"
__device__ __forceinline__ void stg_q128(void* p, uint32_t a, uint32_t b, uint32_t c, uint32_t d, bool on) {
    asm volatile("{.reg .pred q; setp.ne.u32 q, %5, 0; @q " ST_Q ".v4.u32 [%0], {%1,%2,%3,%4};}"
                 ::"l"(p), "r"(a), "r"(b), "r"(c), "r"(d), "r"((uint32_t)on) : "memory");
}
__device__ __forceinline__ void stg_q64(void* p, uint32_t a, uint32_t b, bool on) {
    asm volatile("{.reg .pred q; setp.ne.u32 q, %3, 0; @q " ST_Q ".v2.u32 [%0], {%1,%2};}"
                 ::"l"(p), "r"(a), "r"(b), "r"((uint32_t)on) : "memory");
}
__device__ __forceinline__ void st_rlx_if(uint32_t* p, uint32_t v, bool on) {
    asm volatile("{.reg .pred q; setp.ne.u32 q, %2, 0; @q st.relaxed.gpu.global.u32 [%0], %1;}" ::"l"(p), "r"(v), "r"((uint32_t)on) : "memory");
}
__device__ __forceinline__ uint32_t ld_rlx_if(const uint32_t* p, bool on) {
    uint32_t v;
    asm volatile("{.reg .pred q; setp.ne.u32 q, %2, 0; mov.b32 %0, 0; @q ld.relaxed.gpu.global.u32 %0, [%1];}" : "=&r"(v) : "l"(p), "r"((uint32_t)on) : "memory");
    return v;
}
__device__ __forceinline__ void ldq128_keep(uint4& v, const void* p, bool on) {
    asm volatile("{.reg .pred q; setp.ne.u32 q, %5, 0; @q ld.relaxed.gpu.global.v4.u32 {%0,%1,%2,%3}, [%4];}"
                 : "+r"(v.x), "+r"(v.y), "+r"(v.z), "+r"(v.w) : "l"(p), "r"((uint32_t)on) : "memory");
}
__device__ __forceinline__ void ldq64_keep(uint2& v, const void* p, bool on) {
    asm volatile("{.reg .pred q; setp.ne.u32 q, %3, 0; @q ld.relaxed.gpu.global.v2.u32 {%0,%1}, [%2];}"
                 : "+r"(v.x), "+r"(v.y) : "l"(p), "r"((uint32_t)on) : "memory");
}
__device__ __forceinline__ void atoms_add_keep(uint32_t& o, uint32_t a, uint32_t v, bool on) {
    asm volatile("{.reg .pred q; setp.ne.u32 q, %3, 0; @q atom.shared.add.u32 %0, [%1], %2;}" : "+r"(o) : "r"(a), "r"(v), "r"((uint32_t)on) : "memory");
}
__device__ __forceinline__ void reds_add(uint32_t a, uint32_t v) { asm volatile("red.shared.add.u32 [%0], %1;" ::"r"(a), "r"(v) : "memory"); }
__device__ __forceinline__ void sts32_if(uint32_t a, uint32_t v, bool on) {
    asm volatile("{.reg .pred q; setp.ne.u32 q, %2, 0; @q st.shared.u32 [%0], %1;}" ::"r"(a), "r"(v), "r"((uint32_t)on) : "memory");
}
__device__ __forceinline__ void sts64_if(uint32_t a, uint32_t x, uint32_t y, bool on) {
    asm volatile("{.reg .pred q; setp.ne.u32 q, %3, 0; @q st.shared.v2.u32 [%0], {%1,%2};}" ::"r"(a), "r"(x), "r"(y), "r"((uint32_t)on) : "memory");
}
__device__ __forceinline__ void lds128_keep(uint4& v, uint32_t a, bool on) {
    asm volatile("{.reg .pred q; setp.ne.u32 q, %5, 0; @q ld.volatile.shared.v4.u32 {%0,%1,%2,%3}, [%4];}"
                 : "+r"(v.x), "+r"(v.y), "+r"(v.z), "+r"(v.w) : "r"(a), "r"((uint32_t)on) : "memory");
}
__device__ __forceinline__ void or3_if(uint32_t& x, uint32_t a, uint32_t b, bool on) {
    asm("{.reg .pred q; setp.ne.u32 q, %3, 0; @q lop3.b32 %0, %0, %1, %2, 0xfe;}" : "+r"(x) : "r"(a), "r"(b), "r"((uint32_t)on));
}
__device__ __forceinline__ uint32_t clk() {
    uint32_t t;
    asm volatile("mov.u32 %0, %%clock;" : "=r"(t) :: "memory");
    return t;
}
__device__ __forceinline__ void sg_add(int row, float a, float b, float c, float d) {
    red_v4(g_Sg + row, a, b, c, d);
    st_rlx(g_dirty + (row >> 5), 1u);
}
__device__ __forceinline__ void slow_add(const uint2* m, uint32_t sb, int in, int out, float c) {
    const uint2 r = __ldg(m + in);
    const float x[4] = {bflo(r.x), bfhi(r.x), bflo(r.y), bfhi(r.y)};
    float y[4] = {0.f, 0.f, 0.f, 0.f};
#pragma unroll
    for (int k = 0; k < 4; k++) {
        const uint4 q = lds128(sb + SM_W + 320 + k * 16);
        y[0] = k ? y[0] + x[k] * __uint_as_float(q.x) : x[k] * __uint_as_float(q.x);
        y[1] = k ? y[1] + x[k] * __uint_as_float(q.y) : x[k] * __uint_as_float(q.y);
        y[2] = k ? y[2] + x[k] * __uint_as_float(q.z) : x[k] * __uint_as_float(q.z);
        y[3] = k ? y[3] + x[k] * __uint_as_float(q.w) : x[k] * __uint_as_float(q.w);
    }
    const uint32_t lo = pack_bf2(y[0], y[1]), hi = pack_bf2(y[2], y[3]);
    sg_add(out, c * bflo(lo), c * bfhi(lo), c * bflo(hi), c * bfhi(hi));
}

struct Mat4 { uint32_t b[4]; };
__device__ __forceinline__ Mat4 load_mat4(const __nv_bfloat16* w, int lane) {
    const unsigned short* u = (const unsigned short*)w + (lane >> 2 & 1);
    const bool on = lane >> 3 == (lane & 3);
    Mat4 m;
#pragma unroll
    for (int k = 0; k < 4; k++) m.b[k] = on ? u[(k & 1) * 8 + (k & 2)] | (uint32_t)u[(k & 1) * 8 + 4 + (k & 2)] << 16 : 0u;
    return m;
}
__device__ __forceinline__ void mul4(const uint4& x, const Mat4& m, float (&y)[8]) {
#pragma unroll
    for (int h = 0; h < 2; h++)
        asm("mma.sync.aligned.m16n8k16.row.col.f32.bf16.bf16.f32 {%0,%1,%2,%3}, {%4,%5,%6,%7}, {%8,%9}, {%10,%10,%10,%10};"
            : "=f"(y[2 * h]), "=f"(y[2 * h + 1]), "=f"(y[4 + 2 * h]), "=f"(y[5 + 2 * h])
            : "r"(x.x), "r"(x.z), "r"(x.y), "r"(x.w), "r"(m.b[2 * h]), "r"(m.b[2 * h + 1]), "f"(0.f));
}

struct Scale { uint32_t eb[4]; bool allslow; };
__device__ __forceinline__ void md_stats(const uint4& in, const Mat4& wd, int lane) {
    float y[8];
    mul4(in, wd, y);
    uint32_t mx[4], se[4];
#pragma unroll
    for (int c = 0; c < 4; c++) {
        uint32_t a = __float_as_uint(y[c]) & 0x7fffffffu, b = __float_as_uint(y[4 + c]) & 0x7fffffffu;
        if (a >= 0x7f800000u) a = 0;
        if (b >= 0x7f800000u) b = 0;
        mx[c] = __reduce_max_sync(0xffffffffu, max(a, b));
        se[c] = __reduce_add_sync(0xffffffffu, (a >> 23) + (b >> 23) + (a ? 1u << 20 : 0u) + (b ? 1u << 20 : 0u));
    }
    if (lane < 4) {
        asm volatile("red.shared.max.u32 [%0], %1;" ::"r"(SB + SM_STAT + lane * 4), "r"(lane == 0 ? mx[0] : lane == 1 ? mx[1] : lane == 2 ? mx[2] : mx[3]) : "memory");
        reds_add(SB + SM_STAT + 16 + lane * 4, lane == 0 ? se[0] : lane == 1 ? se[1] : lane == 2 ? se[2] : se[3]);
    }
}
__device__ __forceinline__ Scale get_scale(uint32_t sb) {
    Scale s;
    s.allslow = false;
#pragma unroll
    for (int k = 0; k < 4; k++) {
        const uint32_t mx = lds32(sb + SM_STAT + 4 * k), se = lds32(sb + SM_STAT + 16 + 4 * k);
        const uint32_t mean = (uint32_t)__fdividef((float)(se & 0xfffffu), (float)max(se >> 20, 1u));
        uint32_t eb = min(min((mx + 0x6e0000u) >> 23, mean + 5u), 227u);
        if (eb < 27u) { s.allslow = s.allslow || mx != 0; eb = 27u; }
        if (eb > 170u) s.allslow = true;
        s.eb[k] = eb;
    }
    return s;
}

__device__ __forceinline__ uint32_t probe_rt(uint32_t* p) {
    uint32_t best = 0xffffffffu;
#pragma unroll 1
    for (int r = 0; r < CFG_PROBES; r++) {
        const uint32_t t0 = clock();
        uint32_t v;
        asm volatile("atom.relaxed.gpu.global.add.u32 %0, [%1], 1;" : "=r"(v) : "l"(p) : "memory");
        if (v > 100000u) __trap();
        const uint32_t t1 = clock();
        best = min(best, t1 - t0);
    }
    return best;
}
__device__ __forceinline__ uint32_t* pub_ptr(const Params& p, int blk, uint32_t sel) {
    const int pr = blk / 44;
    return (uint32_t*)(p.ring + PROBE_OFF + (pr ? 4096u << pr : 0u) + (sel << 12) + 2176 + (blk - pr * 44) * 32);
}
__device__ __forceinline__ void probe(const Params& p, uint32_t sb, int w, int lane) {
    const int blk = blockIdx.x, pr = w >> 1;
    uint32_t off = PROBE_OFF + blk * 16 + (pr ? 4096u << pr : 0u);
    if (pr == 7) off = blk < NWIN ? blk * WIN + 4064 : PROBE_OFF + 3584 + blk % 16 * 32;
    off += (w & 1) * 4096;
    if (lane < 8) st_rlx((uint32_t*)(p.ring + (off & ~31u)) + lane, 0u);
    if (lane == 0) sts32(sb + SM_PROBE + w * 4, probe_rt((uint32_t*)(p.ring + off)));
}
__device__ __forceinline__ void assign_role(const Params& p, uint32_t sb, int lane) {
    {
        const bool x = lane < 8 && lds32(sb + SM_PROBE + lane * 8 + 4) < lds32(sb + SM_PROBE + lane * 8);
        const uint32_t near = __ballot_sync(0xffffffffu, x), bits = near & 1 ? ~near | 1u : near;
        const uint32_t tag = (lds32(sb + SM_MISC + 16) + 1) << 30;
        if (lane < 16) st_rlx(pub_ptr(p, blockIdx.x, lane >> 3) + (lane & 7), tag | (bits & 0xffu));
        constexpr int K = (NCTA + 31) / 32;
        __nanosleep(CFG_P0);
        uint32_t v[K], bad;
        int guard = 0;
        do {
            bad = 0;
#pragma unroll
            for (int k = 0; k < K; k++) {
                const int b = min(lane + 32 * k, NCTA - 1);
                v[k] = ld_rlx(pub_ptr(p, b, near >> (b / 44) & 1));
                bad |= v[k] ^ tag;
            }
            bad = __any_sync(0xffffffffu, bad >> 30);
            if (bad) __nanosleep(CFG_PSLEEP);
            if (++guard > GUARD) __trap();
        } while (bad);
#pragma unroll
        for (int k = 0; k < K; k++) sts32(sb + SM_PUB + (lane + 32 * k) * 4, v[k]);
    }
    __syncwarp();
    constexpr int NP = NCTA / 2, NTAB = H2 + H3;
    const int me = blockIdx.x >> 1, odd = blockIdx.x & 1;
    uint32_t pp[3], key[3];
    int n1 = 0;
#pragma unroll
    for (int k = 0; k < 3; k++) {
        const int i = lane + 32 * k;
        pp[k] = lds32(sb + SM_PUB + min(i, NP - 1) * 8) & 1;
        key[k] = (i * CFG_KM % CFG_KN) << 8 | i;
        n1 += 2 * __popc(__ballot_sync(0xffffffffu, i < NP && pp[k]));
    }
    bool fixed = n1 < NTAB || NCTA - n1 < NTAB;
    if (fixed) {
        n1 = NP / 2 * 2;
        pp[0] = pp[1] = pp[2] = lane & 1;
    }
    const uint32_t mine = __shfl_sync(0xffffffffu, (me < 32 ? key[0] : me < 64 ? key[1] : key[2]) * 2 + (me < 32 ? pp[0] : me < 64 ? pp[1] : pp[2]), me & 31);
    const int part = mine & 1;
    int pos = odd;
#pragma unroll
    for (int k = 0; k < 3; k++) pos += 2 * __popc(__ballot_sync(0xffffffffu, lane + 32 * k < NP && pp[k] == (uint32_t)part && key[k] < mine / 2));
    const int role = pos < H2 ? 1 : pos < NTAB ? 2 : 0;
    const int id = pos < H2 ? part * H2 + pos : pos < NTAB ? part * H3 + pos - H2 : (part ? NCTA - n1 - NTAB : 0) + pos - NTAB;
    const uint32_t v = lds32(sb + SM_PUB + lane * 4);
    uint32_t lin = 0;
#pragma unroll
    for (int b = 0; b < 6; b++) lin |= (__popc(__ballot_sync(0xffffffffu, (v >> (b + 1)) & 1)) > 16 ? 1u : 0u) << b;
    if (lane == 0) {
        sts32(sb + SM_MISC, role << 8 | id);
        sts32(sb + SM_MISC + 4, lin);
        sts32(sb + SM_MISC + 8, NCTA - n1 - NTAB);
        sts32(sb + SM_MISC + 20, part);
        sts32(sb + SM_MISC + 12, role == 0 ? id : role == 1 ? N1 + id : N1 + N2 + id);
    }
}
__device__ __forceinline__ uint32_t sel_of(uint32_t sb, int widx, uint32_t k, int part) {
    return (__popc(k & lds32(sb + SM_MISC + 4)) ^ (lds32(sb + SM_PUB + widx * 4) >> 7) ^ part) & 1;
}
__device__ __forceinline__ uint32_t gran_off(uint32_t sb, int widx, int k, int part) { return (2 * k + sel_of(sb, widx, k, part)) << 12; }
__device__ __forceinline__ uint32_t q1a_off(uint32_t sb, int src, int blk, int part) { return gran_off(sb, 2 * blk + part, src >> 1, part) + (src & 1) * 2048; }
__device__ __forceinline__ uint32_t q1h_off(uint32_t sb, int src, int blk, int part) { return gran_off(sb, 2 * blk + part, 32 + (src >> 2), part) + (src & 3) * 1024; }
__device__ __forceinline__ uint32_t* ctl_word(const Params& p, uint32_t sb, int k, int word, int part) {
    const int widx = CWIN + lds32(sb + SM_MISC + 16);
    return (uint32_t*)(p.ring + (widx * WIN + ((2 * k + sel_of(sb, widx, k, part)) << 12))) + word;
}
__device__ __forceinline__ uint32_t* cred1_of(const Params& p, uint32_t sb, int src) { return ctl_word(p, sb, src >> 3, (src & 7) * 128, src >= (int)lds32(sb + SM_MISC + 8)); }
__device__ __forceinline__ uint32_t* fin1_of(const Params& p, uint32_t sb, int dst) { return ctl_word(p, sb, 8 + (dst >> 3), (dst & 7) * 128, dst / H2); }
__device__ __forceinline__ uint32_t* cred2_of(const Params& p, uint32_t sb, int src) { return ctl_word(p, sb, 16 + (src >> 3), (src & 7) * 128, src / H2); }
__device__ __forceinline__ uint32_t* fin2_of(const Params& p, uint32_t sb, int dst) { return ctl_word(p, sb, 24 + (dst >> 3), (dst & 7) * 128, dst / H3); }
__device__ __forceinline__ uint32_t* rdy_of(const Params& p, uint32_t sb, int word, int part) { return ctl_word(p, sb, 28, word, part); }
__device__ __forceinline__ uint32_t q2_off(uint32_t sb, int blk, int dst) {
    return (N2 + dst) * WIN + gran_off(sb, N2 + dst, (blk >> 1) * 4 + (blk & 1), dst / H3);
}
template <bool IS1>
__device__ __forceinline__ void clear_queues(const Params& p, uint32_t sb, int id, int lane) {
    constexpr int NA = (N1 + 1) / 2, NG = NA + (N1 + 3) / 4, N = IS1 ? NG * N2 : NI * 2;
    if (IS1) {
#pragma unroll 1
        for (int k = 0; k < 8; k++) sts128(sb + SM_ZERO + (k * 32 + lane) * 16, make_uint4(0, 0, 0, 0));
        if (lane == 0) spin_ge(rdy_of(p, sb, 320, lds32(sb + SM_MISC + 20)), NTAIL);
    }
    __syncwarp();
    fence_async_smem();
    for (int k = IS1 ? id + (lane < CFG_CLN ? lane : N) * N1 : lane; k < N; k += IS1 ? CFG_CLN * N1 : 32) {
        if (IS1 && k >= CFG_CLN * N1) __nanosleep(CFG_CLS);
        const int wi = k / NG, g = k - wi * NG;
        const uint32_t off = IS1 ? wi * WIN + gran_off(sb, wi, g < NA ? g : 32 + g - NA, wi & 1) : q2_off(sb, k >> 1, id) + (k & 1) * 16384;
        bulk_store(p.ring + off, sb + SM_ZERO, 4096);
    }
    asm volatile("cp.async.bulk.commit_group;" ::: "memory");
    asm volatile("cp.async.bulk.wait_group 0;" ::: "memory");
    TR(21, IS1 && lane == 0);
    if (!IS1) {
        fence_async_all();
        __syncwarp();
        fence_gpu();
        if (lane < NI) red_rlx(rdy_of(p, sb, id / H3 * H2 + lane, id / H3), 1u);
    }
    __syncwarp();
}

struct In8 { uint4 a[2], o[2]; uint2 g[2]; };
__device__ __forceinline__ void p1_load(const Params& p, In8& r, int i4) {
#pragma unroll
    for (int u = 0; u < 2; u++) {
        [[maybe_unused]] uint32_t x, y;
        asm volatile("tex.1d.v4.u32.s32 {%0,%1,%2,%3}, [%4, {%5}];" : "=r"(r.a[u].x), "=r"(r.a[u].y), "=r"(r.a[u].z), "=r"(r.a[u].w) : "l"(p.t_in), "r"(i4 + u * 32));
        asm volatile("tex.1d.v4.u32.s32 {%0,%1,%2,%3}, [%4, {%5}];" : "=r"(r.o[u].x), "=r"(r.o[u].y), "=r"(r.o[u].z), "=r"(r.o[u].w) : "l"(p.t_out), "r"(i4 + u * 32));
        asm volatile("tex.1d.v4.u32.s32 {%0,%1,%2,%3}, [%4, {%5}];" : "=r"(r.g[u].x), "=r"(r.g[u].y), "=r"(x), "=r"(y) : "l"(p.t_ang), "r"(i4 + u * 32));
    }
}
__device__ __forceinline__ uint32_t imad(uint32_t a, uint32_t b, uint32_t c) {
    uint32_t r;
    asm("mad.lo.u32 %0, %1, %2, %3;" : "=r"(r) : "r"(a), "r"(b), "r"(c));
    return r;
}
__device__ __forceinline__ unsigned char* ring_ptr(const Params& p, uint32_t lo) {
    uint64_t r;
    asm("mov.b64 %0, {%1, %2};" : "=l"(r) : "r"(lo), "r"(p.ring_hi));
    return (unsigned char*)r;
}
__device__ __forceinline__ uint32_t keep32(uint32_t x) {
    return __shfl_sync(0xffffffffu, x, threadIdx.x & 31);
}
__device__ __forceinline__ uint32_t opaque32(uint32_t x) {
    asm volatile("" : "+r"(x));
    return x;
}
template <typename T> __device__ __forceinline__ T* opaque(T* p) {
    asm volatile("" : "+l"(p));
    return p;
}
template <int LUT> __device__ __forceinline__ uint32_t lop3(uint32_t a, uint32_t b, uint32_t c) {
    uint32_t r;
    asm("lop3.b32 %0, %1, %2, %3, %4;" : "=r"(r) : "r"(a), "r"(b), "r"(c), "n"(LUT));
    return r;
}
__device__ __forceinline__ uint32_t dp4(uint32_t a, uint32_t b, uint32_t c) {
    uint32_t r;
    asm("dp4a.u32.u32 %0, %1, %2, %3;" : "=r"(r) : "r"(a), "r"(b), "r"(c));
    return r;
}
__device__ __forceinline__ uint32_t dp2(uint32_t a, uint32_t b, uint32_t c) {
    uint32_t r;
    asm("dp2a.lo.u32.u32 %0, %1, %2, %3;" : "=r"(r) : "r"(a), "r"(b), "r"(c));
    return r;
}
__device__ __forceinline__ void p1_put(uint32_t sb, uint32_t wa, uint32_t wb, uint32_t old, bool on) {
    asm volatile("{.reg .pred q; setp.ne.u32 q, %3, 0; @q st.shared.v2.u32 [%0], {%1,%2};}"
                 ::"r"(sb + A_ST + prmt(old, wb, 0xf762)), "r"(wa), "r"(prmt(wb, old, 0x7210)), "r"((uint32_t)on) : "memory");
}
__device__ __forceinline__ void p1_slow_tile(const Params& p, uint32_t sb, int i4) {
    const float f = __bfloat162float(p.freq[0]);
#pragma unroll 1
    for (int u = 0; u < 8; u++) {
        const int k4 = i4 + (u >> 2) * 32;
        if (k4 < p.n4) {
            const size_t t = (size_t)k4 * 4 + (u & 3);
            const float x = __bfloat162float(__float2bfloat16(f * __bfloat162float(p.angle[t])));
            slow_add(p.m, sb, p.idx_in[t], p.idx_out[t], __bfloat162float(__float2bfloat16(cosf(x))));
        }
    }
}
__device__ __forceinline__ void role_p1(const Params& p, uint32_t sb, int id, int w, int lane) {
    lane = keep32(lane);
    const uint32_t f2 = (uint32_t)__bfloat16_as_ushort(p.freq[0]) * 0x10001u;
    constexpr int TG = CFG_TG, NTK = P1W;
    static_assert(NTK <= 16, "tickets");
    const int tc = (w + id) % NTK, first = (N1 * P1W + tc) * (TG * 64);
    uint32_t* const tickets = opaque(ctl_word(p, sb, 29 + tc / 8, tc % 8 * 128 + lane, tc & 1));
    auto draw = [&]() {
        uint32_t t = 0;
        asm volatile("{.reg .pred q; setp.eq.u32 q, %2, 0; @q atom.relaxed.gpu.global.add.u32 %0, [%1], 1;}" : "+r"(t) : "l"(tickets), "r"(lane) : "memory");
        return t;
    };
    int i4 = (id * P1W + w) * (TG * 64);
    In8 r;
    ACC_DECL
    uint32_t tk = draw();
    p1_load(p, r, i4 + lane);
    while (i4 < p.n4) {
        const int cur = i4;
        i4 += 64;
        if (i4 % (TG * 64) == 0) {
            i4 = min(__shfl_sync(0xffffffffu, tk, 0), 0x7fffffffu / (NTK * TG * 64) - N1 * P1W / NTK - 2) * (NTK * TG * 64) + first;
            tk = draw();
        }
        uint32_t wa[8], wb[8], x2[4];
        x2[0] = mul_bf2(r.g[0].x, f2); x2[1] = mul_bf2(r.g[0].y, f2);
        x2[2] = mul_bf2(r.g[1].x, f2); x2[3] = mul_bf2(r.g[1].y, f2);
        const uint32_t mx = maxabs_bf2(maxabs_bf2(x2[0], x2[1]), maxabs_bf2(x2[2], x2[3]));
        const bool fast = __all_sync(0xffffffffu, cur + 64 <= p.n4 && ((mx & 0x7fffu) <= 0x4300u) && ((mx & 0x7fff0000u) <= 0x43000000u));
        {
            const uint32_t in[8] = {r.a[0].x, r.a[0].y, r.a[0].z, r.a[0].w, r.a[1].x, r.a[1].y, r.a[1].z, r.a[1].w};
            const uint32_t ou[8] = {r.o[0].x, r.o[0].y, r.o[0].z, r.o[0].w, r.o[1].x, r.o[1].y, r.o[1].z, r.o[1].w};
#pragma unroll
            for (int j = 0; j < 8; j += 2) {
                const uint32_t ch = mul_h2(pack_h2(__cosf(bflo(x2[j >> 1])), __cosf(bfhi(x2[j >> 1]))), 0x24002400u);
#pragma unroll
                for (int k = j; k < j + 2; k++) {
                    const uint32_t blk = __umulhi(in[k], p.magic2), il = imad(blk, p.nrows2, in[k]);
                    wa[k] = k & 1 ? bitsel(ch, il, 0xffff0000u) : imad(ch, 65536u, il);
                    wb[k] = imad(blk, 1u << 21, imad(ou[k] >> 5, 1u - (1u << 21), ou[k] << 16));
                }
            }
        }
        p1_load(p, r, i4 + lane);
        if (fast) {
            uint32_t old[8], any = 0;
#pragma unroll
            for (int j = 0; j < 8; j++) old[j] = atoms_add(dp2(wb[j], 0x400u, 0u) + (sb + A_CNT), 0x80001u);
#pragma unroll
            for (int j = 0; j < 8; j++) any |= old[j];
            if (!__any_sync(0xffffffffu, any & 0xffe0u)) {
#pragma unroll
                for (int j = 0; j < 8; j++) p1_put(sb, wa[j], wb[j], old[j], true);
            } else {
                uint32_t pend = 0;
#pragma unroll
                for (int j = 0; j < 8; j++) { p1_put(sb, wa[j], wb[j], old[j], !(old[j] & 0xffe0u)); if (old[j] & 0xffe0u) pend |= 1u << j; }
                ACC(0, 1)
                for (int guard = 0; __any_sync(0xffffffffu, pend); guard++) {
                    __nanosleep(CFG_BSLEEP);
                    ACC(1, 1)
#pragma unroll
                    for (int j = 0; j < 8; j++) {
                        if (__any_sync(0xffffffffu, pend >> j & 1)) {
                            const uint32_t c = lds32v(sb + A_CNT + (pend >> j & 1 ? wb[j] >> 16 : 0) * 4);
                            const bool go = (pend >> j & 1) && (((old[j] >> 19) - (c >> 19) + c) & 8191u) < 32u;
                            p1_put(sb, wa[j], wb[j], old[j], go);
                            if (go) pend &= ~(1u << j);
                        }
                    }
                    if (guard > GUARD) __trap();
                }
            }
        } else {
            p1_slow_tile(p, sb, cur + lane);
            __syncwarp();
        }
    }
    __syncwarp();
    mbar_arrive_if(sb + SM_DONE, lane == 0);
    ACC_SAVE
}

__device__ __forceinline__ void role_flush(const Params& p, uint32_t sb, int id, int f, int lane) {
    lane = keep32(lane);
    const int half = lane >> 4, o = lane >> 2, q = lane & 3;
    const uint32_t hm = keep32(half ? 0xffff0000u : 0xffffu), lth = keep32(((1u << lane) - 1) & hm);
    const uint32_t list = sb + A_LIST + f * LISTB, cnt = keep32(sb + A_CNT + (f * GPW * 32 + lane) * 4);
    const uint32_t cred = opaque32(sb + SM_CRED + (half * 32 + f * GPW) * 4);
    const uint32_t pa = opaque32(p.ring_lo + (id >> 1) * 8192 + (id & 1) * 2048 + q * 16);
    const uint32_t ph = opaque32(p.ring_lo + (32 + (id >> 2)) * 8192 + (id & 3) * 1024 + q * 8 - 2048);
    const uint32_t sa = q * 16 + (o & 1) * 64;
    uint32_t qo[GPW], hs[GPW], cr[4] = {0, 0, 0, 0};
#pragma unroll
    for (int g = 0; g < GPW; g++) {
        const int blk = f * GPW + g;
        qo[g] = 32u << 25;
        const uint32_t sa = sel_of(sb, 2 * blk + half, id >> 1, half), sh = sel_of(sb, 2 * blk + half, 32 + (id >> 2), half);
        hs[g] = sa << 31 | (2 * sh + 1 - sa) << 22 | 1u << 24 | (lane & 15) << 15 | (blk * 32 + lane) * 2;
    }
    uint4 x[KR] = {}, y[KR] = {};
    uint32_t c[GPW] = {};
    auto scan = [&]() {
#pragma unroll
        for (int g = 0; g < GPW; g++) c[g] = lds32v(cnt + g * 128);
    };
    auto credits = [&]() {
        if (GPW == 4) { const uint4 v = lds128(cred); cr[0] = v.x; cr[1] = v.y; cr[2] = v.z; cr[3] = v.w; }
        else { const uint2 v = lds64v(cred); cr[0] = v.x; cr[1] = v.y; }
    };
    ACC_DECL
    int guard = 0;
    bool idle = false, done = false;
    while (true) {
        uint32_t fr[GPW], rank[GPW], num = 0, left = 0;
        bool ok[GPW];
        if (idle && !done && __all_sync(0xffffffffu, mbar_test(sb + SM_DONE, 0))) {
            done = true;
            TR(17, f == 0 && lane == 0);
#pragma unroll
            for (int g = 0; g < GPW; g++) {
                const uint32_t u = lds32v(cnt + g * 128) & 31u, hd = hs[g] ^ (u & 16u ? imad(hs[g], 1u << 24, 1u) & 0x01000001u : 0u);
#pragma unroll 2
                for (uint32_t j = 0, k; k = (j + lane) & 15u, j < 16; j++)
                    sts64_if(sb + A_ST + ((hd & 0x7ffu) << 7) + k * 8, p.rows2, (lane * 16 + k) | (hd & 0x1000000u), (u & 15u) && k >= (u & 15u));
                reds_add(cnt + g * 128, ((0u - u) & 15u) * 0x80001u);
            }
            __syncwarp();
            scan();
        }
#pragma unroll
        for (int g = 0; g < GPW; g++) {
            const bool isfull = c[g] & 0xfff0u;
            rank[g] = __popc(__ballot_sync(0xffffffffu, isfull) & lth);
            ok[g] = isfull && (int)(rank[g] << 25) < (int)(cr[g] - qo[g] + (63u << 25));
            ACC(2, __popc(__ballot_sync(0xffffffffu, isfull && !ok[g])))
        }
#pragma unroll
        for (int g = 0; g < GPW; g++) {
            const uint32_t m = __ballot_sync(0xffffffffu, ok[g]), n = __popc(m & hm), all = __popc(m), e = num + rank[g] + (half ? all - n : 0u);
            sts32_if(KR == 2 ? list + (e & 48u) * 4 + (e & 7u) * 8 + (e >> 1 & 4u) : imad(e, 4u, list), bitsel(imad(rank[g], 1u << 25, qo[g]), hs[g], 0x7e000000u), ok[g]);
            if (ok[g]) hs[g] ^= imad(hs[g], 1u << 24, 1u) & 0x01000001u;
            fr[g] = ok[g] ? 0u - 16u : 0u;
            left |= c[g] + fr[g];
            qo[g] = imad(n, 1u << 25, qo[g]);
            num += all;
        }
        __syncwarp();
        ACC(0, 1) ACC(1, num)
        if (num) {
            uint32_t la = list + o * (KR == 2 ? 8 : 4);
            int todo = (int)num - o, rest = num;
            do {
                uint32_t d[KR];
                if (KR == 2) { const uint2 v = lds64v(la); d[0] = v.x; d[KR - 1] = v.y; }
                else {
#pragma unroll
                    for (int k = 0; k < KR; k++) d[k] = lds32v(la + 32 * k);
                }
                while (true) {
                    uint32_t bad = 0;
#pragma unroll
                    for (int k = 0; k < KR; k++) {
                        const uint32_t m = d[k] & 0x7ffu;
                        lds128_keep(x[k], imad(m, 128u, sa) + (sb + A_ST), todo > 8 * k);
                        lds128_keep(y[k], imad(m, 128u, sa ^ 64) + (sb + A_ST), todo > 8 * k);
                    }
#pragma unroll
                    for (int k = 0; k < KR; k++)
                        or3_if(bad, lop3<0x7e>(x[k].y, x[k].w, d[k]), lop3<0x7e>(y[k].y, y[k].w, d[k]), todo > 8 * k);
                    if (!__any_sync(0xffffffffu, (int)imad(bad, 128u, 0u) < 0)) break;
                    if (++guard > GUARD) __trap();
                }
#pragma unroll
                for (int k = 0; k < KR; k++) {
                    const uint32_t mi = d[k] & 0x7e0u, dm = d[k] & 0xbec00000u;
                    x[k].x = bitsel(d[k], x[k].x, 0x40078000u);
                    x[k].y = prmt(x[k].y, x[k].w, 0x5410);
                    x[k].w = prmt(y[k].y, y[k].w, 0x5410);
                    y[k].x = bitsel(d[k], y[k].x, 0x40000000u);
                    y[k].y = y[k].z;
                    stg_q128(ring_ptr(p, dp4(dm, 0x20000000u, imad(mi, WIN / 32, pa))), x[k].x, x[k].y, x[k].z, x[k].w, X_ST1 todo > 8 * k);
                    stg_q64(ring_ptr(p, dp4(dm, 0x10200000u, imad(mi, WIN / 32, ph))), y[k].x, y[k].y, X_ST1 todo > 8 * k);
                }
                la += 32 * KR;
                todo -= 8 * KR;
                rest -= 8 * KR;
            } while (rest > 0);
#pragma unroll
            for (int g = 0; g < GPW; g++) c[g] = atoms_add(cnt + g * 128, fr[g]) + fr[g];
            credits();
            idle = num <= CFG_TH;
            if (done && !__any_sync(0xffffffffu, left & 0xffffu)) break;
            if (idle) { __nanosleep(CFG_TS); scan(); credits(); }
        } else {
            if (done && !__any_sync(0xffffffffu, left & 0xffffu)) break;
            idle = true;
            __nanosleep(CFG_FSLEEP);
            scan();
            credits();
            if (++guard > GUARD) __trap();
        }
    }
#pragma unroll
    for (int g = 0; g < GPW; g++) st_rlx_if(fin1_of(p, sb, half * H2 + f * GPW + g) + id, qo[g] - (32u << 25) + 1u, (lane & 15) == 0 && f * GPW + g < NI);
    mbar_arrive_if(sb + SM_DONE2, lane == 0);
    TR(18, f == 0 && lane == 0);
    ACC_SAVE
}
__device__ __forceinline__ void role_credit1(const Params& p, uint32_t sb, int id, int lane) {
    const uint32_t* const cred = cred1_of(p, sb, id) + lane * 2;
    for (int guard = 0; !__all_sync(0xffffffffu, mbar_test(sb + SM_DONE2, 0)); guard++) {
        const uint2 v = ldg_q64(cred);
        sts64(sb + SM_CRED + lane * 8, v.x, v.y);
        __nanosleep(CFG_C1SLEEP);
        if (guard > GUARD) __trap();
    }
}

__device__ __forceinline__ float h2f(uint32_t h) {
    float f;
    asm("{.reg .b16 t; cvt.u16.u32 t, %1; cvt.f32.f16 %0, t;}" : "=f"(f) : "r"(h));
    return f;
}
__device__ __forceinline__ void p2_slow(const Params& p, uint32_t sb, const uint32_t* tmp, int row0, uint32_t dst) {
#pragma unroll 1
    for (int j = 0; j < 4; j++)
        if (tmp[8 + j] & 0x40u) slow_add(p.m, sb, row0 + (tmp[j] & 0x7fffu), (tmp[4 + j] & 0x7fffu) * 32 + dst, h2f(tmp[j] >> 16) * 64.0f);
}
__device__ __forceinline__ uint32_t mul_h2_hi(uint32_t a, uint32_t b) {
    uint32_t r;
    asm("{.reg .b16 l, h; .reg .b32 t; mov.b32 {l, h}, %2; mov.b32 t, {h, h}; mul.rn.f16x2 %0, %1, t;}" : "=r"(r) : "r"(a), "r"(b));
    return r;
}
template <bool CHECK>
__device__ __forceinline__ void role_p2(const Params& p, uint32_t sb, int id, int w, int lane) {
    lane = keep32(lane);
    const int part = id / H2, blk = id - part * H2, row0 = blk * p.rows2;
    const int o = lane >> 2, q = lane & 3;
    uint32_t* const cbase = (uint32_t*)(p.ring + (CWIN + lds32(sb + SM_MISC + 16)) * WIN);
    const uint32_t cred = opaque32((uint32_t)(uintptr_t)(cbase + part * 32 + blk));
    const uint32_t pa = opaque32(p.ring_lo + (2 * blk + part) * WIN + q * 16), ph = opaque32(pa - q * 8);
    const uint32_t po = opaque32(p.ring_lo + (q2_off(sb, blk, part * H3) & ~4096u) + q * 16 + (o & 1) * 64);
    const uint32_t sel = __ballot_sync(0xffffffffu, q2_off(sb, blk, part * H3 + (lane & 15)) & 4096u) << 12;
    const uint32_t* const fins = fin1_of(p, sb, id);
    uint32_t st[QPW] = {}, sq[QPW] = {};
    uint4 qa[NBT];
    uint2 qh[NBT];
    auto load = [&](int k) {
        qa[k] = ldg_q128(ring_ptr(p, pa + (bitsel(sq[k], st[k] >> 19, 0x7f800u) & 0x7ffc0u)));
        qh[k] = ldg_q64(ring_ptr(p, ph + (bitsel(sq[k] >> 9, st[k] >> 20, 0x7fc00u) & 0x7ffe0u)));
    };
#pragma unroll
    for (int k = 0; k < QPW; k++) {
        const int src = w * QPW + k;
        st[k] = o << 25 | (src < N1 ? 1u : 5u);
        sq[k] = src < N1 ? q1h_off(sb, src, blk, part) << 9 | q1a_off(sb, src, blk, part) | (uint32_t)(cred1_of(p, sb, src) - cbase) / 8 : 0x7e000u * 513u;
    }
#pragma unroll
    for (int k = 0; k < NBT; k++) load(k);
    ACC_DECL
    int guard = 0;
    uint32_t streak = 0;
    while (true) {
        uint32_t nn[NBT], xx[NBT][4], hh[NBT][2], dd[NBT], any = 0;
        bool last = false;
#pragma unroll
        for (int k = 0; k < NBT; k++) {
            const uint4 a = qa[k];
            const uint2 h = qh[k];
            uint32_t n = 8;
            const uint32_t miss = __ballot_sync(0xffffffffu, (int)imad((a.x ^ st[k]) & (h.x ^ st[k]), 2u, 0u) >= 0);
            if (miss) {
                n = (__ffs(miss) - 1) >> 2;
                if (!__any_sync(0xffffffffu, st[k] & 8u)) { if (streak < CFG_PSTREAK) n &= CFG_PMASK; }
                else if (!__any_sync(0xffffffffu, ((st[k] >> 6) + ((n - o) << 19) ^ st[k]) & 0x1f80000u)) { st[k] |= 4u; last = true; }
            }
            ACC(1, n == 0) ACC(2, n != 0) ACC(3, n)
            st[k] = imad(n, 1u << 25, st[k]);
            st_rlx_if((uint32_t*)ring_ptr(p, imad(sq[k] & 0x7f0u, 32u, cred)), st[k], X_CR1 lane == 0 && n && (n < 8 || !(st[k] & CFG_CRM << 28)));
            xx[k][0] = bitsel(a.x, 0x00040000u, 0xbff87fffu); xx[k][1] = a.z; xx[k][2] = h.x & 0xbfffffffu; xx[k][3] = h.y;
            hh[k][0] = a.y; hh[k][1] = a.w; dd[k] = a.x >> 13 & 0x3cu; nn[k] = n;
            any |= n;
        }
        if (!any) {
#pragma unroll
            for (int k = 0; k < QPW; k++) {
                const uint32_t fin = ld_rlx(fins + ((sq[k] >> 12 & 62u) | (sq[k] >> 11 & 1u)));
                if (fin & 1u) st[k] |= (fin >> 6 & 0x1f80000u) | ((fin ^ (st[k] - (o << 25))) >> 25 ? 8u : 12u);
            }
            last = true;
            if (++guard > GUARD) __trap();
            streak++;
        } else streak = 0;
        if (last) {
            uint32_t all = 4u;
#pragma unroll
            for (int k = 0; k < QPW; k++) all &= st[k];
            last = __all_sync(0xffffffffu, all);
        }
        {
            uint32_t t[QPW], u[QPW];
#pragma unroll
            for (int k = 0; k < QPW; k++) { t[k] = st[(k + NBT) % QPW]; u[k] = sq[(k + NBT) % QPW]; }
#pragma unroll
            for (int k = 0; k < QPW; k++) { st[k] = t[k]; sq[k] = u[k]; }
        }
#pragma unroll
        for (int k = 0; k < NBT; k++) load(k);
#pragma unroll
      for (int k = 0; k < NBT; k++) {
        if (nn[k]) {
            const uint32_t* const x = xx[k];
            const uint32_t h0 = hh[k][0], h1 = hh[k][1], d4 = dd[k];
            const bool v = o < nn[k];
            uint32_t old = 0, ta[4], tb[4], w0[4], w1[4];
            atoms_add_keep(old, sb + SM_CNT2 + d4, 0x10001u, q == 0 && v);
#pragma unroll
            for (int j = 0; j < 4; j++) {
                ta[j] = lds32nv(dp2(x[j], 4u, 0u) + (sb + B_TA));
                tb[j] = lds16nv(dp2(x[j], 2u, 0u) + (sb + B_TB));
            }
            old = __shfl_sync(0xffffffffu, old, lane & 28);
            const uint32_t tag = old << 8 & 0x40000000u;
#pragma unroll
            for (int j = 0; j < 4; j++) {
                const uint32_t z = prmt(j & 2 ? h1 : h0, 0, j & 1 ? 0x4342 : 0x4140);
                const uint32_t t23 = prmt((ta[j] & 0x60076007u) * 2050u, tb[j], 0x5341) & 0xfffcffffu;
                w0[j] = (imad(z, 128u, j & 1 ? 0u : tag) & 0x78007800u) | mul_h2_hi(ta[j] & 0x9ff89ff8u, x[j]);
                w1[j] = (imad(z, 2048u, 0u) & 0x78007800u) | mul_h2_hi(t23, x[j]);
            }
            if (CHECK && v && ((tb[0] | tb[1] | tb[2] | tb[3]) & 0x40u)) {
                uint32_t tmp[12];
#pragma unroll
                for (int j = 0; j < 4; j++) {
                    tmp[j] = x[j]; tmp[4 + j] = (j & 2 ? h1 : h0) >> (j & 1 ? 16 : 0); tmp[8 + j] = tb[j];
                    if (tb[j] & 0x40u) { w0[j] &= 0x78007800u; w1[j] &= 0x78007800u; }
                }
                p2_slow(p, sb, tmp, row0, part * H3 + d4 / 4);
            }
            const uint32_t off = (bitsel(old >> 9, old >> 7, 0x0f80u) & 0x4f80u) + imad(d4, WIN / 4, (sel >> (d4 / 4) & 4096u) + po);
            bool wait = old & (0x10000u - NQ2);
            if (!__any_sync(0xffffffffu, wait)) {
                stg_q128(ring_ptr(p, off), w0[0], w1[0], w0[1], w1[1], X_ST2 v);
                stg_q128(ring_ptr(p, off ^ 64u), w0[2], w1[2], w0[3], w1[3], X_ST2 v);
            } else {
                bool pend = v;
                ACC(0, 1)
                for (int g2 = 0;; g2++) {
                    stg_q128(ring_ptr(p, off), w0[0], w1[0], w0[1], w1[1], pend && !wait);
                    stg_q128(ring_ptr(p, off ^ 64u), w0[2], w1[2], w0[3], w1[3], pend && !wait);
                    pend = wait;
                    if (!__any_sync(0xffffffffu, pend)) break;
                    __nanosleep(CFG_BSLEEP);
                    const uint32_t c = lds32v(sb + SM_CNT2 + d4);
                    wait = pend && (((old >> 16) - (c >> 16) + c) & 0xffffu) >= NQ2;
                    if (g2 > GUARD) __trap();
                }
            }
        }
      }
        if (last) break;
    }
    TR(17, w == 0 && lane == 0);
    __syncwarp();
    uint32_t rank = 0;
    if (lane == 0) { __threadfence_block(); rank = atoms_add(sb + SM_FIN, 1u); __threadfence_block(); }
    if (__shfl_sync(0xffffffffu, rank, 0) == P2W - 1 && lane < 16)
        st_rlx(fin2_of(p, sb, part * H3 + lane) + blk, FIN | (((lds32v(sb + SM_CNT2 + lane * 4) >> 16) - NQ2) & 0xffffu));
    __syncwarp();
    mbar_arrive_if(sb + SM_DONE, lane == 0);
    ACC_SAVE
}
__device__ __forceinline__ void role_credit(const Params& p, uint32_t sb, int id, int lane) {
    const uint32_t* const cred = cred2_of(p, sb, id) + (lane & 15);
    uint32_t last = 0;
    for (int guard = 0;; guard++) {
        if (__all_sync(0xffffffffu, mbar_test(sb + SM_DONE, 0))) break;
        const uint32_t c = ld_rlx(cred);
        if (lane < 16 && c != last) reds_add(sb + SM_CNT2 + lane * 4, 0u - ((c - last) & 0xffffu));
        last = c;
        __nanosleep(CFG_CSLEEP);
        if (guard > GUARD) __trap();
    }
}

__device__ __forceinline__ void p3_wrap(uint32_t sb, int id, const uint32_t* tmp) {
    const Scale sc = get_scale(sb);
#pragma unroll 1
    for (int j = 0; j < 8; j++) {
        const uint32_t old = tmp[4 + j], v = tmp[12 + j], nw = old + v, t = (old ^ nw) & (v ^ nw);
        if (t & 0x80008000u) {
            const float k = (t & 0x8000u) ? ((v & 0x8000u) ? -1.0f : 1.0f) : 0.0f;
            const float q = (t & 0x80000000u) ? ((int)v < 0 ? -65536.0f : 65536.0f) : 0.0f;
            const uint32_t e0 = (j & 1) ? sc.eb[2] : sc.eb[0], e1 = (j & 1) ? sc.eb[3] : sc.eb[1];
            const float lo = k * 65536.0f * __uint_as_float((e0 - 10) << 23), hi = (q - k) * __uint_as_float((e1 - 10) << 23);
            if (j & 1) sg_add(tmp[j >> 1] * 32 + id, 0.f, 0.f, lo, hi);
            else sg_add(tmp[j >> 1] * 32 + id, lo, hi, 0.f, 0.f);
        }
    }
}
__device__ __forceinline__ uint32_t p3_val(uint32_t w) {
    const uint32_t mk = prmt(w, 0, 0xBB99);
    return ((w & 0x07ff07ffu) ^ mk) - mk;
}
__device__ __forceinline__ void role_p3(const Params& p, uint32_t sb, int id, int w, int lane) {
    lane = keep32(lane);
    uint32_t* const cred = opaque(cred2_of(p, sb, id / H3 * H2 + w) + id % H3);
    const uint32_t pq = opaque32(p.ring_lo + q2_off(sb, w, id) + lane * 16);
    auto off = [&](uint32_t n) { return (n & 1u) << 11 | (n & 2u) << 13; };
    const uint32_t pp = opaque32(pq - lane * 16 + 112);
    const uint32_t* const finp = opaque(fin2_of(p, sb, id) + w);
    auto tag_of = [&](uint32_t n) { return ~n << 28; };
    uint32_t n = 0, fin = 0, pr = 0, pk = 0;
    uint4 v[4] = {};
    bool have = false, last = false;
    ACC_DECL
    int guard = 0;
    while (true) {
        const uint32_t ex = tag_of(n);
        const bool ok = have && !__any_sync(0xffffffffu, ((v[0].x ^ ex) | (v[1].x ^ ex) | (v[2].x ^ ex) | (v[3].x ^ ex)) & 0x40000000u);
        if (ok) n++;
        const bool ready = (ok || !have) && __all_sync(0xffffffffu, !((pr ^ tag_of(n)) & 0x40000000u));
        st_rlx_if(cred, n * 16, X_CR2 lane == 0 && ok);
        if (!ok && !ready && __all_sync(0xffffffffu, fin & FIN)) {
            const uint32_t left = __shfl_sync(0xffffffffu, (fin - n * 16) & 0xffffu, 0);
            if (left - 1u > 0x8000u) break;
            if (left < 16u) {
#pragma unroll
                for (int u = 0; u < 4; u++) {
                    v[u] = make_uint4(ex & 0x40000000u, 0, 0, 0);
                    ldq128_keep(v[u], ring_ptr(p, pq + off(n)) + u * 512, u * 4 + (lane >> 3) < left);
                }
                have = last = !__any_sync(0xffffffffu, ((v[0].x ^ ex) | (v[1].x ^ ex) | (v[2].x ^ ex) | (v[3].x ^ ex)) & 0x40000000u);
                pr = ~tag_of(n + have);
                if (++guard > GUARD) __trap();
                continue;
            }
        }
        uint32_t row[8], val[16];
#pragma unroll
        for (int u = 0; u < 4; u++) {
            const uint4 x = v[u];
            row[2 * u] = prmt(bitsel(x.x << 1, x.y >> 3, 0x7000f000u), 0, 0x4431);
            row[2 * u + 1] = prmt(bitsel(x.z << 1, x.w >> 3, 0x7000f000u), 0, 0x4431);
            val[4 * u] = p3_val(x.x); val[4 * u + 1] = p3_val(x.y);
            val[4 * u + 2] = p3_val(x.z); val[4 * u + 3] = p3_val(x.w);
        }
#pragma unroll
        for (int u = 0; u < 4; u++) ldq128_keep(v[u], ring_ptr(p, pq + off(n)) + u * 512, ready);
        pk = ready ? CFG_PK1 * 128 : ok ? CFG_PK2 * 128 : have ? 15 * 128 : max(pk, CFG_PK3 * 128u);
        pr = ld_rlx((const uint32_t*)ring_ptr(p, pp + off(n + ready) + pk));
        ACC(2, have && !ok)
        have = ready;
        if (!ok) {
            ACC(1, 1)
            fin = ld_rlx(finp);
            if (++guard > GUARD) __trap();
        } else {
#pragma unroll
            for (int u = 0; u < 4; u += 2) {
                uint32_t old[8], chk = 0;
#pragma unroll
                for (int j = 0; j < 4; j++) {
                    old[2 * j] = atoms_add(sb + C_S + row[2 * u + j] * 4, val[4 * u + 2 * j]);
                    old[2 * j + 1] = atoms_add(sb + C_S + ROWS3_MAX * 4 + row[2 * u + j] * 4, val[4 * u + 2 * j + 1]);
                }
#pragma unroll
                for (int j = 0; j < 8; j++) {
                    const uint32_t nw = old[j] + val[4 * u + j];
                    chk |= (old[j] ^ nw) & (val[4 * u + j] ^ nw);
                }
                if (chk & 0x80008000u) {
                    uint32_t tmp[20];
#pragma unroll
                    for (int j = 0; j < 8; j++) { tmp[j >> 1] = row[2 * u + (j >> 1)]; tmp[4 + j] = old[j]; tmp[12 + j] = val[4 * u + j]; }
                    p3_wrap(sb, id, tmp);
                }
            }
            __syncwarp();
            if (last) break;
        }
    }
    ACC_SAVE
}

__device__ __forceinline__ void row_gates(const float* sw, const uint32_t* c2, uint32_t dbits, float4& gs, float4& gr) {
    const uint32_t d2 = dbits * 0x10001u;
    gs = gr = make_float4(0.f, 0.f, 0.f, 0.f);
#pragma unroll
    for (int r2 = 0; r2 < 4; r2++) {
        uint32_t df = sub_bf2(d2, c2[r2]);
        uint32_t ar = mul_bf2(mul_bf2(df, df), 0xC120C120u);
        uint32_t rb = pack_bf2(__expf(bflo(ar)), __expf(bfhi(ar)));
        const float r0 = bflo(rb), r1 = bfhi(rb);
        const float4 s0 = *(const float4*)(sw + r2 * 8), s1 = *(const float4*)(sw + r2 * 8 + 4);
        const float4 q0 = *(const float4*)(sw + 32 + r2 * 8), q1 = *(const float4*)(sw + 32 + r2 * 8 + 4);
        gs.x += r0 * s0.x + r1 * s1.x; gs.y += r0 * s0.y + r1 * s1.y;
        gs.z += r0 * s0.z + r1 * s1.z; gs.w += r0 * s0.w + r1 * s1.w;
        gr.x += r0 * q0.x + r1 * q1.x; gr.y += r0 * q0.y + r1 * q1.y;
        gr.z += r0 * q0.z + r1 * q1.z; gr.w += r0 * q0.w + r1 * q1.w;
    }
}
__device__ __forceinline__ uint2 finish_row(const float* wu, const float4& gs, const float4& gr, const float S[4], uint2 mrow) {
    const float a[4] = {S[0] * gs.x, S[1] * gs.y, S[2] * gs.z, S[3] * gs.w};
    float u[4] = {0, 0, 0, 0};
#pragma unroll
    for (int k = 0; k < 4; k++) {
        u[0] += a[k] * wu[4 * k]; u[1] += a[k] * wu[4 * k + 1]; u[2] += a[k] * wu[4 * k + 2]; u[3] += a[k] * wu[4 * k + 3];
    }
    return make_uint2(pack_bf2(bflo(mrow.x) + u[0] * gr.x, bfhi(mrow.x) + u[1] * gr.y),
                      pack_bf2(bflo(mrow.y) + u[2] * gr.z, bfhi(mrow.y) + u[3] * gr.w));
}
__device__ __forceinline__ void load_tail_weights(const Params& p, float* sw, int tid) {
    if (tid < 32) sw[tid] = __bfloat162float(p.w_sbf[tid]);
    else if (tid < 64) sw[tid] = __bfloat162float(p.w_rbf[tid - 32]);
    else if (tid < 80) sw[tid] = __bfloat162float(p.w_up[tid - 64]);
    else if (tid < 96) sw[tid] = __bfloat162float(p.w_down[tid - 80]);
}
__device__ __forceinline__ float exp_ftz(float x) {
    float r;
    asm("ex2.approx.ftz.f32 %0, %1;" : "=f"(r) : "f"(x * 1.4426950408889634f));
    return r;
}
__device__ __forceinline__ void tail_rows(const Params& p, int tidx, int w, int lane) {
    constexpr uint32_t sb = SB;
    if (w == NW - 1 && lane < 2) {
        fence_gpu();
        red_rlx(rdy_of(p, sb, 320, lane), 1u);
    }
    if (w >= NPC * WPP) return;
    const int pc = w / WPP, r0 = pc * RPC + (tidx * WPP + w - pc * WPP) * 8, e0 = r0 * 32;
    const uint32_t G = sb + T_G + w * TWB, M = G + 4096, D = M + 2048;
    cp16z(D + lane * 16, p.dist + e0 + lane * 8, min(max(p.E - e0 - lane * 8, 0), 8) * 2);
#pragma unroll
    for (int k = 0; k < 4; k++) cp16(M + (k * 32 + lane) * 16, p.m + e0 + (k * 32 + lane) * 2, e0 + (k * 32 + lane) * 2 < p.E);
    cp_commit();
    const Scale sc = get_scale(sb);
    const float lsb[4] = {__uint_as_float((sc.eb[0] - 10) << 23), __uint_as_float((sc.eb[1] - 10) << 23),
                          __uint_as_float((sc.eb[2] - 10) << 23), __uint_as_float((sc.eb[3] - 10) << 23)};
    {
        const int g = lane >> 2, t = lane & 3;
        const uint32_t c2 = ((const uint32_t*)p.centers)[t];
        const unsigned short* wg = (const unsigned short*)(g < 4 ? p.w_sbf : p.w_rbf) + t * 8 + (g & 3);
        const uint32_t b = wg[0] | (uint32_t)wg[4] << 16;
        cp_wait<0>();
        __syncwarp();
        TR(19, w == 0 && lane == 0 && b + c2 != 0x12345);
#pragma unroll 2
        for (int k = 0; k < 16; k++) {
            const uint32_t dv = lds32(D + (k * 8 + g) * 4);
            uint32_t a[2];
#pragma unroll
            for (int h = 0; h < 2; h++) {
                const uint32_t df = sub_bf2(prmt(dv, 0, h ? 0x3232 : 0x1010), c2);
                const uint32_t ar = mul_bf2(mul_bf2(df, df), 0xC120C120u);
                a[h] = pack_bf2(exp_ftz(bflo(ar)), exp_ftz(bfhi(ar)));
            }
            float d[4];
            asm("mma.sync.aligned.m16n8k8.row.col.f32.bf16.bf16.f32 {%0,%1,%2,%3}, {%4,%5}, {%6}, {%7,%7,%7,%7};"
                : "=f"(d[0]), "=f"(d[1]), "=f"(d[2]), "=f"(d[3]) : "r"(a[0]), "r"(a[1]), "r"(b), "f"(0.f));
            const uint32_t at = G + (k * 16 + g * 2) * 16 + t * 4;
            sts32(at, pack_bf2(d[0], d[1]));
            sts32(at + 16, pack_bf2(d[2], d[3]));
        }
    }
    __syncwarp();
    TR(2, w == 0 && lane == 0);
    float wu[16];
#pragma unroll
    for (int k = 0; k < 4; k++) *(uint4*)(wu + 4 * k) = lds128(sb + SM_W + 256 + 16 * k);
    uint32_t dirty = 0;
#pragma unroll 1
    for (int pass = CFG_DRY ? 0 : 1; pass < 2; pass++) {
        if (pass) {
            if (w == pc * WPP && lane < 2) spin_ge(rdy_of(p, sb, lane ? 320 : 160 + 32 * pc, lds32(sb + SM_MISC + 20)), lane ? NTAIL : N3);
            __syncwarp();
            bar_sync(1 + pc, WPP * 32);
            TR(3, w == 0 && lane == 0);
            TR(10, w == NPC * WPP - 1 && lane == 0);
            if (r0 >= (int)p.rows3) return;
        }
        uint4 sv[4] = {};
#pragma unroll
        for (int u = 0; u < 4; u++) ldq128_keep(sv[u], &g_S[0][u * 16 + (lane >> 1)][r0 + (lane & 1) * 4], pass);
        if (pass && lane < 8 && (r0 + lane) * 32 < p.E && (dirty = ld_rlx(g_dirty + r0 + lane))) st_rlx(g_dirty + r0 + lane, 0u);
        dirty = __ballot_sync(0xffffffffu, dirty != 0);
        uint32_t xs[8] = {sv[0].x, sv[0].y, sv[0].z, sv[0].w, sv[1].x, sv[1].y, sv[1].z, sv[1].w};
        uint32_t ys[8] = {sv[2].x, sv[2].y, sv[2].z, sv[2].w, sv[3].x, sv[3].y, sv[3].z, sv[3].w};
        asm volatile("" : "+r"(lane));
        auto finish = [&](int k, uint32_t x, uint32_t y, bool extra) {
            const int i = (lane & 1) * 128 + (lane >> 1) + (k & 3) * 32 + (k >> 2) * 16, e = e0 + i;
            float S[4];
            const uint32_t tx = x + 0x80008000u, ty = y + 0x80008000u;
            S[0] = (__uint_as_float(prmt(tx, 0x4b000000u, 0x7610)) - 8421376.0f) * lsb[0];
            S[1] = (__uint_as_float(prmt(tx, 0x4b000000u, 0x7632)) - 8421376.0f) * lsb[1];
            S[2] = (__uint_as_float(prmt(ty, 0x4b000000u, 0x7610)) - 8421376.0f) * lsb[2];
            S[3] = (__uint_as_float(prmt(ty, 0x4b000000u, 0x7632)) - 8421376.0f) * lsb[3];
            if (extra && e < p.E) {
                const float4 g = __ldcg(g_Sg + e);
                S[0] += g.x; S[1] += g.y; S[2] += g.z; S[3] += g.w;
                __stcg(g_Sg + e, make_float4(0.f, 0.f, 0.f, 0.f));
            }
            const uint4 g = lds128(G + i * 16);
            const uint2 o = finish_row(wu, make_float4(bflo(g.x), bfhi(g.x), bflo(g.y), bfhi(g.y)), make_float4(bflo(g.z), bfhi(g.z), bflo(g.w), bfhi(g.w)), S,
                                       lds64v(M + i * 8));
            asm volatile("{.reg .pred q; setp.ne.u32 q, %3, 0; @q st.global.v2.u32 [%0], {%1,%2};}"
                         ::"l"(p.out + e), "r"(o.x), "r"(o.y), "r"((uint32_t)(pass && e < p.E)));
        };
        if (!dirty) {
#pragma unroll
            for (int k = 0; k < 8; k++) finish(k, xs[k], ys[k], false);
        } else {
#pragma unroll 1
            for (int k = 0; k < 8; k++) {
                finish(k, xs[0], ys[0], dirty >> ((lane & 1) * 4 + (k & 3)) & 1);
#pragma unroll
                for (int j = 0; j < 7; j++) { xs[j] = xs[j + 1]; ys[j] = ys[j + 1]; }
            }
        }
    }
    TR(9, w == 0 && lane == 0);
    TR(11, w == NPC * WPP - 1 && lane == 0);
}

#define CFG_MAP1 1
__global__ void __launch_bounds__(NT, 1) k_main(const __grid_constant__ Params p) {
    extern __shared__ __align__(1024) unsigned char smem[];
    constexpr uint32_t sb = SB;
    if ((uint32_t)__cvta_generic_to_shared(smem) != SB) __trap();
    const int tid = threadIdx.x, w = __shfl_sync(0xffffffffu, tid >> 5, 0), lane = tid & 31;
    if (w < NPROBE) probe(p, sb, w, lane);
    else {
        if (tid == NT - 1) sts32(sb + SM_MISC + 16, ld_rlx(&g_epoch) & 1);
        if (tid >= NT - 32 && lane < 12) sts32(sb + SM_FIN + lane * 4, 0u);
        load_tail_weights(p, (float*)(smem + SM_W), tid - NPROBE * 32);
        const int k = blockIdx.x % (NCTA / 2) * 14 + lane;
        if (w == NW - 2 && lane < 14 && k < NT - 32) asm volatile("prefetch.global.L2 [%0];" ::"l"((const uint4*)p.m + k * (p.E / 2 / (NT - 32))));
    }
    cta_sync();
    if (w) {
        const uint4 in = __ldg((const uint4*)p.m + (tid - 32) * (p.E / 2 / (NT - 32)));
        const Mat4 wd = load_mat4(p.w_down, lane);
        for (int i = SM_DATA / 16 + tid - 32; i < ZEND / 16; i += NT - 32) ((uint4*)smem)[i] = make_uint4(0, 0, 0, 0);
        if (tid - 32 < 256) ((uint4*)(smem + SM_ZERO))[tid - 32] = make_uint4(0, 0, 0, 0);
        if (tid < 48) sts32(sb + SM_CNT2 + (tid - 32) * 4, NQ2 << 16);
        __syncwarp();
        if (CFG_PFD && tid == NT - 1) {
            __nanosleep(CFG_PFD);
            const uint32_t n = (p.E / 2 + NCTA - 1) / NCTA, o = blockIdx.x * n;
            if (o < (uint32_t)p.E / 2) asm volatile("cp.async.bulk.prefetch.L2.global [%0], %1;" ::"l"((const uint4*)p.m + o), "r"(min(n, p.E / 2 - o) * 16) : "memory");
        }
        __syncwarp();
        md_stats(in, wd, lane);
    } else assign_role(p, sb, lane);
    if (tid == 0) {
        mbar_init(sb + SM_DONE, lds32(sb + SM_MISC) >> 8 ? P2W : P1W);
        mbar_init(sb + SM_DONE2, NF);
    }
    cta_sync();
    const uint32_t rid = __shfl_sync(0xffffffffu, lds32(sb + SM_MISC), 0);
    const int role = rid >> 8, id = rid & 255;
    TR(5, tid == 0);
    if (role == 0) {
        const int ww = CFG_MAP1 == 0 ? ((w & 3) == 3 ? NW : (w >> 2) * 3 + (w & 3)) : CFG_MAP1 == 1 ? (w & 2 ? NW : (w >> 2) * 2 + (w & 1)) : w;
        const int sw = CFG_MAP1 == 0 ? ((w & 3) == 3 ? w >> 2 : NW) : CFG_MAP1 == 1 ? (w & 2 ? (w >> 2) * 2 + (w & 1) : NW) : w - P1W;
        static_assert(CFG_MAP1 == 0 ? (P1W <= NW / 4 * 3 && NF + 2 <= NW / 4) : CFG_MAP1 == 1 ? (P1W <= NW / 2 && NF + 2 <= NW / 2) : true, "warp map");
        for (int i = tid; i < NF * GPW * 32; i += NT) sts32(sb + A_CNT + i * 4, 1u << 24);
        if (tid < 64) sts32(sb + SM_CRED + tid * 4, 0u);
        cta_sync();
        TR(1, tid == 0);
        if (ww < P1W) role_p1(p, sb, id, ww, lane);
        else if (sw < NF) role_flush(p, sb, id, sw, lane);
        else if (sw == NF) role_credit1(p, sb, id, lane);
        else if (w == NW - 1) {
            uint4* owin = (uint4*)(p.ring + (CWIN + (lds32(sb + SM_MISC + 16) ^ 1)) * WIN);
            for (int i = id * 32 + lane; i < CPAIRS * 512; i += N1 * 32) __stcg(owin + i, make_uint4(0, 0, 0, 0));
            __syncwarp();
        }
    } else if (role == 1) {
        const int row0 = id % H2 * p.rows2;
        const int nrows = min((int)p.rows2, p.E - row0);
        constexpr int NTB = NT - 32, TBD = CFG_TBD;
        bool flagged = false;
        if (w < NW - 1) {
            const Scale sc = get_scale(sb);
            const Mat4 wd = load_mat4(p.w_down, lane);
            Mat4 ws;
#pragma unroll
            for (int k = 0; k < 4; k++) ws.b[k] = mul_bf2(wd.b[k], ((246u - (lane & 4 ? sc.eb[(k & 2) + 1] : sc.eb[k & 2])) << 7) * 0x10001u);
            const uint4* const src = (const uint4*)(p.m + row0);
            uint4 r2[TBD], nx[TBD];
            auto fetch = [&](int i) {
#pragma unroll
                for (int k = 0; k < TBD; k++)
                    asm volatile("ld.global.nc.v4.u32 {%0,%1,%2,%3}, [%4];" : "=r"(nx[k].x), "=r"(nx[k].y), "=r"(nx[k].z), "=r"(nx[k].w) : "l"(src + min(i + k * NTB, nrows / 2 - 1)));
            };
            fetch(tid);
#pragma unroll 1
            for (int i0 = tid; 2 * (i0 - lane) < nrows; i0 += TBD * NTB) {
#pragma unroll
                for (int k = 0; k < TBD; k++) r2[k] = make_uint4(nx[k].x, nx[k].z, nx[k].y, nx[k].w);
                fetch(i0 + TBD * NTB);
#pragma unroll
                for (int k = 0; k < TBD; k++) {
                    const int i = i0 + k * NTB;
                    float y[8];
                    mul4(make_uint4(r2[k].x, r2[k].z, r2[k].y, r2[k].w), ws, y);
                    uint32_t a[4], h[4], ta[2];
#pragma unroll
                    for (int j = 0; j < 4; j++) { a[j] = pack_h2(y[2 * j], y[2 * j + 1]); h[j] = a[j] + 0x00040004u; }
#pragma unroll
                    for (int j = 0; j < 2; j++) ta[j] = bitsel(h[2 * j], bitsel(h[2 * j + 1] >> 3, h[2 * j + 1] << 7, 0x00070007u), 0x9ff89ff8u);
                    uint32_t tb = prmt(h[1], h[3], 0x7531);
                    const uint32_t b0 = a[0] | a[1] | h[0] | h[1], b1 = a[2] | a[3] | h[2] | h[3];
                    if (__any_sync(0xffffffffu, ((b0 | b1) & 0x60006000u) || sc.allslow)) {
                        if ((b0 & 0x60006000u) || sc.allslow) { ta[0] = 0; tb = (tb & 0xffff0000u) | 0x40u; }
                        if ((b1 & 0x60006000u) || sc.allslow) { ta[1] = 0; tb = (tb & 0xffffu) | 0x400000u; }
                        flagged = true;
                    }
                    sts64_if(sb + B_TA + i * 8, ta[0], ta[1], 2 * i < nrows);
                    sts32_if(sb + B_TB + i * 4, tb, 2 * i < nrows);
                }
            }
            if (tid == 0) {
                sts32(sb + B_TA + p.rows2 * 4, 0u);
                sts16(sb + B_TB + p.rows2 * 2, 0u);
            }
            TR(8, tid == 0);
        } else if (lane == 0) spin_ge(rdy_of(p, sb, id, id / H2), H3);
        __syncwarp();
        flagged = __any_sync(0xffffffffu, __syncthreads_or(flagged));
        TR(1, tid == 0);
        if (w < P2W) {
            if (flagged) role_p2<true>(p, sb, id, w, lane);
            else role_p2<false>(p, sb, id, w, lane);
        } else if (w == P2W) role_credit(p, sb, id, lane);
    } else {
        if (w == 0) clear_queues<false>(p, sb, id, lane);
        if (tid >= 32 && tid < 33 + NPC) mbar_init(sb + SM_CNT2 + (tid - 32) * 8, 1);
        cta_sync();
        TR(1, tid == 0);
        if (w < P3W) role_p3(p, sb, id, w, lane);
        cta_sync();
        TR(2, tid == 0);
        if (w < NPC && lane == 0) {
            fence_async_smem();
            const int n = min(((int)p.rows3 + 7) / 8 * 8 - w * RPC, RPC);
            if (w >= CFG_DOUT) mbar_wait(sb + SM_CNT2 + (w + 1 - CFG_DOUT) * 8, 0);
            if (n > 0) {
                bulk_store(g_S[0][id] + w * RPC, sb + C_S + w * RPC * 4, n * 4);
                bulk_store(g_S[1][id] + w * RPC, sb + C_S + (ROWS3_MAX + w * RPC) * 4, n * 4);
            }
            asm volatile("cp.async.bulk.commit_group;" ::: "memory");
            asm volatile("cp.async.bulk.wait_group.read 0;" ::: "memory");
            mbar_arrive(sb + SM_CNT2 + w * 8 + 8);
            asm volatile("cp.async.bulk.wait_group 0;" ::: "memory");
            fence_gpu();
            red_rlx(rdy_of(p, sb, 160 + 32 * w, 0), 1u);
            red_rlx(rdy_of(p, sb, 160 + 32 * w, 1), 1u);
            if (id == 0 && w == 0) red_rlx(&g_epoch, 1u);
            TR(12 + w, true);
        }
        return;
    }
    cta_sync();
    TR(18, tid == 0 && role == 1);
    if (role == 0 && w == NW - 2) clear_queues<true>(p, sb, id, lane);
    tail_rows(p, role * N1 + id, w, lane);
}

__global__ void k_direct(const Params p, long long T) {
    float wd[16];
#pragma unroll
    for (int i = 0; i < 16; i++) wd[i] = __bfloat162float(p.w_down[i]);
    const float f = __bfloat162float(p.freq[0]);
    for (long long t = blockIdx.x * (long long)blockDim.x + threadIdx.x; t < T; t += (long long)gridDim.x * blockDim.x) {
        float x = __bfloat162float(__float2bfloat16(f * __bfloat162float(p.angle[t])));
        float c = __bfloat162float(__float2bfloat16(cosf(x)));
        uint2 md = down_row(__ldg(p.m + p.idx_in[t]), wd);
        red_v4(g_Sg + p.idx_out[t], c * bflo(md.x), c * bfhi(md.x), c * bflo(md.y), c * bfhi(md.y));
    }
}
__global__ void k_direct_tail(const Params p) {
    __shared__ __align__(16) float sw[96];
    load_tail_weights(p, sw, threadIdx.x);
    __syncthreads();
    uint32_t c2[4];
#pragma unroll
    for (int i = 0; i < 4; i++) c2[i] = ((const uint32_t*)p.centers)[i];
    for (int e = blockIdx.x * blockDim.x + threadIdx.x; e < p.E; e += gridDim.x * blockDim.x) {
        float4 g = __ldcg(g_Sg + e);
        __stcg(g_Sg + e, make_float4(0.f, 0.f, 0.f, 0.f));
        const float Sv[4] = {g.x, g.y, g.z, g.w};
        float4 gs, gr;
        row_gates(sw, c2, __bfloat16_as_ushort(p.dist[e]), gs, gr);
        p.out[e] = finish_row(sw + 64, gs, gr, Sv, __ldg(p.m + e));
    }
}

static bool pick_rows(int E, int n, int rows_max, int mult, uint32_t* rows, uint32_t* magic) {
    for (uint32_t r = (E + n - 1) / n; r <= (uint32_t)rows_max; r++) {
        if (r < 2 || r % mult) continue;
        uint64_t mg = ((1ull << 32) + r - 1) / r;
        uint64_t err = mg * r - (1ull << 32);
        if (err * (uint64_t)n < mg) { *rows = r; *magic = (uint32_t)mg; return true; }
    }
    return false;
}

}

extern "C" void kernel_launch(void* const* d_in, const int* in_sizes, int n_in, void* d_out, int out_size) {
    using namespace gs;
    (void)n_in; (void)out_size;
    Params p;
    p.m = (const uint2*)d_in[0];
    p.idx_in = (const int*)d_in[1];
    p.idx_out = (const int*)d_in[2];
    p.dist = (const __nv_bfloat16*)d_in[3];
    p.angle = (const __nv_bfloat16*)d_in[4];
    p.centers = (const __nv_bfloat16*)d_in[5];
    p.freq = (const __nv_bfloat16*)d_in[6];
    p.w_rbf = (const __nv_bfloat16*)d_in[7];
    p.w_sbf = (const __nv_bfloat16*)d_in[8];
    p.w_down = (const __nv_bfloat16*)d_in[9];
    p.w_up = (const __nv_bfloat16*)d_in[10];
    p.out = (uint2*)d_out;
    p.E = in_sizes[3];
    const long long T = in_sizes[1];
    p.n4 = (int)(T / 4);
    p.rows2 = p.magic2 = 0;
    p.ring = nullptr;

    static int sms = 0, rsv = 0;
    if (!sms) {
        int dev = 0;
        cudaGetDevice(&dev);
        cudaDeviceGetAttribute(&rsv, cudaDevAttrReservedSharedMemoryPerBlock, dev);
        cudaDeviceGetAttribute(&sms, cudaDevAttrMultiProcessorCount, dev);
        cudaFuncSetAttribute(k_main, cudaFuncAttributeMaxDynamicSharedMemorySize, SMEM_BYTES);
    }
    cudaStream_t st = cudaStreamPerThread;
    bool fast = (T % 4 == 0) && T > 0 && sms >= NCTA && rsv == (int)SB && p.E >= 65536 && p.E <= E_MAX &&
                p.E % 4 == 0 && (((uintptr_t)p.m | (uintptr_t)p.idx_in | (uintptr_t)p.idx_out | (uintptr_t)p.angle) & 15) == 0 &&
                pick_rows(p.E, NI, ROWS2_MAX, 2, &p.rows2, &p.magic2);
    p.c1 = 1;
    p.nrows2 = 0u - p.rows2;
    p.rows3 = (p.E + 31) / 32;
    fast = fast && (p.rows2 * (NI - 1) + 2 <= (uint32_t)p.E);
    static const void* tkey[3] = {nullptr, nullptr, nullptr};
    static cudaTextureObject_t tex[3] = {0, 0, 0};
    static long long tlen = -1;
    const void* tptr[3] = {p.idx_in, p.idx_out, p.angle};
    for (int k = 0; fast && k < 3; k++) {
        if (tkey[k] == tptr[k] && tlen == T) continue;
        if (tkey[k]) cudaDestroyTextureObject(tex[k]);
        tkey[k] = nullptr;
        cudaResourceDesc rd = {};
        rd.resType = cudaResourceTypeLinear;
        rd.res.linear.devPtr = (void*)tptr[k];
        rd.res.linear.desc = cudaCreateChannelDesc(32, 32, k < 2 ? 32 : 0, k < 2 ? 32 : 0, cudaChannelFormatKindUnsigned);
        rd.res.linear.sizeInBytes = (size_t)T * (k < 2 ? 4 : 2);
        cudaTextureDesc td = {};
        td.readMode = cudaReadModeElementType;
        if (cudaCreateTextureObject(&tex[k], &rd, &td, nullptr) == cudaSuccess) tkey[k] = tptr[k];
        else { (void)cudaGetLastError(); fast = false; }
    }
    if (fast) tlen = T;
    p.t_in = tex[0]; p.t_out = tex[1]; p.t_ang = tex[2];
    if (fast) {
        void* ring = nullptr;
        cudaGetSymbolAddress(&ring, g_ring);
        uintptr_t a = ((uintptr_t)ring + WIN - 1) & ~(uintptr_t)(WIN - 1);
        if (a >> 32 != (a + RING_BYTES - 1) >> 32) a += RING_BYTES;
        p.ring = (unsigned char*)a;
        p.ring_lo = (uint32_t)a;
        p.ring_hi = (uint32_t)(a >> 32);
        k_main<<<NCTA, NT, SMEM_BYTES, st>>>(p);
    } else {
        k_direct<<<sms * 8, 256, 0, st>>>(p, T);
        k_direct_tail<<<sms * 4, 256, 0, st>>>(p);
    }
}
```

```cpp
#include <cuda_runtime.h>
#include <cuda_bf16.h>
#include <stdint.h>

#define CFG_N1 56
#define CFG_NI 22
#define CFG_NW 28
#define CFG_P1W 14
#define CFG_GPW 2
#define CFG_KR 1
#define CFG_SMPAD 0
#define CFG_QPW 3
#define CFG_TG 2
#define CFG_PMASK 8
#define CFG_PSTREAK 1
#define CFG_NBT 1
#define CFG_KM 5
#define CFG_KN 9
#define CFG_TBD 4
#define CFG_P0 500
#define CFG_PFD 200
#define CFG_C1SLEEP 200
#define CFG_PK1 6
#define CFG_PK2 8
#define CFG_PK3 11
#define CFG_CLN 2
#define CFG_CLS 300
#define CFG_DOUT 2
#define CFG_TBLOW 1
#define CFG_LLOW 1
#define CFG_CRM 0
#define CFG_ZE 0
#define CFG_TH 14
#define CFG_TS 200
#define CFG_POLL 64
#define CFG_HINT 20000
#define CFG_BSLEEP 100
#define CFG_CSLEEP 200
#define CFG_FSLEEP 100
#define CFG_PSLEEP 100
#define CFG_DRY 1
#define CFG_PROBES 4

namespace gs {

constexpr int E_MAX = 640000;
constexpr int N1 = CFG_N1, NI = CFG_NI, N2 = 2 * NI, N3 = 32, NCTA = N1 + N2 + N3;
constexpr int H2 = NI, H3 = N3 / 2;
constexpr int NB = NI * N3;
constexpr int NW = CFG_NW, NT = NW * 32;
constexpr int GPW = CFG_GPW, NF = (NI + GPW - 1) / GPW;
constexpr int QPW = CFG_QPW, NBT = CFG_NBT;
constexpr int P1W = CFG_P1W, P2W = (N1 + QPW - 1) / QPW, P3W = NI;
constexpr int NQ1 = 32, NQ2 = 64;
constexpr int ROWS2_MAX = ((E_MAX + NI - 1) / NI + 31) / 8 * 8;
constexpr int ROWS3_MAX = (E_MAX / 32 + 31) / 32 * 32;
constexpr int NTAIL = N1 + N2;
constexpr int NPC = 5, WPP = 5, RPC = NTAIL * WPP * 8;
constexpr int GUARD = 1 << 26;
static_assert(NCTA % 4 == 0 && NCTA <= 192, "roles come in CTA pairs, per partition");
static_assert((GPW == 2 || GPW == 4) && QPW >= NBT && QPW <= 4 && NI <= 32 && N1 <= 62, "queue ownership");
static_assert(P1W + NF + 2 <= NW && P2W + 2 <= NW && P3W + 1 <= NW && P1W * 256 + 64 < 8192, "warp roles");
static_assert(ROWS2_MAX + 8 <= 32768 && ROWS3_MAX <= 32768, "index bits");

constexpr uint32_t SB = 1024;
constexpr int SM_DONE = 0, SM_DONE2 = 8;
constexpr int SM_MISC = 16;
constexpr int SM_FIN = 48;
constexpr int SM_STAT = 64;
constexpr int SM_CNT2 = 128;
constexpr int SM_W = 256;
constexpr int SM_PUB = SM_W + 384;
constexpr int SM_PROBE = SM_PUB + 768;
constexpr int SM_CRED = 1792;
constexpr int SM_DATA = 2048;
constexpr int cmax(int a, int b) { return a > b ? a : b; }
constexpr int A_CNT = SM_DATA;
constexpr int KR = CFG_KR, LISTB = (GPW * 32 + 8 * KR) * 4;
constexpr int A_ST = A_CNT + NF * GPW * 128 + (CFG_LLOW ? (NF * LISTB + 127) / 128 * 128 : 0);
constexpr int A_LIST = CFG_LLOW ? A_CNT + NF * GPW * 128 : A_ST + NB * 256;
constexpr int A_END = A_ST + NB * 256 + (CFG_LLOW ? 0 : NF * LISTB);
constexpr int B_TB = CFG_TBLOW ? SM_DATA : SM_DATA + (ROWS2_MAX + 8) * 4;
constexpr int B_TA = CFG_TBLOW ? SM_DATA + (ROWS2_MAX + 8) * 2 : SM_DATA;
constexpr int B_END = SM_DATA + (ROWS2_MAX + 8) * 6;
constexpr int C_S = SM_DATA;
constexpr int C_END = C_S + ROWS3_MAX * 8;
constexpr int T_G = SM_DATA, TWB = 4096 + 2048 + 512, T_END = T_G + NPC * WPP * TWB;
constexpr int ZEND = cmax(A_END, C_END);
constexpr int SM_ZERO = (cmax(C_END, T_END) + 127) / 128 * 128;
constexpr int SMEM_BYTES = cmax(cmax(A_END, B_END), SM_ZERO + 4096) + CFG_SMPAD;
static_assert(SMEM_BYTES <= 232448 && SM_PROBE + 128 <= SM_CRED, "shared memory");
static_assert(NPC * RPC >= ROWS3_MAX && NPC * WPP + 2 <= NW, "tail");

constexpr uint32_t FIN = 0x80000000u;

constexpr uint32_t WIN = 524288;
constexpr int CWIN = N2 + N3, NWIN = CWIN + 2, CPAIRS = 31;
constexpr uint32_t PROBE_OFF = (uint32_t)NWIN * WIN;
constexpr int NPROBE = 16;
static_assert(NWIN <= NCTA && NPROBE <= NW, "windows");
constexpr size_t RING_BYTES = (size_t)PROBE_OFF + WIN;
__device__ __align__(128) unsigned char g_ring[2 * RING_BYTES + WIN];
__device__ __align__(128) uint32_t g_S[2][32][ROWS3_MAX];
__device__ __align__(128) float4 g_Sg[E_MAX];
__device__ uint32_t g_dirty[E_MAX / 32];
__device__ uint32_t g_epoch;

#define TR(ev, on)
#define ACC_DECL
#define ACC(i, n)
#define ACC_SAVE

struct Params {
    const uint2* m;
    const int* idx_in;
    const int* idx_out;
    const __nv_bfloat16* dist;
    const __nv_bfloat16* angle;
    const __nv_bfloat16* centers;
    const __nv_bfloat16* freq;
    const __nv_bfloat16* w_rbf;
    const __nv_bfloat16* w_sbf;
    const __nv_bfloat16* w_down;
    const __nv_bfloat16* w_up;
    uint2* out;
    unsigned char* ring;
    cudaTextureObject_t t_in, t_out, t_ang;
    int E, n4;
    uint32_t rows2, nrows2, magic2, rows3;
    uint32_t ring_lo, ring_hi, c1;
};

__device__ __forceinline__ float bflo(uint32_t w) { return __uint_as_float(w << 16); }
__device__ __forceinline__ float bfhi(uint32_t w) { return __uint_as_float(w & 0xffff0000u); }
__device__ __forceinline__ uint32_t pack_bf2(float lo, float hi) {
    uint32_t r;
    asm("cvt.rn.bf16x2.f32 %0, %1, %2;" : "=r"(r) : "f"(hi), "f"(lo));
    return r;
}
__device__ __forceinline__ uint32_t mul_bf2(uint32_t a, uint32_t b) {
    uint32_t r;
    asm("mul.rn.bf16x2 %0, %1, %2;" : "=r"(r) : "r"(a), "r"(b));
    return r;
}
__device__ __forceinline__ uint32_t sub_bf2(uint32_t a, uint32_t b) {
    uint32_t r;
    asm("sub.rn.bf16x2 %0, %1, %2;" : "=r"(r) : "r"(a), "r"(b));
    return r;
}
__device__ __forceinline__ uint32_t maxabs_bf2(uint32_t a, uint32_t b) {
    uint32_t r;
    asm("max.NaN.xorsign.abs.bf16x2 %0, %1, %2;" : "=r"(r) : "r"(a), "r"(b));
    return r;
}
__device__ __forceinline__ void mbar_init(uint32_t a, uint32_t n) {
    asm volatile("mbarrier.init.shared::cta.b64 [%0], %1;" ::"r"(a), "r"(n) : "memory");
}
__device__ __forceinline__ void mbar_arrive(uint32_t a) {
    asm volatile("mbarrier.arrive.shared::cta.b64 _, [%0];" ::"r"(a) : "memory");
}
__device__ __forceinline__ void mbar_arrive_n(uint32_t a, uint32_t n) {
    asm volatile("mbarrier.arrive.shared::cta.b64 _, [%0], %1;" ::"r"(a), "r"(n) : "memory");
}
__device__ __forceinline__ void mbar_arrive_if(uint32_t a, bool on) {
    asm volatile("{.reg .pred q; setp.ne.u32 q, %1, 0; @q mbarrier.arrive.shared::cta.b64 _, [%0];}" ::"r"(a), "r"((uint32_t)on) : "memory");
}
__device__ __forceinline__ void mbar_wait(uint32_t a, uint32_t parity) {
    uint32_t ok;
    int guard = 0;
    do {
        asm volatile("{.reg .pred p; mbarrier.try_wait.parity.shared::cta.b64 p, [%1], %2, %3; selp.u32 %0, 1, 0, p;}"
                     : "=r"(ok) : "r"(a), "r"(parity), "r"(CFG_HINT) : "memory");
        if (!ok) {
            if (++guard > GUARD) __trap();
        }
    } while (!ok);
}
__device__ __forceinline__ void cta_sync() { __syncwarp(); __syncthreads(); }
__device__ __forceinline__ void bar_sync(int id, int n) { asm volatile("bar.sync %0, %1;" ::"r"(id), "r"(n) : "memory"); }
__device__ __forceinline__ void bar_arrive(int id, int n) { asm volatile("bar.arrive %0, %1;" ::"r"(id), "r"(n) : "memory"); }
__device__ __forceinline__ bool mbar_test(uint32_t a, uint32_t parity) {
    uint32_t ok;
    asm volatile("{.reg .pred p; mbarrier.test_wait.parity.shared::cta.b64 p, [%1], %2; selp.u32 %0, 1, 0, p;}"
                 : "=r"(ok) : "r"(a), "r"(parity) : "memory");
    return ok;
}
__device__ __forceinline__ uint32_t ld_acq(const uint32_t* p) {
    uint32_t v;
    asm volatile("ld.acquire.gpu.global.u32 %0, [%1];" : "=r"(v) : "l"(p) : "memory");
    return v;
}
__device__ __forceinline__ uint32_t ld_rlx(const uint32_t* p) {
    uint32_t v;
    asm volatile("ld.relaxed.gpu.global.u32 %0, [%1];" : "=r"(v) : "l"(p) : "memory");
    return v;
}
__device__ __forceinline__ void st_rlx(uint32_t* p, uint32_t v) {
    asm volatile("st.relaxed.gpu.global.u32 [%0], %1;" ::"l"(p), "r"(v) : "memory");
}
__device__ __forceinline__ void red_rlx(uint32_t* p, uint32_t v) {
    asm volatile("red.relaxed.gpu.global.add.u32 [%0], %1;" ::"l"(p), "r"(v) : "memory");
}
__device__ __forceinline__ bool elect_one() {
    uint32_t p;
    asm volatile("{.reg .pred P; elect.sync _|P, 0xffffffff; selp.u32 %0, 1, 0, P;}" : "=r"(p));
    return p;
}
__device__ __forceinline__ uint32_t spin_ge(const uint32_t* p, uint32_t target) {
    int guard = 0;
    while (ld_rlx(p) < target) {
        __nanosleep(CFG_POLL);
        if (++guard > GUARD) __trap();
    }
    return ld_acq(p);
}
__device__ __forceinline__ void fence_gpu() { asm volatile("fence.acq_rel.gpu;" ::: "memory"); }
__device__ __forceinline__ void fence_async_smem() { asm volatile("fence.proxy.async.shared::cta;" ::: "memory"); }
__device__ __forceinline__ void fence_async_all() { asm volatile("fence.proxy.async;" ::: "memory"); }
__device__ __forceinline__ void bulk_store(void* g, uint32_t s, uint32_t bytes) {
    asm volatile("cp.async.bulk.global.shared::cta.bulk_group [%0], [%1], %2;" ::"l"(g), "r"(s), "r"(bytes) : "memory");
}
__device__ __forceinline__ void cp16(uint32_t s, const void* g, bool on) {
    asm volatile("{.reg .pred q; setp.ne.u32 q, %2, 0; @q cp.async.cg.shared.global [%0], [%1], 16;}" ::"r"(s), "l"(g), "r"((uint32_t)on) : "memory");
}
__device__ __forceinline__ void cp16z(uint32_t s, const void* g, int bytes) {
    asm volatile("cp.async.cg.shared.global [%0], [%1], 16, %2;" ::"r"(s), "l"(g), "r"(bytes) : "memory");
}
__device__ __forceinline__ void cp_commit() { asm volatile("cp.async.commit_group;" ::: "memory"); }
template <int N> __device__ __forceinline__ void cp_wait() { asm volatile("cp.async.wait_group %0;" ::"n"(N) : "memory"); }
__device__ __forceinline__ uint32_t atoms_add(uint32_t a, uint32_t v) {
    uint32_t o;
    asm volatile("atom.shared.add.u32 %0, [%1], %2;" : "=r"(o) : "r"(a), "r"(v) : "memory");
    return o;
}
__device__ __forceinline__ void sts32(uint32_t a, uint32_t v) { asm volatile("st.shared.u32 [%0], %1;" ::"r"(a), "r"(v) : "memory"); }
__device__ __forceinline__ void sts16(uint32_t a, uint32_t v) { asm volatile("st.shared.u16 [%0], %1;" ::"r"(a), "h"((uint16_t)v) : "memory"); }
__device__ __forceinline__ void sts64(uint32_t a, uint32_t x, uint32_t y) { asm volatile("st.shared.v2.u32 [%0], {%1,%2};" ::"r"(a), "r"(x), "r"(y) : "memory"); }
__device__ __forceinline__ uint32_t lds32(uint32_t a) {
    uint32_t v;
    asm volatile("ld.shared.u32 %0, [%1];" : "=r"(v) : "r"(a) : "memory");
    return v;
}
__device__ __forceinline__ uint2 lds64(uint32_t a) {
    uint2 v;
    asm volatile("ld.shared.v2.u32 {%0,%1}, [%2];" : "=r"(v.x), "=r"(v.y) : "r"(a));
    return v;
}
__device__ __forceinline__ uint2 lds64v(uint32_t a) {
    uint2 v;
    asm volatile("ld.volatile.shared.v2.u32 {%0,%1}, [%2];" : "=r"(v.x), "=r"(v.y) : "r"(a) : "memory");
    return v;
}
__device__ __forceinline__ uint32_t lds32v(uint32_t a) {
    uint32_t v;
    asm volatile("ld.volatile.shared.u32 %0, [%1];" : "=r"(v) : "r"(a) : "memory");
    return v;
}
__device__ __forceinline__ uint4 lds128(uint32_t a) {
    uint4 v;
    asm volatile("ld.shared.v4.u32 {%0,%1,%2,%3}, [%4];" : "=r"(v.x), "=r"(v.y), "=r"(v.z), "=r"(v.w) : "r"(a) : "memory");
    return v;
}
__device__ __forceinline__ void sts128(uint32_t a, uint4 v) {
    asm volatile("st.shared.v4.u32 [%0], {%1,%2,%3,%4};" ::"r"(a), "r"(v.x), "r"(v.y), "r"(v.z), "r"(v.w) : "memory");
}
#define LD_Q "ld.relaxed.gpu.global"
__device__ __forceinline__ uint4 ldg_q128(const void* p) {
    uint4 v;
    asm volatile(LD_Q ".v4.u32 {%0,%1,%2,%3}, [%4];"
                 : "=r"(v.x), "=r"(v.y), "=r"(v.z), "=r"(v.w) : "l"(p) : "memory");
    return v;
}
__device__ __forceinline__ uint2 ldg_q64(const void* p) {
    uint2 v;
    asm volatile(LD_Q ".v2.u32 {%0,%1}, [%2];" : "=r"(v.x), "=r"(v.y) : "l"(p) : "memory");
    return v;
}
__device__ __forceinline__ void red_v4(float4* p, float a, float b, float c, float d) {
    asm volatile("red.global.add.v4.f32 [%0], {%1,%2,%3,%4};" ::"l"(p), "f"(a), "f"(b), "f"(c), "f"(d) : "memory");
}
__device__ __forceinline__ uint2 down_row(uint2 r, const float* wd) {
    float x0 = bflo(r.x), x1 = bfhi(r.x), x2 = bflo(r.y), x3 = bfhi(r.y);
    float y[4];
#pragma unroll
    for (int j = 0; j < 4; j++) y[j] = x0 * wd[j] + x1 * wd[4 + j] + x2 * wd[8 + j] + x3 * wd[12 + j];
    return make_uint2(pack_bf2(y[0], y[1]), pack_bf2(y[2], y[3]));
}
__device__ __forceinline__ uint32_t prmt(uint32_t a, uint32_t b, uint32_t s) {
    uint32_t r;
    asm("prmt.b32 %0, %1, %2, %3;" : "=r"(r) : "r"(a), "r"(b), "r"(s));
    return r;
}
__device__ __forceinline__ uint32_t bitsel(uint32_t a, uint32_t b, uint32_t m) {
    uint32_t r;
    asm("lop3.b32 %0, %1, %2, %3, 0xE4;" : "=r"(r) : "r"(a), "r"(b), "r"(m));
    return r;
}
__device__ __forceinline__ uint32_t pack_h2(float lo, float hi) {
    uint32_t r;
    asm("cvt.rn.f16x2.f32 %0, %1, %2;" : "=r"(r) : "f"(hi), "f"(lo));
    return r;
}
__device__ __forceinline__ uint32_t mul_h2(uint32_t a, uint32_t b) {
    uint32_t r;
    asm("mul.rn.f16x2 %0, %1, %2;" : "=r"(r) : "r"(a), "r"(b));
    return r;
}
__device__ __forceinline__ uint32_t lds32nv(uint32_t a) {
    uint32_t v;
    asm volatile("ld.shared.u32 %0, [%1];" : "=r"(v) : "r"(a));
    return v;
}
__device__ __forceinline__ uint32_t lds16nv(uint32_t a) {
    uint32_t v;
    asm volatile("ld.shared.u16 %0, [%1];" : "=r"(v) : "r"(a));
    return v;
}
#define X_CR1
#define X_CR2
#define X_ST1
#define X_ST2
#define ST_Q "st.relaxed.gpu.global"
__device__ __forceinline__ void stg_q128(void* p, uint32_t a, uint32_t b, uint32_t c, uint32_t d, bool on) {
    asm volatile("{.reg .pred q; setp.ne.u32 q, %5, 0; @q " ST_Q ".v4.u32 [%0], {%1,%2,%3,%4};}"
                 ::"l"(p), "r"(a), "r"(b), "r"(c), "r"(d), "r"((uint32_t)on) : "memory");
}
__device__ __forceinline__ void stg_q64(void* p, uint32_t a, uint32_t b, bool on) {
    asm volatile("{.reg .pred q; setp.ne.u32 q, %3, 0; @q " ST_Q ".v2.u32 [%0], {%1,%2};}"
                 ::"l"(p), "r"(a), "r"(b), "r"((uint32_t)on) : "memory");
}
__device__ __forceinline__ void st_rlx_if(uint32_t* p, uint32_t v, bool on) {
    asm volatile("{.reg .pred q; setp.ne.u32 q, %2, 0; @q st.relaxed.gpu.global.u32 [%0], %1;}" ::"l"(p), "r"(v), "r"((uint32_t)on) : "memory");
}
__device__ __forceinline__ uint32_t ld_rlx_if(const uint32_t* p, bool on) {
    uint32_t v;
    asm volatile("{.reg .pred q; setp.ne.u32 q, %2, 0; mov.b32 %0, 0; @q ld.relaxed.gpu.global.u32 %0, [%1];}" : "=&r"(v) : "l"(p), "r"((uint32_t)on) : "memory");
    return v;
}
__device__ __forceinline__ void ldq128_keep(uint4& v, const void* p, bool on) {
    asm volatile("{.reg .pred q; setp.ne.u32 q, %5, 0; @q ld.relaxed.gpu.global.v4.u32 {%0,%1,%2,%3}, [%4];}"
                 : "+r"(v.x), "+r"(v.y), "+r"(v.z), "+r"(v.w) : "l"(p), "r"((uint32_t)on) : "memory");
}
__device__ __forceinline__ void ldq64_keep(uint2& v, const void* p, bool on) {
    asm volatile("{.reg .pred q; setp.ne.u32 q, %3, 0; @q ld.relaxed.gpu.global.v2.u32 {%0,%1}, [%2];}"
                 : "+r"(v.x), "+r"(v.y) : "l"(p), "r"((uint32_t)on) : "memory");
}
__device__ __forceinline__ void atoms_add_keep(uint32_t& o, uint32_t a, uint32_t v, bool on) {
    asm volatile("{.reg .pred q; setp.ne.u32 q, %3, 0; @q atom.shared.add.u32 %0, [%1], %2;}" : "+r"(o) : "r"(a), "r"(v), "r"((uint32_t)on) : "memory");
}
__device__ __forceinline__ void reds_add(uint32_t a, uint32_t v) { asm volatile("red.shared.add.u32 [%0], %1;" ::"r"(a), "r"(v) : "memory"); }
__device__ __forceinline__ void sts32_if(uint32_t a, uint32_t v, bool on) {
    asm volatile("{.reg .pred q; setp.ne.u32 q, %2, 0; @q st.shared.u32 [%0], %1;}" ::"r"(a), "r"(v), "r"((uint32_t)on) : "memory");
}
__device__ __forceinline__ void sts64_if(uint32_t a, uint32_t x, uint32_t y, bool on) {
    asm volatile("{.reg .pred q; setp.ne.u32 q, %3, 0; @q st.shared.v2.u32 [%0], {%1,%2};}" ::"r"(a), "r"(x), "r"(y), "r"((uint32_t)on) : "memory");
}
__device__ __forceinline__ void lds128_keep(uint4& v, uint32_t a, bool on) {
    asm volatile("{.reg .pred q; setp.ne.u32 q, %5, 0; @q ld.volatile.shared.v4.u32 {%0,%1,%2,%3}, [%4];}"
                 : "+r"(v.x), "+r"(v.y), "+r"(v.z), "+r"(v.w) : "r"(a), "r"((uint32_t)on) : "memory");
}
__device__ __forceinline__ void or3_if(uint32_t& x, uint32_t a, uint32_t b, bool on) {
    asm("{.reg .pred q; setp.ne.u32 q, %3, 0; @q lop3.b32 %0, %0, %1, %2, 0xfe;}" : "+r"(x) : "r"(a), "r"(b), "r"((uint32_t)on));
}
__device__ __forceinline__ uint32_t clk() {
    uint32_t t;
    asm volatile("mov.u32 %0, %%clock;" : "=r"(t) :: "memory");
    return t;
}
__device__ __forceinline__ void sg_add(int row, float a, float b, float c, float d) {
    red_v4(g_Sg + row, a, b, c, d);
    st_rlx(g_dirty + (row >> 5), 1u);
}
__device__ __forceinline__ void slow_add(const uint2* m, uint32_t sb, int in, int out, float c) {
    const uint2 r = __ldg(m + in);
    const float x[4] = {bflo(r.x), bfhi(r.x), bflo(r.y), bfhi(r.y)};
    float y[4] = {0.f, 0.f, 0.f, 0.f};
#pragma unroll
    for (int k = 0; k < 4; k++) {
        const uint4 q = lds128(sb + SM_W + 320 + k * 16);
        y[0] = k ? y[0] + x[k] * __uint_as_float(q.x) : x[k] * __uint_as_float(q.x);
        y[1] = k ? y[1] + x[k] * __uint_as_float(q.y) : x[k] * __uint_as_float(q.y);
        y[2] = k ? y[2] + x[k] * __uint_as_float(q.z) : x[k] * __uint_as_float(q.z);
        y[3] = k ? y[3] + x[k] * __uint_as_float(q.w) : x[k] * __uint_as_float(q.w);
    }
    const uint32_t lo = pack_bf2(y[0], y[1]), hi = pack_bf2(y[2], y[3]);
    sg_add(out, c * bflo(lo), c * bfhi(lo), c * bflo(hi), c * bfhi(hi));
}

struct Mat4 { uint32_t b[4]; };
__device__ __forceinline__ Mat4 load_mat4(const __nv_bfloat16* w, int lane) {
    const unsigned short* u = (const unsigned short*)w + (lane >> 2 & 1);
    const bool on = lane >> 3 == (lane & 3);
    Mat4 m;
#pragma unroll
    for (int k = 0; k < 4; k++) m.b[k] = on ? u[(k & 1) * 8 + (k & 2)] | (uint32_t)u[(k & 1) * 8 + 4 + (k & 2)] << 16 : 0u;
    return m;
}
__device__ __forceinline__ void mul4(const uint4& x, const Mat4& m, float (&y)[8]) {
#pragma unroll
    for (int h = 0; h < 2; h++)
        asm("mma.sync.aligned.m16n8k16.row.col.f32.bf16.bf16.f32 {%0,%1,%2,%3}, {%4,%5,%6,%7}, {%8,%9}, {%10,%10,%10,%10};"
            : "=f"(y[2 * h]), "=f"(y[2 * h + 1]), "=f"(y[4 + 2 * h]), "=f"(y[5 + 2 * h])
            : "r"(x.x), "r"(x.z), "r"(x.y), "r"(x.w), "r"(m.b[2 * h]), "r"(m.b[2 * h + 1]), "f"(0.f));
}

struct Scale { uint32_t eb[4]; bool allslow; };
__device__ __forceinline__ void md_stats(const uint4& in, const Mat4& wd, int lane) {
    float y[8];
    mul4(in, wd, y);
    uint32_t mx[4], se[4];
#pragma unroll
    for (int c = 0; c < 4; c++) {
        uint32_t a = __float_as_uint(y[c]) & 0x7fffffffu, b = __float_as_uint(y[4 + c]) & 0x7fffffffu;
        if (a >= 0x7f800000u) a = 0;
        if (b >= 0x7f800000u) b = 0;
        mx[c] = __reduce_max_sync(0xffffffffu, max(a, b));
        se[c] = __reduce_add_sync(0xffffffffu, (a >> 23) + (b >> 23) + (a ? 1u << 20 : 0u) + (b ? 1u << 20 : 0u));
    }
    if (lane < 4) {
        asm volatile("red.shared.max.u32 [%0], %1;" ::"r"(SB + SM_STAT + lane * 4), "r"(lane == 0 ? mx[0] : lane == 1 ? mx[1] : lane == 2 ? mx[2] : mx[3]) : "memory");
        reds_add(SB + SM_STAT + 16 + lane * 4, lane == 0 ? se[0] : lane == 1 ? se[1] : lane == 2 ? se[2] : se[3]);
    }
}
__device__ __forceinline__ Scale get_scale(uint32_t sb) {
    Scale s;
    s.allslow = false;
#pragma unroll
    for (int k = 0; k < 4; k++) {
        const uint32_t mx = lds32(sb + SM_STAT + 4 * k), se = lds32(sb + SM_STAT + 16 + 4 * k);
        const uint32_t mean = (uint32_t)__fdividef((float)(se & 0xfffffu), (float)max(se >> 20, 1u));
        uint32_t eb = min(min((mx + 0x6e0000u) >> 23, mean + 5u), 227u);
        if (eb < 27u) { s.allslow = s.allslow || mx != 0; eb = 27u; }
        if (eb > 170u) s.allslow = true;
        s.eb[k] = eb;
    }
    return s;
}

__device__ __forceinline__ uint32_t probe_rt(uint32_t* p) {
    uint32_t best = 0xffffffffu;
#pragma unroll 1
    for (int r = 0; r < CFG_PROBES; r++) {
        const uint32_t t0 = clock();
        uint32_t v;
        asm volatile("atom.relaxed.gpu.global.add.u32 %0, [%1], 1;" : "=r"(v) : "l"(p) : "memory");
        if (v > 100000u) __trap();
        const uint32_t t1 = clock();
        best = min(best, t1 - t0);
    }
    return best;
}
__device__ __forceinline__ uint32_t* pub_ptr(const Params& p, int blk, uint32_t sel) {
    const int pr = blk / 44;
    return (uint32_t*)(p.ring + PROBE_OFF + (pr ? 4096u << pr : 0u) + (sel << 12) + 2176 + (blk - pr * 44) * 32);
}
__device__ __forceinline__ void probe(const Params& p, uint32_t sb, int w, int lane) {
    const int blk = blockIdx.x, pr = w >> 1;
    uint32_t off = PROBE_OFF + blk * 16 + (pr ? 4096u << pr : 0u);
    if (pr == 7) off = blk < NWIN ? blk * WIN + 4064 : PROBE_OFF + 3584 + blk % 16 * 32;
    off += (w & 1) * 4096;
    if (lane < 8) st_rlx((uint32_t*)(p.ring + (off & ~31u)) + lane, 0u);
    if (lane == 0) sts32(sb + SM_PROBE + w * 4, probe_rt((uint32_t*)(p.ring + off)));
}
__device__ __forceinline__ void assign_role(const Params& p, uint32_t sb, int lane) {
    {
        const bool x = lane < 8 && lds32(sb + SM_PROBE + lane * 8 + 4) < lds32(sb + SM_PROBE + lane * 8);
        const uint32_t near = __ballot_sync(0xffffffffu, x), bits = near & 1 ? ~near | 1u : near;
        const uint32_t tag = (lds32(sb + SM_MISC + 16) + 1) << 30;
        if (lane < 16) st_rlx(pub_ptr(p, blockIdx.x, lane >> 3) + (lane & 7), tag | (bits & 0xffu));
        constexpr int K = (NCTA + 31) / 32;
        __nanosleep(CFG_P0);
        uint32_t v[K], bad;
        int guard = 0;
        do {
            bad = 0;
#pragma unroll
            for (int k = 0; k < K; k++) {
                const int b = min(lane + 32 * k, NCTA - 1);
                v[k] = ld_rlx(pub_ptr(p, b, near >> (b / 44) & 1));
                bad |= v[k] ^ tag;
            }
            bad = __any_sync(0xffffffffu, bad >> 30);
            if (bad) __nanosleep(CFG_PSLEEP);
            if (++guard > GUARD) __trap();
        } while (bad);
#pragma unroll
        for (int k = 0; k < K; k++) sts32(sb + SM_PUB + (lane + 32 * k) * 4, v[k]);
    }
    __syncwarp();
    constexpr int NP = NCTA / 2, NTAB = H2 + H3;
    const int me = blockIdx.x >> 1, odd = blockIdx.x & 1;
    uint32_t pp[3], key[3];
    int n1 = 0;
#pragma unroll
    for (int k = 0; k < 3; k++) {
        const int i = lane + 32 * k;
        pp[k] = lds32(sb + SM_PUB + min(i, NP - 1) * 8) & 1;
        key[k] = (i * CFG_KM % CFG_KN) << 8 | i;
        n1 += 2 * __popc(__ballot_sync(0xffffffffu, i < NP && pp[k]));
    }
    bool fixed = n1 < NTAB || NCTA - n1 < NTAB;
    if (fixed) {
        n1 = NP / 2 * 2;
        pp[0] = pp[1] = pp[2] = lane & 1;
    }
    const uint32_t mine = __shfl_sync(0xffffffffu, (me < 32 ? key[0] : me < 64 ? key[1] : key[2]) * 2 + (me < 32 ? pp[0] : me < 64 ? pp[1] : pp[2]), me & 31);
    const int part = mine & 1;
    int pos = odd;
#pragma unroll
    for (int k = 0; k < 3; k++) pos += 2 * __popc(__ballot_sync(0xffffffffu, lane + 32 * k < NP && pp[k] == (uint32_t)part && key[k] < mine / 2));
    const int role = pos < H2 ? 1 : pos < NTAB ? 2 : 0;
    const int id = pos < H2 ? part * H2 + pos : pos < NTAB ? part * H3 + pos - H2 : (part ? NCTA - n1 - NTAB : 0) + pos - NTAB;
    const uint32_t v = lds32(sb + SM_PUB + lane * 4);
    uint32_t lin = 0;
#pragma unroll
    for (int b = 0; b < 6; b++) lin |= (__popc(__ballot_sync(0xffffffffu, (v >> (b + 1)) & 1)) > 16 ? 1u : 0u) << b;
    if (lane == 0) {
        sts32(sb + SM_MISC, role << 8 | id);
        sts32(sb + SM_MISC + 4, lin);
        sts32(sb + SM_MISC + 8, NCTA - n1 - NTAB);
        sts32(sb + SM_MISC + 20, part);
        sts32(sb + SM_MISC + 12, role == 0 ? id : role == 1 ? N1 + id : N1 + N2 + id);
    }
}
__device__ __forceinline__ uint32_t sel_of(uint32_t sb, int widx, uint32_t k, int part) {
    return (__popc(k & lds32(sb + SM_MISC + 4)) ^ (lds32(sb + SM_PUB + widx * 4) >> 7) ^ part) & 1;
}
__device__ __forceinline__ uint32_t gran_off(uint32_t sb, int widx, int k, int part) { return (2 * k + sel_of(sb, widx, k, part)) << 12; }
__device__ __forceinline__ uint32_t q1a_off(uint32_t sb, int src, int blk, int part) { return gran_off(sb, 2 * blk + part, src >> 1, part) + (src & 1) * 2048; }
__device__ __forceinline__ uint32_t q1h_off(uint32_t sb, int src, int blk, int part) { return gran_off(sb, 2 * blk + part, 32 + (src >> 2), part) + (src & 3) * 1024; }
__device__ __forceinline__ uint32_t* ctl_word(const Params& p, uint32_t sb, int k, int word, int part) {
    const int widx = CWIN + lds32(sb + SM_MISC + 16);
    return (uint32_t*)(p.ring + (widx * WIN + ((2 * k + sel_of(sb, widx, k, part)) << 12))) + word;
}
__device__ __forceinline__ uint32_t* cred1_of(const Params& p, uint32_t sb, int src) { return ctl_word(p, sb, src >> 3, (src & 7) * 128, src >= (int)lds32(sb + SM_MISC + 8)); }
__device__ __forceinline__ uint32_t* fin1_of(const Params& p, uint32_t sb, int dst) { return ctl_word(p, sb, 8 + (dst >> 3), (dst & 7) * 128, dst / H2); }
__device__ __forceinline__ uint32_t* cred2_of(const Params& p, uint32_t sb, int src) { return ctl_word(p, sb, 16 + (src >> 3), (src & 7) * 128, src / H2); }
__device__ __forceinline__ uint32_t* fin2_of(const Params& p, uint32_t sb, int dst) { return ctl_word(p, sb, 24 + (dst >> 3), (dst & 7) * 128, dst / H3); }
__device__ __forceinline__ uint32_t* rdy_of(const Params& p, uint32_t sb, int word, int part) { return ctl_word(p, sb, 28, word, part); }
__device__ __forceinline__ uint32_t q2_off(uint32_t sb, int blk, int dst) {
    return (N2 + dst) * WIN + gran_off(sb, N2 + dst, (blk >> 1) * 4 + (blk & 1), dst / H3);
}
template <bool IS1>
__device__ __forceinline__ void clear_queues(const Params& p, uint32_t sb, int id, int lane) {
    constexpr int NA = (N1 + 1) / 2, NG = NA + (N1 + 3) / 4, N = IS1 ? NG * N2 : NI * 2;
    if (IS1) {
#pragma unroll 1
        for (int k = 0; k < 8; k++) sts128(sb + SM_ZERO + (k * 32 + lane) * 16, make_uint4(0, 0, 0, 0));
        if (lane == 0) spin_ge(rdy_of(p, sb, 320, lds32(sb + SM_MISC + 20)), NTAIL);
    }
    __syncwarp();
    fence_async_smem();
    for (int k = IS1 ? id + (lane < CFG_CLN ? lane : N) * N1 : lane; k < N; k += IS1 ? CFG_CLN * N1 : 32) {
        if (IS1 && k >= CFG_CLN * N1) __nanosleep(CFG_CLS);
        const int wi = k / NG, g = k - wi * NG;
        const uint32_t off = IS1 ? wi * WIN + gran_off(sb, wi, g < NA ? g : 32 + g - NA, wi & 1) : q2_off(sb, k >> 1, id) + (k & 1) * 16384;
        bulk_store(p.ring + off, sb + SM_ZERO, 4096);
    }
    asm volatile("cp.async.bulk.commit_group;" ::: "memory");
    asm volatile("cp.async.bulk.wait_group 0;" ::: "memory");
    TR(21, IS1 && lane == 0);
    if (!IS1) {
        fence_async_all();
        __syncwarp();
        fence_gpu();
        if (lane < NI) red_rlx(rdy_of(p, sb, id / H3 * H2 + lane, id / H3), 1u);
    }
    __syncwarp();
}

struct In8 { uint4 a[2], o[2]; uint2 g[2]; };
__device__ __forceinline__ void p1_load(const Params& p, In8& r, int i4) {
#pragma unroll
    for (int u = 0; u < 2; u++) {
        [[maybe_unused]] uint32_t x, y;
        asm volatile("tex.1d.v4.u32.s32 {%0,%1,%2,%3}, [%4, {%5}];" : "=r"(r.a[u].x), "=r"(r.a[u].y), "=r"(r.a[u].z), "=r"(r.a[u].w) : "l"(p.t_in), "r"(i4 + u * 32));
        asm volatile("tex.1d.v4.u32.s32 {%0,%1,%2,%3}, [%4, {%5}];" : "=r"(r.o[u].x), "=r"(r.o[u].y), "=r"(r.o[u].z), "=r"(r.o[u].w) : "l"(p.t_out), "r"(i4 + u * 32));
        asm volatile("tex.1d.v4.u32.s32 {%0,%1,%2,%3}, [%4, {%5}];" : "=r"(r.g[u].x), "=r"(r.g[u].y), "=r"(x), "=r"(y) : "l"(p.t_ang), "r"(i4 + u * 32));
    }
}
__device__ __forceinline__ uint32_t imad(uint32_t a, uint32_t b, uint32_t c) {
    uint32_t r;
    asm("mad.lo.u32 %0, %1, %2, %3;" : "=r"(r) : "r"(a), "r"(b), "r"(c));
    return r;
}
__device__ __forceinline__ unsigned char* ring_ptr(const Params& p, uint32_t lo) {
    uint64_t r;
    asm("mov.b64 %0, {%1, %2};" : "=l"(r) : "r"(lo), "r"(p.ring_hi));
    return (unsigned char*)r;
}
__device__ __forceinline__ uint32_t keep32(uint32_t x) {
    return __shfl_sync(0xffffffffu, x, threadIdx.x & 31);
}
__device__ __forceinline__ uint32_t opaque32(uint32_t x) {
    asm volatile("" : "+r"(x));
    return x;
}
template <typename T> __device__ __forceinline__ T* opaque(T* p) {
    asm volatile("" : "+l"(p));
    return p;
}
template <int LUT> __device__ __forceinline__ uint32_t lop3(uint32_t a, uint32_t b, uint32_t c) {
    uint32_t r;
    asm("lop3.b32 %0, %1, %2, %3, %4;" : "=r"(r) : "r"(a), "r"(b), "r"(c), "n"(LUT));
    return r;
}
__device__ __forceinline__ uint32_t dp4(uint32_t a, uint32_t b, uint32_t c) {
    uint32_t r;
    asm("dp4a.u32.u32 %0, %1, %2, %3;" : "=r"(r) : "r"(a), "r"(b), "r"(c));
    return r;
}
__device__ __forceinline__ uint32_t dp2(uint32_t a, uint32_t b, uint32_t c) {
    uint32_t r;
    asm("dp2a.lo.u32.u32 %0, %1, %2, %3;" : "=r"(r) : "r"(a), "r"(b), "r"(c));
    return r;
}
__device__ __forceinline__ void p1_put(uint32_t sb, uint32_t wa, uint32_t wb, uint32_t old, bool on) {
    asm volatile("{.reg .pred q; setp.ne.u32 q, %3, 0; @q st.shared.v2.u32 [%0], {%1,%2};}"
                 ::"r"(sb + A_ST + prmt(old, wb, 0xf762)), "r"(wa), "r"(prmt(wb, old, 0x7210)), "r"((uint32_t)on) : "memory");
}
__device__ __forceinline__ void p1_slow_tile(const Params& p, uint32_t sb, int i4) {
    const float f = __bfloat162float(p.freq[0]);
#pragma unroll 1
    for (int u = 0; u < 8; u++) {
        const int k4 = i4 + (u >> 2) * 32;
        if (k4 < p.n4) {
            const size_t t = (size_t)k4 * 4 + (u & 3);
            const float x = __bfloat162float(__float2bfloat16(f * __bfloat162float(p.angle[t])));
            slow_add(p.m, sb, p.idx_in[t], p.idx_out[t], __bfloat162float(__float2bfloat16(cosf(x))));
        }
    }
}
__device__ __forceinline__ void role_p1(const Params& p, uint32_t sb, int id, int w, int lane) {
    lane = keep32(lane);
    const uint32_t f2 = (uint32_t)__bfloat16_as_ushort(p.freq[0]) * 0x10001u;
    constexpr int TG = CFG_TG, NTK = P1W;
    static_assert(NTK <= 16, "tickets");
    const int tc = (w + id) % NTK, first = (N1 * P1W + tc) * (TG * 64);
    uint32_t* const tickets = opaque(ctl_word(p, sb, 29 + tc / 8, tc % 8 * 128 + lane, tc & 1));
    auto draw = [&]() {
        uint32_t t = 0;
        asm volatile("{.reg .pred q; setp.eq.u32 q, %2, 0; @q atom.relaxed.gpu.global.add.u32 %0, [%1], 1;}" : "+r"(t) : "l"(tickets), "r"(lane) : "memory");
        return t;
    };
    int i4 = (id * P1W + w) * (TG * 64);
    In8 r;
    ACC_DECL
    uint32_t tk = draw();
    p1_load(p, r, i4 + lane);
    while (i4 < p.n4) {
        const int cur = i4;
        i4 += 64;
        if (i4 % (TG * 64) == 0) {
            i4 = min(__shfl_sync(0xffffffffu, tk, 0), 0x7fffffffu / (NTK * TG * 64) - N1 * P1W / NTK - 2) * (NTK * TG * 64) + first;
            tk = draw();
        }
        uint32_t wa[8], wb[8], x2[4];
        x2[0] = mul_bf2(r.g[0].x, f2); x2[1] = mul_bf2(r.g[0].y, f2);
        x2[2] = mul_bf2(r.g[1].x, f2); x2[3] = mul_bf2(r.g[1].y, f2);
        const uint32_t mx = maxabs_bf2(maxabs_bf2(x2[0], x2[1]), maxabs_bf2(x2[2], x2[3]));
        const bool fast = __all_sync(0xffffffffu, cur + 64 <= p.n4 && ((mx & 0x7fffu) <= 0x4300u) && ((mx & 0x7fff0000u) <= 0x43000000u));
        {
            const uint32_t in[8] = {r.a[0].x, r.a[0].y, r.a[0].z, r.a[0].w, r.a[1].x, r.a[1].y, r.a[1].z, r.a[1].w};
            const uint32_t ou[8] = {r.o[0].x, r.o[0].y, r.o[0].z, r.o[0].w, r.o[1].x, r.o[1].y, r.o[1].z, r.o[1].w};
#pragma unroll
            for (int j = 0; j < 8; j += 2) {
                const uint32_t ch = mul_h2(pack_h2(__cosf(bflo(x2[j >> 1])), __cosf(bfhi(x2[j >> 1]))), 0x24002400u);
#pragma unroll
                for (int k = j; k < j + 2; k++) {
                    const uint32_t blk = __umulhi(in[k], p.magic2), il = imad(blk, p.nrows2, in[k]);
                    wa[k] = k & 1 ? bitsel(ch, il, 0xffff0000u) : imad(ch, 65536u, il);
                    wb[k] = imad(blk, 1u << 21, imad(ou[k] >> 5, 1u - (1u << 21), ou[k] << 16));
                }
            }
        }
        p1_load(p, r, i4 + lane);
        if (fast) {
            uint32_t old[8], any = 0;
#pragma unroll
            for (int j = 0; j < 8; j++) old[j] = atoms_add(dp2(wb[j], 0x400u, 0u) + (sb + A_CNT), 0x80001u);
#pragma unroll
            for (int j = 0; j < 8; j++) any |= old[j];
            if (!__any_sync(0xffffffffu, any & 0xffe0u)) {
#pragma unroll
                for (int j = 0; j < 8; j++) p1_put(sb, wa[j], wb[j], old[j], true);
            } else {
                uint32_t pend = 0;
#pragma unroll
                for (int j = 0; j < 8; j++) { p1_put(sb, wa[j], wb[j], old[j], !(old[j] & 0xffe0u)); if (old[j] & 0xffe0u) pend |= 1u << j; }
                ACC(0, 1)
                for (int guard = 0; __any_sync(0xffffffffu, pend); guard++) {
                    __nanosleep(CFG_BSLEEP);
                    ACC(1, 1)
#pragma unroll
                    for (int j = 0; j < 8; j++) {
                        if (__any_sync(0xffffffffu, pend >> j & 1)) {
                            const uint32_t c = lds32v(sb + A_CNT + (pend >> j & 1 ? wb[j] >> 16 : 0) * 4);
                            const bool go = (pend >> j & 1) && (((old[j] >> 19) - (c >> 19) + c) & 8191u) < 32u;
                            p1_put(sb, wa[j], wb[j], old[j], go);
                            if (go) pend &= ~(1u << j);
                        }
                    }
                    if (guard > GUARD) __trap();
                }
            }
        } else {
            p1_slow_tile(p, sb, cur + lane);
            __syncwarp();
        }
    }
    __syncwarp();
    mbar_arrive_if(sb + SM_DONE, lane == 0);
    ACC_SAVE
}

__device__ __forceinline__ void role_flush(const Params& p, uint32_t sb, int id, int f, int lane) {
    lane = keep32(lane);
    const int half = lane >> 4, o = lane >> 2, q = lane & 3;
    const uint32_t hm = keep32(half ? 0xffff0000u : 0xffffu), lth = keep32(((1u << lane) - 1) & hm);
    const uint32_t list = sb + A_LIST + f * LISTB, cnt = keep32(sb + A_CNT + (f * GPW * 32 + lane) * 4);
    const uint32_t cred = opaque32(sb + SM_CRED + (half * 32 + f * GPW) * 4);
    const uint32_t pa = opaque32(p.ring_lo + (id >> 1) * 8192 + (id & 1) * 2048 + q * 16);
    const uint32_t ph = opaque32(p.ring_lo + (32 + (id >> 2)) * 8192 + (id & 3) * 1024 + q * 8 - 2048);
    const uint32_t sa = q * 16 + (o & 1) * 64;
    uint32_t qo[GPW], hs[GPW], cr[4] = {0, 0, 0, 0};
#pragma unroll
    for (int g = 0; g < GPW; g++) {
        const int blk = f * GPW + g;
        qo[g] = 32u << 25;
        const uint32_t sa = sel_of(sb, 2 * blk + half, id >> 1, half), sh = sel_of(sb, 2 * blk + half, 32 + (id >> 2), half);
        hs[g] = sa << 31 | (2 * sh + 1 - sa) << 22 | 1u << 24 | (lane & 15) << 15 | (blk * 32 + lane) * 2;
    }
    uint4 x[KR] = {}, y[KR] = {};
    uint32_t c[GPW] = {};
    auto scan = [&]() {
#pragma unroll
        for (int g = 0; g < GPW; g++) c[g] = lds32v(cnt + g * 128);
    };
    auto credits = [&]() {
        if (GPW == 4) { const uint4 v = lds128(cred); cr[0] = v.x; cr[1] = v.y; cr[2] = v.z; cr[3] = v.w; }
        else { const uint2 v = lds64v(cred); cr[0] = v.x; cr[1] = v.y; }
    };
    ACC_DECL
    int guard = 0;
    bool idle = false, done = false;
    while (true) {
        uint32_t fr[GPW], rank[GPW], num = 0, left = 0;
        bool ok[GPW];
        if (idle && !done && __all_sync(0xffffffffu, mbar_test(sb + SM_DONE, 0))) {
            done = true;
            TR(17, f == 0 && lane == 0);
#pragma unroll
            for (int g = 0; g < GPW; g++) {
                const uint32_t u = lds32v(cnt + g * 128) & 31u, hd = hs[g] ^ (u & 16u ? imad(hs[g], 1u << 24, 1u) & 0x01000001u : 0u);
#pragma unroll 2
                for (uint32_t j = 0, k; k = (j + lane) & 15u, j < 16; j++)
                    sts64_if(sb + A_ST + ((hd & 0x7ffu) << 7) + k * 8, p.rows2, (lane * 16 + k) | (hd & 0x1000000u), (u & 15u) && k >= (u & 15u));
                reds_add(cnt + g * 128, ((0u - u) & 15u) * 0x80001u);
            }
            __syncwarp();
            scan();
        }
#pragma unroll
        for (int g = 0; g < GPW; g++) {
            const bool isfull = c[g] & 0xfff0u;
            rank[g] = __popc(__ballot_sync(0xffffffffu, isfull) & lth);
            ok[g] = isfull && (int)(rank[g] << 25) < (int)(cr[g] - qo[g] + (63u << 25));
            ACC(2, __popc(__ballot_sync(0xffffffffu, isfull && !ok[g])))
        }
#pragma unroll
        for (int g = 0; g < GPW; g++) {
            const uint32_t m = __ballot_sync(0xffffffffu, ok[g]), n = __popc(m & hm), all = __popc(m), e = num + rank[g] + (half ? all - n : 0u);
            sts32_if(KR == 2 ? list + (e & 48u) * 4 + (e & 7u) * 8 + (e >> 1 & 4u) : imad(e, 4u, list), bitsel(imad(rank[g], 1u << 25, qo[g]), hs[g], 0x7e000000u), ok[g]);
            if (ok[g]) hs[g] ^= imad(hs[g], 1u << 24, 1u) & 0x01000001u;
            fr[g] = ok[g] ? 0u - 16u : 0u;
            left |= c[g] + fr[g];
            qo[g] = imad(n, 1u << 25, qo[g]);
            num += all;
        }
        __syncwarp();
        ACC(0, 1) ACC(1, num)
        if (num) {
            uint32_t la = list + o * (KR == 2 ? 8 : 4);
            int todo = (int)num - o, rest = num;
            do {
                uint32_t d[KR];
                if (KR == 2) { const uint2 v = lds64v(la); d[0] = v.x; d[KR - 1] = v.y; }
                else {
#pragma unroll
                    for (int k = 0; k < KR; k++) d[k] = lds32v(la + 32 * k);
                }
                while (true) {
                    uint32_t bad = 0;
#pragma unroll
                    for (int k = 0; k < KR; k++) {
                        const uint32_t m = d[k] & 0x7ffu;
                        lds128_keep(x[k], imad(m, 128u, sa) + (sb + A_ST), todo > 8 * k);
                        lds128_keep(y[k], imad(m, 128u, sa ^ 64) + (sb + A_ST), todo > 8 * k);
                    }
#pragma unroll
                    for (int k = 0; k < KR; k++)
                        or3_if(bad, lop3<0x7e>(x[k].y, x[k].w, d[k]), lop3<0x7e>(y[k].y, y[k].w, d[k]), todo > 8 * k);
                    if (!__any_sync(0xffffffffu, (int)imad(bad, 128u, 0u) < 0)) break;
                    if (++guard > GUARD) __trap();
                }
#pragma unroll
                for (int k = 0; k < KR; k++) {
                    const uint32_t mi = d[k] & 0x7e0u, dm = d[k] & 0xbec00000u;
                    x[k].x = bitsel(d[k], x[k].x, 0x40078000u);
                    x[k].y = prmt(x[k].y, x[k].w, 0x5410);
                    x[k].w = prmt(y[k].y, y[k].w, 0x5410);
                    y[k].x = bitsel(d[k], y[k].x, 0x40000000u);
                    y[k].y = y[k].z;
                    stg_q128(ring_ptr(p, dp4(dm, 0x20000000u, imad(mi, WIN / 32, pa))), x[k].x, x[k].y, x[k].z, x[k].w, X_ST1 todo > 8 * k);
                    stg_q64(ring_ptr(p, dp4(dm, 0x10200000u, imad(mi, WIN / 32, ph))), y[k].x, y[k].y, X_ST1 todo > 8 * k);
                }
                la += 32 * KR;
                todo -= 8 * KR;
                rest -= 8 * KR;
            } while (rest > 0);
#pragma unroll
            for (int g = 0; g < GPW; g++) c[g] = atoms_add(cnt + g * 128, fr[g]) + fr[g];
            credits();
            idle = num <= CFG_TH;
            if (done && !__any_sync(0xffffffffu, left & 0xffffu)) break;
            if (idle) { __nanosleep(CFG_TS); scan(); credits(); }
        } else {
            if (done && !__any_sync(0xffffffffu, left & 0xffffu)) break;
            idle = true;
            __nanosleep(CFG_FSLEEP);
            scan();
            credits();
            if (++guard > GUARD) __trap();
        }
    }
#pragma unroll
    for (int g = 0; g < GPW; g++) st_rlx_if(fin1_of(p, sb, half * H2 + f * GPW + g) + id, qo[g] - (32u << 25) + 1u, (lane & 15) == 0 && f * GPW + g < NI);
    mbar_arrive_if(sb + SM_DONE2, lane == 0);
    TR(18, f == 0 && lane == 0);
    ACC_SAVE
}
__device__ __forceinline__ void role_credit1(const Params& p, uint32_t sb, int id, int lane) {
    const uint32_t* const cred = cred1_of(p, sb, id) + lane * 2;
    for (int guard = 0; !__all_sync(0xffffffffu, mbar_test(sb + SM_DONE2, 0)); guard++) {
        const uint2 v = ldg_q64(cred);
        sts64(sb + SM_CRED + lane * 8, v.x, v.y);
        __nanosleep(CFG_C1SLEEP);
        if (guard > GUARD) __trap();
    }
}

__device__ __forceinline__ float h2f(uint32_t h) {
    float f;
    asm("{.reg .b16 t; cvt.u16.u32 t, %1; cvt.f32.f16 %0, t;}" : "=f"(f) : "r"(h));
    return f;
}
__device__ __forceinline__ void p2_slow(const Params& p, uint32_t sb, const uint32_t* tmp, int row0, uint32_t dst) {
#pragma unroll 1
    for (int j = 0; j < 4; j++)
        if (tmp[8 + j] & 0x40u) slow_add(p.m, sb, row0 + (tmp[j] & 0x7fffu), (tmp[4 + j] & 0x7fffu) * 32 + dst, h2f(tmp[j] >> 16) * 64.0f);
}
__device__ __forceinline__ uint32_t mul_h2_hi(uint32_t a, uint32_t b) {
    uint32_t r;
    asm("{.reg .b16 l, h; .reg .b32 t; mov.b32 {l, h}, %2; mov.b32 t, {h, h}; mul.rn.f16x2 %0, %1, t;}" : "=r"(r) : "r"(a), "r"(b));
    return r;
}
template <bool CHECK>
__device__ __forceinline__ void role_p2(const Params& p, uint32_t sb, int id, int w, int lane) {
    lane = keep32(lane);
    const int part = id / H2, blk = id - part * H2, row0 = blk * p.rows2;
    const int o = lane >> 2, q = lane & 3;
    uint32_t* const cbase = (uint32_t*)(p.ring + (CWIN + lds32(sb + SM_MISC + 16)) * WIN);
    const uint32_t cred = opaque32((uint32_t)(uintptr_t)(cbase + part * 32 + blk));
    const uint32_t pa = opaque32(p.ring_lo + (2 * blk + part) * WIN + q * 16), ph = opaque32(pa - q * 8);
    const uint32_t po = opaque32(p.ring_lo + (q2_off(sb, blk, part * H3) & ~4096u) + q * 16 + (o & 1) * 64);
    const uint32_t sel = __ballot_sync(0xffffffffu, q2_off(sb, blk, part * H3 + (lane & 15)) & 4096u) << 12;
    const uint32_t* const fins = fin1_of(p, sb, id);
    uint32_t st[QPW] = {}, sq[QPW] = {};
    uint4 qa[NBT];
    uint2 qh[NBT];
    auto load = [&](int k) {
        qa[k] = ldg_q128(ring_ptr(p, pa + (bitsel(sq[k], st[k] >> 19, 0x7f800u) & 0x7ffc0u)));
        qh[k] = ldg_q64(ring_ptr(p, ph + (bitsel(sq[k] >> 9, st[k] >> 20, 0x7fc00u) & 0x7ffe0u)));
    };
#pragma unroll
    for (int k = 0; k < QPW; k++) {
        const int src = w * QPW + k;
        st[k] = o << 25 | (src < N1 ? 1u : 5u);
        sq[k] = src < N1 ? q1h_off(sb, src, blk, part) << 9 | q1a_off(sb, src, blk, part) | (uint32_t)(cred1_of(p, sb, src) - cbase) / 8 : 0x7e000u * 513u;
    }
#pragma unroll
    for (int k = 0; k < NBT; k++) load(k);
    ACC_DECL
    int guard = 0;
    uint32_t streak = 0;
    while (true) {
        uint32_t nn[NBT], xx[NBT][4], hh[NBT][2], dd[NBT], any = 0;
        bool last = false;
#pragma unroll
        for (int k = 0; k < NBT; k++) {
            const uint4 a = qa[k];
            const uint2 h = qh[k];
            uint32_t n = 8;
            const uint32_t miss = __ballot_sync(0xffffffffu, (int)imad((a.x ^ st[k]) & (h.x ^ st[k]), 2u, 0u) >= 0);
            if (miss) {
                n = (__ffs(miss) - 1) >> 2;
                if (!__any_sync(0xffffffffu, st[k] & 8u)) { if (streak < CFG_PSTREAK) n &= CFG_PMASK; }
                else if (!__any_sync(0xffffffffu, ((st[k] >> 6) + ((n - o) << 19) ^ st[k]) & 0x1f80000u)) { st[k] |= 4u; last = true; }
            }
            ACC(1, n == 0) ACC(2, n != 0) ACC(3, n)
            st[k] = imad(n, 1u << 25, st[k]);
            st_rlx_if((uint32_t*)ring_ptr(p, imad(sq[k] & 0x7f0u, 32u, cred)), st[k], X_CR1 lane == 0 && n && (n < 8 || !(st[k] & CFG_CRM << 28)));
            xx[k][0] = bitsel(a.x, 0x00040000u, 0xbff87fffu); xx[k][1] = a.z; xx[k][2] = h.x & 0xbfffffffu; xx[k][3] = h.y;
            hh[k][0] = a.y; hh[k][1] = a.w; dd[k] = a.x >> 13 & 0x3cu; nn[k] = n;
            any |= n;
        }
        if (!any) {
#pragma unroll
            for (int k = 0; k < QPW; k++) {
                const uint32_t fin = ld_rlx(fins + ((sq[k] >> 12 & 62u) | (sq[k] >> 11 & 1u)));
                if (fin & 1u) st[k] |= (fin >> 6 & 0x1f80000u) | ((fin ^ (st[k] - (o << 25))) >> 25 ? 8u : 12u);
            }
            last = true;
            if (++guard > GUARD) __trap();
            streak++;
        } else streak = 0;
        if (last) {
            uint32_t all = 4u;
#pragma unroll
            for (int k = 0; k < QPW; k++) all &= st[k];
            last = __all_sync(0xffffffffu, all);
        }
        {
            uint32_t t[QPW], u[QPW];
#pragma unroll
            for (int k = 0; k < QPW; k++) { t[k] = st[(k + NBT) % QPW]; u[k] = sq[(k + NBT) % QPW]; }
#pragma unroll
            for (int k = 0; k < QPW; k++) { st[k] = t[k]; sq[k] = u[k]; }
        }
#pragma unroll
        for (int k = 0; k < NBT; k++) load(k);
#pragma unroll
      for (int k = 0; k < NBT; k++) {
        if (nn[k]) {
            const uint32_t* const x = xx[k];
            const uint32_t h0 = hh[k][0], h1 = hh[k][1], d4 = dd[k];
            const bool v = o < nn[k];
            uint32_t old = 0, ta[4], tb[4], w0[4], w1[4];
            atoms_add_keep(old, sb + SM_CNT2 + d4, 0x10001u, q == 0 && v);
#pragma unroll
            for (int j = 0; j < 4; j++) {
                ta[j] = lds32nv(dp2(x[j], 4u, 0u) + (sb + B_TA));
                tb[j] = lds16nv(dp2(x[j], 2u, 0u) + (sb + B_TB));
            }
            old = __shfl_sync(0xffffffffu, old, lane & 28);
            const uint32_t tag = old << 8 & 0x40000000u;
#pragma unroll
            for (int j = 0; j < 4; j++) {
                const uint32_t z = prmt(j & 2 ? h1 : h0, 0, j & 1 ? 0x4342 : 0x4140);
                const uint32_t t23 = prmt((ta[j] & 0x60076007u) * 2050u, tb[j], 0x5341) & 0xfffcffffu;
                w0[j] = (imad(z, 128u, j & 1 ? 0u : tag) & 0x78007800u) | mul_h2_hi(ta[j] & 0x9ff89ff8u, x[j]);
                w1[j] = (imad(z, 2048u, 0u) & 0x78007800u) | mul_h2_hi(t23, x[j]);
            }
            if (CHECK && v && ((tb[0] | tb[1] | tb[2] | tb[3]) & 0x40u)) {
                uint32_t tmp[12];
#pragma unroll
                for (int j = 0; j < 4; j++) {
                    tmp[j] = x[j]; tmp[4 + j] = (j & 2 ? h1 : h0) >> (j & 1 ? 16 : 0); tmp[8 + j] = tb[j];
                    if (tb[j] & 0x40u) { w0[j] &= 0x78007800u; w1[j] &= 0x78007800u; }
                }
                p2_slow(p, sb, tmp, row0, part * H3 + d4 / 4);
            }
            const uint32_t off = (bitsel(old >> 9, old >> 7, 0x0f80u) & 0x4f80u) + imad(d4, WIN / 4, (sel >> (d4 / 4) & 4096u) + po);
            bool wait = old & (0x10000u - NQ2);
            if (!__any_sync(0xffffffffu, wait)) {
                stg_q128(ring_ptr(p, off), w0[0], w1[0], w0[1], w1[1], X_ST2 v);
                stg_q128(ring_ptr(p, off ^ 64u), w0[2], w1[2], w0[3], w1[3], X_ST2 v);
            } else {
                bool pend = v;
                ACC(0, 1)
                for (int g2 = 0;; g2++) {
                    stg_q128(ring_ptr(p, off), w0[0], w1[0], w0[1], w1[1], pend && !wait);
                    stg_q128(ring_ptr(p, off ^ 64u), w0[2], w1[2], w0[3], w1[3], pend && !wait);
                    pend = wait;
                    if (!__any_sync(0xffffffffu, pend)) break;
                    __nanosleep(CFG_BSLEEP);
                    const uint32_t c = lds32v(sb + SM_CNT2 + d4);
                    wait = pend && (((old >> 16) - (c >> 16) + c) & 0xffffu) >= NQ2;
                    if (g2 > GUARD) __trap();
                }
            }
        }
      }
        if (last) break;
    }
    TR(17, w == 0 && lane == 0);
    __syncwarp();
    uint32_t rank = 0;
    if (lane == 0) { __threadfence_block(); rank = atoms_add(sb + SM_FIN, 1u); __threadfence_block(); }
    if (__shfl_sync(0xffffffffu, rank, 0) == P2W - 1 && lane < 16)
        st_rlx(fin2_of(p, sb, part * H3 + lane) + blk, FIN | (((lds32v(sb + SM_CNT2 + lane * 4) >> 16) - NQ2) & 0xffffu));
    __syncwarp();
    mbar_arrive_if(sb + SM_DONE, lane == 0);
    ACC_SAVE
}
__device__ __forceinline__ void role_credit(const Params& p, uint32_t sb, int id, int lane) {
    const uint32_t* const cred = cred2_of(p, sb, id) + (lane & 15);
    uint32_t last = 0;
    for (int guard = 0;; guard++) {
        if (__all_sync(0xffffffffu, mbar_test(sb + SM_DONE, 0))) break;
        const uint32_t c = ld_rlx(cred);
        if (lane < 16 && c != last) reds_add(sb + SM_CNT2 + lane * 4, 0u - ((c - last) & 0xffffu));
        last = c;
        __nanosleep(CFG_CSLEEP);
        if (guard > GUARD) __trap();
    }
}

__device__ __forceinline__ void p3_wrap(uint32_t sb, int id, const uint32_t* tmp) {
    const Scale sc = get_scale(sb);
#pragma unroll 1
    for (int j = 0; j < 8; j++) {
        const uint32_t old = tmp[4 + j], v = tmp[12 + j], nw = old + v, t = (old ^ nw) & (v ^ nw);
        if (t & 0x80008000u) {
            const float k = (t & 0x8000u) ? ((v & 0x8000u) ? -1.0f : 1.0f) : 0.0f;
            const float q = (t & 0x80000000u) ? ((int)v < 0 ? -65536.0f : 65536.0f) : 0.0f;
            const uint32_t e0 = (j & 1) ? sc.eb[2] : sc.eb[0], e1 = (j & 1) ? sc.eb[3] : sc.eb[1];
            const float lo = k * 65536.0f * __uint_as_float((e0 - 10) << 23), hi = (q - k) * __uint_as_float((e1 - 10) << 23);
            if (j & 1) sg_add(tmp[j >> 1] * 32 + id, 0.f, 0.f, lo, hi);
            else sg_add(tmp[j >> 1] * 32 + id, lo, hi, 0.f, 0.f);
        }
    }
}
__device__ __forceinline__ uint32_t p3_val(uint32_t w) {
    const uint32_t mk = prmt(w, 0, 0xBB99);
    return ((w & 0x07ff07ffu) ^ mk) - mk;
}
__device__ __forceinline__ void role_p3(const Params& p, uint32_t sb, int id, int w, int lane) {
    lane = keep32(lane);
    uint32_t* const cred = opaque(cred2_of(p, sb, id / H3 * H2 + w) + id % H3);
    const uint32_t pq = opaque32(p.ring_lo + q2_off(sb, w, id) + lane * 16);
    auto off = [&](uint32_t n) { return (n & 1u) << 11 | (n & 2u) << 13; };
    const uint32_t pp = opaque32(pq - lane * 16 + 112);
    const uint32_t* const finp = opaque(fin2_of(p, sb, id) + w);
    auto tag_of = [&](uint32_t n) { return ~n << 28; };
    uint32_t n = 0, fin = 0, pr = 0, pk = 0;
    uint4 v[4] = {};
    bool have = false, last = false;
    ACC_DECL
    int guard = 0;
    while (true) {
        const uint32_t ex = tag_of(n);
        const bool ok = have && !__any_sync(0xffffffffu, ((v[0].x ^ ex) | (v[1].x ^ ex) | (v[2].x ^ ex) | (v[3].x ^ ex)) & 0x40000000u);
        if (ok) n++;
        const bool ready = (ok || !have) && __all_sync(0xffffffffu, !((pr ^ tag_of(n)) & 0x40000000u));
        st_rlx_if(cred, n * 16, X_CR2 lane == 0 && ok);
        if (!ok && !ready && __all_sync(0xffffffffu, fin & FIN)) {
            const uint32_t left = __shfl_sync(0xffffffffu, (fin - n * 16) & 0xffffu, 0);
            if (left - 1u > 0x8000u) break;
            if (left < 16u) {
#pragma unroll
                for (int u = 0; u < 4; u++) {
                    v[u] = make_uint4(ex & 0x40000000u, 0, 0, 0);
                    ldq128_keep(v[u], ring_ptr(p, pq + off(n)) + u * 512, u * 4 + (lane >> 3) < left);
                }
                have = last = !__any_sync(0xffffffffu, ((v[0].x ^ ex) | (v[1].x ^ ex) | (v[2].x ^ ex) | (v[3].x ^ ex)) & 0x40000000u);
                pr = ~tag_of(n + have);
                if (++guard > GUARD) __trap();
                continue;
            }
        }
        uint32_t row[8], val[16];
#pragma unroll
        for (int u = 0; u < 4; u++) {
            const uint4 x = v[u];
            row[2 * u] = prmt(bitsel(x.x << 1, x.y >> 3, 0x7000f000u), 0, 0x4431);
            row[2 * u + 1] = prmt(bitsel(x.z << 1, x.w >> 3, 0x7000f000u), 0, 0x4431);
            val[4 * u] = p3_val(x.x); val[4 * u + 1] = p3_val(x.y);
            val[4 * u + 2] = p3_val(x.z); val[4 * u + 3] = p3_val(x.w);
        }
#pragma unroll
        for (int u = 0; u < 4; u++) ldq128_keep(v[u], ring_ptr(p, pq + off(n)) + u * 512, ready);
        pk = ready ? CFG_PK1 * 128 : ok ? CFG_PK2 * 128 : have ? 15 * 128 : max(pk, CFG_PK3 * 128u);
        pr = ld_rlx((const uint32_t*)ring_ptr(p, pp + off(n + ready) + pk));
        ACC(2, have && !ok)
        have = ready;
        if (!ok) {
            ACC(1, 1)
            fin = ld_rlx(finp);
            if (++guard > GUARD) __trap();
        } else {
#pragma unroll
            for (int u = 0; u < 4; u += 2) {
                uint32_t old[8], chk = 0;
#pragma unroll
                for (int j = 0; j < 4; j++) {
                    old[2 * j] = atoms_add(sb + C_S + row[2 * u + j] * 4, val[4 * u + 2 * j]);
                    old[2 * j + 1] = atoms_add(sb + C_S + ROWS3_MAX * 4 + row[2 * u + j] * 4, val[4 * u + 2 * j + 1]);
                }
#pragma unroll
                for (int j = 0; j < 8; j++) {
                    const uint32_t nw = old[j] + val[4 * u + j];
                    chk |= (old[j] ^ nw) & (val[4 * u + j] ^ nw);
                }
                if (chk & 0x80008000u) {
                    uint32_t tmp[20];
#pragma unroll
                    for (int j = 0; j < 8; j++) { tmp[j >> 1] = row[2 * u + (j >> 1)]; tmp[4 + j] = old[j]; tmp[12 + j] = val[4 * u + j]; }
                    p3_wrap(sb, id, tmp);
                }
            }
            __syncwarp();
            if (last) break;
        }
    }
    ACC_SAVE
}

__device__ __forceinline__ void row_gates(const float* sw, const uint32_t* c2, uint32_t dbits, float4& gs, float4& gr) {
    const uint32_t d2 = dbits * 0x10001u;
    gs = gr = make_float4(0.f, 0.f, 0.f, 0.f);
#pragma unroll
    for (int r2 = 0; r2 < 4; r2++) {
        uint32_t df = sub_bf2(d2, c2[r2]);
        uint32_t ar = mul_bf2(mul_bf2(df, df), 0xC120C120u);
        uint32_t rb = pack_bf2(__expf(bflo(ar)), __expf(bfhi(ar)));
        const float r0 = bflo(rb), r1 = bfhi(rb);
        const float4 s0 = *(const float4*)(sw + r2 * 8), s1 = *(const float4*)(sw + r2 * 8 + 4);
        const float4 q0 = *(const float4*)(sw + 32 + r2 * 8), q1 = *(const float4*)(sw + 32 + r2 * 8 + 4);
        gs.x += r0 * s0.x + r1 * s1.x; gs.y += r0 * s0.y + r1 * s1.y;
        gs.z += r0 * s0.z + r1 * s1.z; gs.w += r0 * s0.w + r1 * s1.w;
        gr.x += r0 * q0.x + r1 * q1.x; gr.y += r0 * q0.y + r1 * q1.y;
        gr.z += r0 * q0.z + r1 * q1.z; gr.w += r0 * q0.w + r1 * q1.w;
    }
}
__device__ __forceinline__ uint2 finish_row(const float* wu, const float4& gs, const float4& gr, const float S[4], uint2 mrow) {
    const float a[4] = {S[0] * gs.x, S[1] * gs.y, S[2] * gs.z, S[3] * gs.w};
    float u[4] = {0, 0, 0, 0};
#pragma unroll
    for (int k = 0; k < 4; k++) {
        u[0] += a[k] * wu[4 * k]; u[1] += a[k] * wu[4 * k + 1]; u[2] += a[k] * wu[4 * k + 2]; u[3] += a[k] * wu[4 * k + 3];
    }
    return make_uint2(pack_bf2(bflo(mrow.x) + u[0] * gr.x, bfhi(mrow.x) + u[1] * gr.y),
                      pack_bf2(bflo(mrow.y) + u[2] * gr.z, bfhi(mrow.y) + u[3] * gr.w));
}
__device__ __forceinline__ void load_tail_weights(const Params& p, float* sw, int tid) {
    if (tid < 32) sw[tid] = __bfloat162float(p.w_sbf[tid]);
    else if (tid < 64) sw[tid] = __bfloat162float(p.w_rbf[tid - 32]);
    else if (tid < 80) sw[tid] = __bfloat162float(p.w_up[tid - 64]);
    else if (tid < 96) sw[tid] = __bfloat162float(p.w_down[tid - 80]);
}
__device__ __forceinline__ float exp_ftz(float x) {
    float r;
    asm("ex2.approx.ftz.f32 %0, %1;" : "=f"(r) : "f"(x * 1.4426950408889634f));
    return r;
}
__device__ __forceinline__ void tail_rows(const Params& p, int tidx, int w, int lane) {
    constexpr uint32_t sb = SB;
    if (w == NW - 1 && lane < 2) {
        fence_gpu();
        red_rlx(rdy_of(p, sb, 320, lane), 1u);
    }
    if (w >= NPC * WPP) return;
    const int pc = w / WPP, r0 = pc * RPC + (tidx * WPP + w - pc * WPP) * 8, e0 = r0 * 32;
    const uint32_t G = sb + T_G + w * TWB, M = G + 4096, D = M + 2048;
    cp16z(D + lane * 16, p.dist + e0 + lane * 8, min(max(p.E - e0 - lane * 8, 0), 8) * 2);
#pragma unroll
    for (int k = 0; k < 4; k++) cp16(M + (k * 32 + lane) * 16, p.m + e0 + (k * 32 + lane) * 2, e0 + (k * 32 + lane) * 2 < p.E);
    cp_commit();
    const Scale sc = get_scale(sb);
    const float lsb[4] = {__uint_as_float((sc.eb[0] - 10) << 23), __uint_as_float((sc.eb[1] - 10) << 23),
                          __uint_as_float((sc.eb[2] - 10) << 23), __uint_as_float((sc.eb[3] - 10) << 23)};
    {
        const int g = lane >> 2, t = lane & 3;
        const uint32_t c2 = ((const uint32_t*)p.centers)[t];
        const unsigned short* wg = (const unsigned short*)(g < 4 ? p.w_sbf : p.w_rbf) + t * 8 + (g & 3);
        const uint32_t b = wg[0] | (uint32_t)wg[4] << 16;
        cp_wait<0>();
        __syncwarp();
        TR(19, w == 0 && lane == 0 && b + c2 != 0x12345);
#pragma unroll 2
        for (int k = 0; k < 16; k++) {
            const uint32_t dv = lds32(D + (k * 8 + g) * 4);
            uint32_t a[2];
#pragma unroll
            for (int h = 0; h < 2; h++) {
                const uint32_t df = sub_bf2(prmt(dv, 0, h ? 0x3232 : 0x1010), c2);
                const uint32_t ar = mul_bf2(mul_bf2(df, df), 0xC120C120u);
                a[h] = pack_bf2(exp_ftz(bflo(ar)), exp_ftz(bfhi(ar)));
            }
            float d[4];
            asm("mma.sync.aligned.m16n8k8.row.col.f32.bf16.bf16.f32 {%0,%1,%2,%3}, {%4,%5}, {%6}, {%7,%7,%7,%7};"
                : "=f"(d[0]), "=f"(d[1]), "=f"(d[2]), "=f"(d[3]) : "r"(a[0]), "r"(a[1]), "r"(b), "f"(0.f));
            const uint32_t at = G + (k * 16 + g * 2) * 16 + t * 4;
            sts32(at, pack_bf2(d[0], d[1]));
            sts32(at + 16, pack_bf2(d[2], d[3]));
        }
    }
    __syncwarp();
    TR(2, w == 0 && lane == 0);
    float wu[16];
#pragma unroll
    for (int k = 0; k < 4; k++) *(uint4*)(wu + 4 * k) = lds128(sb + SM_W + 256 + 16 * k);
    uint32_t dirty = 0;
#pragma unroll 1
    for (int pass = CFG_DRY ? 0 : 1; pass < 2; pass++) {
        if (pass) {
            if (w == pc * WPP && lane < 2) spin_ge(rdy_of(p, sb, lane ? 320 : 160 + 32 * pc, lds32(sb + SM_MISC + 20)), lane ? NTAIL : N3);
            __syncwarp();
            bar_sync(1 + pc, WPP * 32);
            TR(3, w == 0 && lane == 0);
            TR(10, w == NPC * WPP - 1 && lane == 0);
            if (r0 >= (int)p.rows3) return;
        }
        uint4 sv[4] = {};
#pragma unroll
        for (int u = 0; u < 4; u++) ldq128_keep(sv[u], &g_S[0][u * 16 + (lane >> 1)][r0 + (lane & 1) * 4], pass);
        if (pass && lane < 8 && (r0 + lane) * 32 < p.E && (dirty = ld_rlx(g_dirty + r0 + lane))) st_rlx(g_dirty + r0 + lane, 0u);
        dirty = __ballot_sync(0xffffffffu, dirty != 0);
        uint32_t xs[8] = {sv[0].x, sv[0].y, sv[0].z, sv[0].w, sv[1].x, sv[1].y, sv[1].z, sv[1].w};
        uint32_t ys[8] = {sv[2].x, sv[2].y, sv[2].z, sv[2].w, sv[3].x, sv[3].y, sv[3].z, sv[3].w};
        asm volatile("" : "+r"(lane));
        auto finish = [&](int k, uint32_t x, uint32_t y, bool extra) {
            const int i = (lane & 1) * 128 + (lane >> 1) + (k & 3) * 32 + (k >> 2) * 16, e = e0 + i;
            float S[4];
            const uint32_t tx = x + 0x80008000u, ty = y + 0x80008000u;
            S[0] = (__uint_as_float(prmt(tx, 0x4b000000u, 0x7610)) - 8421376.0f) * lsb[0];
            S[1] = (__uint_as_float(prmt(tx, 0x4b000000u, 0x7632)) - 8421376.0f) * lsb[1];
            S[2] = (__uint_as_float(prmt(ty, 0x4b000000u, 0x7610)) - 8421376.0f) * lsb[2];
            S[3] = (__uint_as_float(prmt(ty, 0x4b000000u, 0x7632)) - 8421376.0f) * lsb[3];
            if (extra && e < p.E) {
                const float4 g = __ldcg(g_Sg + e);
                S[0] += g.x; S[1] += g.y; S[2] += g.z; S[3] += g.w;
                __stcg(g_Sg + e, make_float4(0.f, 0.f, 0.f, 0.f));
            }
            const uint4 g = lds128(G + i * 16);
            const uint2 o = finish_row(wu, make_float4(bflo(g.x), bfhi(g.x), bflo(g.y), bfhi(g.y)), make_float4(bflo(g.z), bfhi(g.z), bflo(g.w), bfhi(g.w)), S,
                                       lds64v(M + i * 8));
            asm volatile("{.reg .pred q; setp.ne.u32 q, %3, 0; @q st.global.v2.u32 [%0], {%1,%2};}"
                         ::"l"(p.out + e), "r"(o.x), "r"(o.y), "r"((uint32_t)(pass && e < p.E)));
        };
        if (!dirty) {
#pragma unroll
            for (int k = 0; k < 8; k++) finish(k, xs[k], ys[k], false);
        } else {
#pragma unroll 1
            for (int k = 0; k < 8; k++) {
                finish(k, xs[0], ys[0], dirty >> ((lane & 1) * 4 + (k & 3)) & 1);
#pragma unroll
                for (int j = 0; j < 7; j++) { xs[j] = xs[j + 1]; ys[j] = ys[j + 1]; }
            }
        }
    }
    TR(9, w == 0 && lane == 0);
    TR(11, w == NPC * WPP - 1 && lane == 0);
}

#define CFG_MAP1 1
__global__ void __launch_bounds__(NT, 1) k_main(const __grid_constant__ Params p) {
    extern __shared__ __align__(1024) unsigned char smem[];
    constexpr uint32_t sb = SB;
    if ((uint32_t)__cvta_generic_to_shared(smem) != SB) __trap();
    const int tid = threadIdx.x, w = __shfl_sync(0xffffffffu, tid >> 5, 0), lane = tid & 31;
    if (w < NPROBE) probe(p, sb, w, lane);
    else {
        if (tid == NT - 1) sts32(sb + SM_MISC + 16, ld_rlx(&g_epoch) & 1);
        if (tid >= NT - 32 && lane < 12) sts32(sb + SM_FIN + lane * 4, 0u);
        if (CFG_ZE) {
        for (int i = SM_DATA / 16 + tid - NPROBE * 32; i < ZEND / 16; i += NT - NPROBE * 32) ((uint4*)smem)[i] = make_uint4(0, 0, 0, 0);
        if (tid - NPROBE * 32 < 256) ((uint4*)(smem + SM_ZERO))[tid - NPROBE * 32] = make_uint4(0, 0, 0, 0);
        }
        load_tail_weights(p, (float*)(smem + SM_W), tid - NPROBE * 32);
        const int k = blockIdx.x % (NCTA / 2) * 14 + lane;
        if (w == NW - 2 && lane < 14 && k < NT - 32) asm volatile("prefetch.global.L2 [%0];" ::"l"((const uint4*)p.m + k * (p.E / 2 / (NT - 32))));
    }
    cta_sync();
    if (w) {
        const uint4 in = __ldg((const uint4*)p.m + (tid - 32) * (p.E / 2 / (NT - 32)));
        const Mat4 wd = load_mat4(p.w_down, lane);
        if (!CFG_ZE) {
        for (int i = SM_DATA / 16 + tid - 32; i < ZEND / 16; i += NT - 32) ((uint4*)smem)[i] = make_uint4(0, 0, 0, 0);
        if (tid - 32 < 256) ((uint4*)(smem + SM_ZERO))[tid - 32] = make_uint4(0, 0, 0, 0);
        }
        if (tid < 48) sts32(sb + SM_CNT2 + (tid - 32) * 4, NQ2 << 16);
        __syncwarp();
        if (CFG_PFD && tid == NT - 1) {
            __nanosleep(CFG_PFD);
            const uint32_t n = (p.E / 2 + NCTA - 1) / NCTA, o = blockIdx.x * n;
            if (o < (uint32_t)p.E / 2) asm volatile("cp.async.bulk.prefetch.L2.global [%0], %1;" ::"l"((const uint4*)p.m + o), "r"(min(n, p.E / 2 - o) * 16) : "memory");
        }
        __syncwarp();
        md_stats(in, wd, lane);
    } else assign_role(p, sb, lane);
    if (tid == 0) {
        mbar_init(sb + SM_DONE, lds32(sb + SM_MISC) >> 8 ? P2W : P1W);
        mbar_init(sb + SM_DONE2, NF);
    }
    cta_sync();
    const uint32_t rid = __shfl_sync(0xffffffffu, lds32(sb + SM_MISC), 0);
    const int role = rid >> 8, id = rid & 255;
    TR(5, tid == 0);
    if (role == 0) {
        const int ww = CFG_MAP1 == 0 ? ((w & 3) == 3 ? NW : (w >> 2) * 3 + (w & 3)) : CFG_MAP1 == 1 ? (w & 2 ? NW : (w >> 2) * 2 + (w & 1)) : w;
        const int sw = CFG_MAP1 == 0 ? ((w & 3) == 3 ? w >> 2 : NW) : CFG_MAP1 == 1 ? (w & 2 ? (w >> 2) * 2 + (w & 1) : NW) : w - P1W;
        static_assert(CFG_MAP1 == 0 ? (P1W <= NW / 4 * 3 && NF + 2 <= NW / 4) : CFG_MAP1 == 1 ? (P1W <= NW / 2 && NF + 2 <= NW / 2) : true, "warp map");
        for (int i = tid; i < NF * GPW * 32; i += NT) sts32(sb + A_CNT + i * 4, 1u << 24);
        if (tid < 64) sts32(sb + SM_CRED + tid * 4, 0u);
        cta_sync();
        TR(1, tid == 0);
        if (ww < P1W) role_p1(p, sb, id, ww, lane);
        else if (sw < NF) role_flush(p, sb, id, sw, lane);
        else if (sw == NF) role_credit1(p, sb, id, lane);
        else if (w == NW - 1) {
            uint4* owin = (uint4*)(p.ring + (CWIN + (lds32(sb + SM_MISC + 16) ^ 1)) * WIN);
            for (int i = id * 32 + lane; i < CPAIRS * 512; i += N1 * 32) __stcg(owin + i, make_uint4(0, 0, 0, 0));
            __syncwarp();
        }
    } else if (role == 1) {
        const int row0 = id % H2 * p.rows2;
        const int nrows = min((int)p.rows2, p.E - row0);
        constexpr int NTB = NT - 32, TBD = CFG_TBD;
        bool flagged = false;
        if (w < NW - 1) {
            const uint4* const src = (const uint4*)(p.m + row0);
            uint4 r2[TBD], nx[TBD];
            auto fetch = [&](int i) {
#pragma unroll
                for (int k = 0; k < TBD; k++)
                    asm volatile("ld.global.nc.v4.u32 {%0,%1,%2,%3}, [%4];" : "=r"(nx[k].x), "=r"(nx[k].y), "=r"(nx[k].z), "=r"(nx[k].w) : "l"(src + min(i + k * NTB, nrows / 2 - 1)));
            };
            fetch(tid);
            const Scale sc = get_scale(sb);
            const Mat4 wd = load_mat4(p.w_down, lane);
            Mat4 ws;
#pragma unroll
            for (int k = 0; k < 4; k++) ws.b[k] = mul_bf2(wd.b[k], ((246u - (lane & 4 ? sc.eb[(k & 2) + 1] : sc.eb[k & 2])) << 7) * 0x10001u);
#pragma unroll 1
            for (int i0 = tid; 2 * (i0 - lane) < nrows; i0 += TBD * NTB) {
#pragma unroll
                for (int k = 0; k < TBD; k++) r2[k] = make_uint4(nx[k].x, nx[k].z, nx[k].y, nx[k].w);
                fetch(i0 + TBD * NTB);
#pragma unroll
                for (int k = 0; k < TBD; k++) {
                    const int i = i0 + k * NTB;
                    float y[8];
                    mul4(make_uint4(r2[k].x, r2[k].z, r2[k].y, r2[k].w), ws, y);
                    uint32_t a[4], h[4], ta[2];
#pragma unroll
                    for (int j = 0; j < 4; j++) { a[j] = pack_h2(y[2 * j], y[2 * j + 1]); h[j] = a[j] + 0x00040004u; }
#pragma unroll
                    for (int j = 0; j < 2; j++) ta[j] = bitsel(h[2 * j], bitsel(h[2 * j + 1] >> 3, h[2 * j + 1] << 7, 0x00070007u), 0x9ff89ff8u);
                    uint32_t tb = prmt(h[1], h[3], 0x7531);
                    const uint32_t b0 = a[0] | a[1] | h[0] | h[1], b1 = a[2] | a[3] | h[2] | h[3];
                    if (__any_sync(0xffffffffu, ((b0 | b1) & 0x60006000u) || sc.allslow)) {
                        if ((b0 & 0x60006000u) || sc.allslow) { ta[0] = 0; tb = (tb & 0xffff0000u) | 0x40u; }
                        if ((b1 & 0x60006000u) || sc.allslow) { ta[1] = 0; tb = (tb & 0xffffu) | 0x400000u; }
                        flagged = true;
                    }
                    sts64_if(sb + B_TA + i * 8, ta[0], ta[1], 2 * i < nrows);
                    sts32_if(sb + B_TB + i * 4, tb, 2 * i < nrows);
                }
            }
            if (tid == 0) {
                sts32(sb + B_TA + p.rows2 * 4, 0u);
                sts16(sb + B_TB + p.rows2 * 2, 0u);
            }
            TR(8, tid == 0);
        } else if (lane == 0) spin_ge(rdy_of(p, sb, id, id / H2), H3);
        __syncwarp();
        flagged = __any_sync(0xffffffffu, __syncthreads_or(flagged));
        TR(1, tid == 0);
        if (w < P2W) {
            if (flagged) role_p2<true>(p, sb, id, w, lane);
            else role_p2<false>(p, sb, id, w, lane);
        } else if (w == P2W) role_credit(p, sb, id, lane);
    } else {
        if (w == 0) clear_queues<false>(p, sb, id, lane);
        if (tid >= 32 && tid < 33 + NPC) mbar_init(sb + SM_CNT2 + (tid - 32) * 8, 1);
        cta_sync();
        TR(1, tid == 0);
        if (w < P3W) role_p3(p, sb, id, w, lane);
        cta_sync();
        TR(2, tid == 0);
        if (w < NPC && lane == 0) {
            fence_async_smem();
            const int n = min(((int)p.rows3 + 7) / 8 * 8 - w * RPC, RPC);
            if (w >= CFG_DOUT) mbar_wait(sb + SM_CNT2 + (w + 1 - CFG_DOUT) * 8, 0);
            if (n > 0) {
                bulk_store(g_S[0][id] + w * RPC, sb + C_S + w * RPC * 4, n * 4);
                bulk_store(g_S[1][id] + w * RPC, sb + C_S + (ROWS3_MAX + w * RPC) * 4, n * 4);
            }
            asm volatile("cp.async.bulk.commit_group;" ::: "memory");
            asm volatile("cp.async.bulk.wait_group.read 0;" ::: "memory");
            mbar_arrive(sb + SM_CNT2 + w * 8 + 8);
            asm volatile("cp.async.bulk.wait_group 0;" ::: "memory");
            fence_gpu();
            red_rlx(rdy_of(p, sb, 160 + 32 * w, 0), 1u);
            red_rlx(rdy_of(p, sb, 160 + 32 * w, 1), 1u);
            if (id == 0 && w == 0) red_rlx(&g_epoch, 1u);
            TR(12 + w, true);
        }
        return;
    }
    cta_sync();
    TR(18, tid == 0 && role == 1);
    if (role == 0 && w == NW - 2) clear_queues<true>(p, sb, id, lane);
    tail_rows(p, role * N1 + id, w, lane);
}

__global__ void k_direct(const Params p, long long T) {
    float wd[16];
#pragma unroll
    for (int i = 0; i < 16; i++) wd[i] = __bfloat162float(p.w_down[i]);
    const float f = __bfloat162float(p.freq[0]);
    for (long long t = blockIdx.x * (long long)blockDim.x + threadIdx.x; t < T; t += (long long)gridDim.x * blockDim.x) {
        float x = __bfloat162float(__float2bfloat16(f * __bfloat162float(p.angle[t])));
        float c = __bfloat162float(__float2bfloat16(cosf(x)));
        uint2 md = down_row(__ldg(p.m + p.idx_in[t]), wd);
        red_v4(g_Sg + p.idx_out[t], c * bflo(md.x), c * bfhi(md.x), c * bflo(md.y), c * bfhi(md.y));
    }
}
__global__ void k_direct_tail(const Params p) {
    __shared__ __align__(16) float sw[96];
    load_tail_weights(p, sw, threadIdx.x);
    __syncthreads();
    uint32_t c2[4];
#pragma unroll
    for (int i = 0; i < 4; i++) c2[i] = ((const uint32_t*)p.centers)[i];
    for (int e = blockIdx.x * blockDim.x + threadIdx.x; e < p.E; e += gridDim.x * blockDim.x) {
        float4 g = __ldcg(g_Sg + e);
        __stcg(g_Sg + e, make_float4(0.f, 0.f, 0.f, 0.f));
        const float Sv[4] = {g.x, g.y, g.z, g.w};
        float4 gs, gr;
        row_gates(sw, c2, __bfloat16_as_ushort(p.dist[e]), gs, gr);
        p.out[e] = finish_row(sw + 64, gs, gr, Sv, __ldg(p.m + e));
    }
}

static bool pick_rows(int E, int n, int rows_max, int mult, uint32_t* rows, uint32_t* magic) {
    for (uint32_t r = (E + n - 1) / n; r <= (uint32_t)rows_max; r++) {
        if (r < 2 || r % mult) continue;
        uint64_t mg = ((1ull << 32) + r - 1) / r;
        uint64_t err = mg * r - (1ull << 32);
        if (err * (uint64_t)n < mg) { *rows = r; *magic = (uint32_t)mg; return true; }
    }
    return false;
}

}

extern "C" void kernel_launch(void* const* d_in, const int* in_sizes, int n_in, void* d_out, int out_size) {
    using namespace gs;
    (void)n_in; (void)out_size;
    Params p;
    p.m = (const uint2*)d_in[0];
    p.idx_in = (const int*)d_in[1];
    p.idx_out = (const int*)d_in[2];
    p.dist = (const __nv_bfloat16*)d_in[3];
    p.angle = (const __nv_bfloat16*)d_in[4];
    p.centers = (const __nv_bfloat16*)d_in[5];
    p.freq = (const __nv_bfloat16*)d_in[6];
    p.w_rbf = (const __nv_bfloat16*)d_in[7];
    p.w_sbf = (const __nv_bfloat16*)d_in[8];
    p.w_down = (const __nv_bfloat16*)d_in[9];
    p.w_up = (const __nv_bfloat16*)d_in[10];
    p.out = (uint2*)d_out;
    p.E = in_sizes[3];
    const long long T = in_sizes[1];
    p.n4 = (int)(T / 4);
    p.rows2 = p.magic2 = 0;
    p.ring = nullptr;

    static int sms = 0, rsv = 0;
    if (!sms) {
        int dev = 0;
        cudaGetDevice(&dev);
        cudaDeviceGetAttribute(&rsv, cudaDevAttrReservedSharedMemoryPerBlock, dev);
        cudaDeviceGetAttribute(&sms, cudaDevAttrMultiProcessorCount, dev);
        cudaFuncSetAttribute(k_main, cudaFuncAttributeMaxDynamicSharedMemorySize, SMEM_BYTES);
    }
    cudaStream_t st = cudaStreamPerThread;
    bool fast = (T % 4 == 0) && T > 0 && sms >= NCTA && rsv == (int)SB && p.E >= 65536 && p.E <= E_MAX &&
                p.E % 4 == 0 && (((uintptr_t)p.m | (uintptr_t)p.idx_in | (uintptr_t)p.idx_out | (uintptr_t)p.angle) & 15) == 0 &&
                pick_rows(p.E, NI, ROWS2_MAX, 2, &p.rows2, &p.magic2);
    p.c1 = 1;
    p.nrows2 = 0u - p.rows2;
    p.rows3 = (p.E + 31) / 32;
    fast = fast && (p.rows2 * (NI - 1) + 2 <= (uint32_t)p.E);
    static const void* tkey[3] = {nullptr, nullptr, nullptr};
    static cudaTextureObject_t tex[3] = {0, 0, 0};
    static long long tlen = -1;
    const void* tptr[3] = {p.idx_in, p.idx_out, p.angle};
    for (int k = 0; fast && k < 3; k++) {
        if (tkey[k] == tptr[k] && tlen == T) continue;
        if (tkey[k]) cudaDestroyTextureObject(tex[k]);
        tkey[k] = nullptr;
        cudaResourceDesc rd = {};
        rd.resType = cudaResourceTypeLinear;
        rd.res.linear.devPtr = (void*)tptr[k];
        rd.res.linear.desc = cudaCreateChannelDesc(32, 32, k < 2 ? 32 : 0, k < 2 ? 32 : 0, cudaChannelFormatKindUnsigned);
        rd.res.linear.sizeInBytes = (size_t)T * (k < 2 ? 4 : 2);
        cudaTextureDesc td = {};
        td.readMode = cudaReadModeElementType;
        if (cudaCreateTextureObject(&tex[k], &rd, &td, nullptr) == cudaSuccess) tkey[k] = tptr[k];
        else { (void)cudaGetLastError(); fast = false; }
    }
    if (fast) tlen = T;
    p.t_in = tex[0]; p.t_out = tex[1]; p.t_ang = tex[2];
    if (fast) {
        void* ring = nullptr;
        cudaGetSymbolAddress(&ring, g_ring);
        uintptr_t a = ((uintptr_t)ring + WIN - 1) & ~(uintptr_t)(WIN - 1);
        if (a >> 32 != (a + RING_BYTES - 1) >> 32) a += RING_BYTES;
        p.ring = (unsigned char*)a;
        p.ring_lo = (uint32_t)a;
        p.ring_hi = (uint32_t)(a >> 32);
        k_main<<<NCTA, NT, SMEM_BYTES, st>>>(p);
    } else {
        k_direct<<<sms * 8, 256, 0, st>>>(p, T);
        k_direct_tail<<<sms * 4, 256, 0, st>>>(p);
    }
}
```

```cpp
#include <cuda_runtime.h>
#include <cuda_bf16.h>
#include <stdint.h>

#define CFG_N1 56
#define CFG_NI 22
#define CFG_NW 28
#define CFG_P1W 14
#define CFG_GPW 2
#define CFG_KR 1
#define CFG_QPW 3
#define CFG_TG 2
#define CFG_PMASK 8
#define CFG_PSTREAK 1
#define CFG_NBT 1
#define CFG_KM 5
#define CFG_KN 9
#define CFG_TBD 4
#define CFG_P0 500
#define CFG_PFD 200
#define CFG_C1SLEEP 200
#define CFG_PK1 6
#define CFG_PK2 8
#define CFG_PK3 11
#define CFG_CLN 2
#define CFG_CLS 300
#define CFG_DOUT 2
#define CFG_TH 14
#define CFG_TS 200
#define CFG_POLL 64
#define CFG_HINT 20000
#define CFG_BSLEEP 100
#define CFG_CSLEEP 200
#define CFG_FSLEEP 100
#define CFG_PSLEEP 100
#define CFG_DRY 1
#define CFG_PROBES 4

namespace gs {

constexpr int E_MAX = 640000;
constexpr int N1 = CFG_N1, NI = CFG_NI, N2 = 2 * NI, N3 = 32, NCTA = N1 + N2 + N3;
constexpr int H2 = NI, H3 = N3 / 2;
constexpr int NB = NI * N3;
constexpr int NW = CFG_NW, NT = NW * 32;
constexpr int GPW = CFG_GPW, NF = (NI + GPW - 1) / GPW;
constexpr int QPW = CFG_QPW, NBT = CFG_NBT;
constexpr int P1W = CFG_P1W, P2W = (N1 + QPW - 1) / QPW, P3W = NI;
constexpr int NQ2 = 64;
constexpr int ROWS2_MAX = ((E_MAX + NI - 1) / NI + 31) / 8 * 8;
constexpr int ROWS3_MAX = (E_MAX / 32 + 31) / 32 * 32;
constexpr int NTAIL = N1 + N2;
constexpr int NPC = 5, WPP = 5, RPC = NTAIL * WPP * 8;
constexpr int GUARD = 1 << 26;
static_assert(NCTA % 4 == 0 && NCTA <= 192, "roles come in CTA pairs, per partition");
static_assert((GPW == 2 || GPW == 4) && QPW >= NBT && QPW <= 4 && NI <= 32 && N1 <= 62, "queue ownership");
static_assert(P1W + NF + 2 <= NW && P2W + 2 <= NW && P3W + 1 <= NW && P1W * 256 + 64 < 8192, "warp roles");
static_assert(ROWS2_MAX + 8 <= 32768 && ROWS3_MAX <= 32768, "index bits");

constexpr uint32_t SB = 1024;
constexpr int SM_DONE = 0, SM_DONE2 = 8;
constexpr int SM_MISC = 16;
constexpr int SM_FIN = 48;
constexpr int SM_STAT = 64;
constexpr int SM_CNT2 = 128;
constexpr int SM_W = 256;
constexpr int SM_PUB = SM_W + 384;
constexpr int SM_PROBE = SM_PUB + 768;
constexpr int SM_CRED = 1792;
constexpr int SM_DATA = 2048;
constexpr int cmax(int a, int b) { return a > b ? a : b; }
constexpr int A_CNT = SM_DATA;
constexpr int KR = CFG_KR, LISTB = (GPW * 32 + 8 * KR) * 4;
constexpr int A_LIST = A_CNT + NF * GPW * 128;
constexpr int A_ST = (A_LIST + NF * LISTB + 127) / 128 * 128;
constexpr int A_END = A_ST + NB * 256;
constexpr int B_TB = SM_DATA;
constexpr int B_TA = SM_DATA + (ROWS2_MAX + 8) * 2;
constexpr int B_END = SM_DATA + (ROWS2_MAX + 8) * 6;
constexpr int C_S = SM_DATA;
constexpr int C_END = C_S + ROWS3_MAX * 8;
constexpr int T_G = SM_DATA, TWB = 4096 + 2048 + 512, T_END = T_G + NPC * WPP * TWB;
constexpr int ZEND = cmax(A_END, C_END);
constexpr int SM_ZERO = (cmax(C_END, T_END) + 127) / 128 * 128;
constexpr int SMEM_BYTES = cmax(cmax(A_END, B_END), SM_ZERO + 4096);
static_assert(SMEM_BYTES <= 232448 && SM_PROBE + 128 <= SM_CRED, "shared memory");
static_assert(NPC * RPC >= ROWS3_MAX && NPC * WPP + 2 <= NW, "tail");

constexpr uint32_t FIN = 0x80000000u;

constexpr uint32_t WIN = 524288;
constexpr int CWIN = N2 + N3, NWIN = CWIN + 2, CPAIRS = 31;
constexpr uint32_t PROBE_OFF = (uint32_t)NWIN * WIN;
constexpr int NPROBE = 16;
static_assert(NWIN <= NCTA && NPROBE <= NW, "windows");
constexpr size_t RING_BYTES = (size_t)PROBE_OFF + WIN;
__device__ __align__(128) unsigned char g_ring[2 * RING_BYTES + WIN];
__device__ __align__(128) uint32_t g_S[2][32][ROWS3_MAX];
__device__ __align__(128) float4 g_Sg[E_MAX];
__device__ uint32_t g_dirty[E_MAX / 32];
__device__ uint32_t g_epoch;

#define TR(ev, on)
#define ACC_DECL
#define ACC(i, n)
#define ACC_SAVE

struct Params {
    const uint2* m;
    const int* idx_in;
    const int* idx_out;
    const __nv_bfloat16* dist;
    const __nv_bfloat16* angle;
    const __nv_bfloat16* centers;
    const __nv_bfloat16* freq;
    const __nv_bfloat16* w_rbf;
    const __nv_bfloat16* w_sbf;
    const __nv_bfloat16* w_down;
    const __nv_bfloat16* w_up;
    uint2* out;
    unsigned char* ring;
    cudaTextureObject_t t_in, t_out, t_ang;
    int E, n4;
    uint32_t rows2, nrows2, magic2, rows3;
    uint32_t ring_lo, ring_hi;
};

__device__ __forceinline__ float bflo(uint32_t w) { return __uint_as_float(w << 16); }
__device__ __forceinline__ float bfhi(uint32_t w) { return __uint_as_float(w & 0xffff0000u); }
__device__ __forceinline__ uint32_t pack_bf2(float lo, float hi) {
    uint32_t r;
    asm("cvt.rn.bf16x2.f32 %0, %1, %2;" : "=r"(r) : "f"(hi), "f"(lo));
    return r;
}
__device__ __forceinline__ uint32_t mul_bf2(uint32_t a, uint32_t b) {
    uint32_t r;
    asm("mul.rn.bf16x2 %0, %1, %2;" : "=r"(r) : "r"(a), "r"(b));
    return r;
}
__device__ __forceinline__ uint32_t sub_bf2(uint32_t a, uint32_t b) {
    uint32_t r;
    asm("sub.rn.bf16x2 %0, %1, %2;" : "=r"(r) : "r"(a), "r"(b));
    return r;
}
__device__ __forceinline__ uint32_t maxabs_bf2(uint32_t a, uint32_t b) {
    uint32_t r;
    asm("max.NaN.xorsign.abs.bf16x2 %0, %1, %2;" : "=r"(r) : "r"(a), "r"(b));
    return r;
}
__device__ __forceinline__ void mbar_init(uint32_t a, uint32_t n) {
    asm volatile("mbarrier.init.shared::cta.b64 [%0], %1;" ::"r"(a), "r"(n) : "memory");
}
__device__ __forceinline__ void mbar_arrive(uint32_t a) {
    asm volatile("mbarrier.arrive.shared::cta.b64 _, [%0];" ::"r"(a) : "memory");
}
__device__ __forceinline__ void mbar_arrive_if(uint32_t a, bool on) {
    asm volatile("{.reg .pred q; setp.ne.u32 q, %1, 0; @q mbarrier.arrive.shared::cta.b64 _, [%0];}" ::"r"(a), "r"((uint32_t)on) : "memory");
}
__device__ __forceinline__ void mbar_wait(uint32_t a, uint32_t parity) {
    uint32_t ok;
    int guard = 0;
    do {
        asm volatile("{.reg .pred p; mbarrier.try_wait.parity.shared::cta.b64 p, [%1], %2, %3; selp.u32 %0, 1, 0, p;}"
                     : "=r"(ok) : "r"(a), "r"(parity), "r"(CFG_HINT) : "memory");
        if (!ok) {
            if (++guard > GUARD) __trap();
        }
    } while (!ok);
}
__device__ __forceinline__ void cta_sync() { __syncwarp(); __syncthreads(); }
__device__ __forceinline__ void bar_sync(int id, int n) { asm volatile("bar.sync %0, %1;" ::"r"(id), "r"(n) : "memory"); }
__device__ __forceinline__ bool mbar_test(uint32_t a, uint32_t parity) {
    uint32_t ok;
    asm volatile("{.reg .pred p; mbarrier.test_wait.parity.shared::cta.b64 p, [%1], %2; selp.u32 %0, 1, 0, p;}"
                 : "=r"(ok) : "r"(a), "r"(parity) : "memory");
    return ok;
}
__device__ __forceinline__ uint32_t ld_acq(const uint32_t* p) {
    uint32_t v;
    asm volatile("ld.acquire.gpu.global.u32 %0, [%1];" : "=r"(v) : "l"(p) : "memory");
    return v;
}
__device__ __forceinline__ uint32_t ld_rlx(const uint32_t* p) {
    uint32_t v;
    asm volatile("ld.relaxed.gpu.global.u32 %0, [%1];" : "=r"(v) : "l"(p) : "memory");
    return v;
}
__device__ __forceinline__ void st_rlx(uint32_t* p, uint32_t v) {
    asm volatile("st.relaxed.gpu.global.u32 [%0], %1;" ::"l"(p), "r"(v) : "memory");
}
__device__ __forceinline__ void red_rlx(uint32_t* p, uint32_t v) {
    asm volatile("red.relaxed.gpu.global.add.u32 [%0], %1;" ::"l"(p), "r"(v) : "memory");
}
__device__ __forceinline__ uint32_t spin_ge(const uint32_t* p, uint32_t target) {
    int guard = 0;
    while (ld_rlx(p) < target) {
        __nanosleep(CFG_POLL);
        if (++guard > GUARD) __trap();
    }
    return ld_acq(p);
}
__device__ __forceinline__ void fence_gpu() { asm volatile("fence.acq_rel.gpu;" ::: "memory"); }
__device__ __forceinline__ void fence_async_smem() { asm volatile("fence.proxy.async.shared::cta;" ::: "memory"); }
__device__ __forceinline__ void fence_async_all() { asm volatile("fence.proxy.async;" ::: "memory"); }
__device__ __forceinline__ void bulk_store(void* g, uint32_t s, uint32_t bytes) {
    asm volatile("cp.async.bulk.global.shared::cta.bulk_group [%0], [%1], %2;" ::"l"(g), "r"(s), "r"(bytes) : "memory");
}
__device__ __forceinline__ void cp16(uint32_t s, const void* g, bool on) {
    asm volatile("{.reg .pred q; setp.ne.u32 q, %2, 0; @q cp.async.cg.shared.global [%0], [%1], 16;}" ::"r"(s), "l"(g), "r"((uint32_t)on) : "memory");
}
__device__ __forceinline__ void cp16z(uint32_t s, const void* g, int bytes) {
    asm volatile("cp.async.cg.shared.global [%0], [%1], 16, %2;" ::"r"(s), "l"(g), "r"(bytes) : "memory");
}
__device__ __forceinline__ void cp_commit() { asm volatile("cp.async.commit_group;" ::: "memory"); }
template <int N> __device__ __forceinline__ void cp_wait() { asm volatile("cp.async.wait_group %0;" ::"n"(N) : "memory"); }
__device__ __forceinline__ uint32_t atoms_add(uint32_t a, uint32_t v) {
    uint32_t o;
    asm volatile("atom.shared.add.u32 %0, [%1], %2;" : "=r"(o) : "r"(a), "r"(v) : "memory");
    return o;
}
__device__ __forceinline__ void sts32(uint32_t a, uint32_t v) { asm volatile("st.shared.u32 [%0], %1;" ::"r"(a), "r"(v) : "memory"); }
__device__ __forceinline__ void sts16(uint32_t a, uint32_t v) { asm volatile("st.shared.u16 [%0], %1;" ::"r"(a), "h"((uint16_t)v) : "memory"); }
__device__ __forceinline__ void sts64(uint32_t a, uint32_t x, uint32_t y) { asm volatile("st.shared.v2.u32 [%0], {%1,%2};" ::"r"(a), "r"(x), "r"(y) : "memory"); }
__device__ __forceinline__ uint32_t lds32(uint32_t a) {
    uint32_t v;
    asm volatile("ld.shared.u32 %0, [%1];" : "=r"(v) : "r"(a) : "memory");
    return v;
}
__device__ __forceinline__ uint2 lds64v(uint32_t a) {
    uint2 v;
    asm volatile("ld.volatile.shared.v2.u32 {%0,%1}, [%2];" : "=r"(v.x), "=r"(v.y) : "r"(a) : "memory");
    return v;
}
__device__ __forceinline__ uint32_t lds32v(uint32_t a) {
    uint32_t v;
    asm volatile("ld.volatile.shared.u32 %0, [%1];" : "=r"(v) : "r"(a) : "memory");
    return v;
}
__device__ __forceinline__ uint4 lds128(uint32_t a) {
    uint4 v;
    asm volatile("ld.shared.v4.u32 {%0,%1,%2,%3}, [%4];" : "=r"(v.x), "=r"(v.y), "=r"(v.z), "=r"(v.w) : "r"(a) : "memory");
    return v;
}
__device__ __forceinline__ void sts128(uint32_t a, uint4 v) {
    asm volatile("st.shared.v4.u32 [%0], {%1,%2,%3,%4};" ::"r"(a), "r"(v.x), "r"(v.y), "r"(v.z), "r"(v.w) : "memory");
}
#define LD_Q "ld.relaxed.gpu.global"
__device__ __forceinline__ uint4 ldg_q128(const void* p) {
    uint4 v;
    asm volatile(LD_Q ".v4.u32 {%0,%1,%2,%3}, [%4];"
                 : "=r"(v.x), "=r"(v.y), "=r"(v.z), "=r"(v.w) : "l"(p) : "memory");
    return v;
}
__device__ __forceinline__ uint2 ldg_q64(const void* p) {
    uint2 v;
    asm volatile(LD_Q ".v2.u32 {%0,%1}, [%2];" : "=r"(v.x), "=r"(v.y) : "l"(p) : "memory");
    return v;
}
__device__ __forceinline__ void red_v4(float4* p, float a, float b, float c, float d) {
    asm volatile("red.global.add.v4.f32 [%0], {%1,%2,%3,%4};" ::"l"(p), "f"(a), "f"(b), "f"(c), "f"(d) : "memory");
}
__device__ __forceinline__ uint2 down_row(uint2 r, const float* wd) {
    float x0 = bflo(r.x), x1 = bfhi(r.x), x2 = bflo(r.y), x3 = bfhi(r.y);
    float y[4];
#pragma unroll
    for (int j = 0; j < 4; j++) y[j] = x0 * wd[j] + x1 * wd[4 + j] + x2 * wd[8 + j] + x3 * wd[12 + j];
    return make_uint2(pack_bf2(y[0], y[1]), pack_bf2(y[2], y[3]));
}
__device__ __forceinline__ uint32_t prmt(uint32_t a, uint32_t b, uint32_t s) {
    uint32_t r;
    asm("prmt.b32 %0, %1, %2, %3;" : "=r"(r) : "r"(a), "r"(b), "r"(s));
    return r;
}
__device__ __forceinline__ uint32_t bitsel(uint32_t a, uint32_t b, uint32_t m) {
    uint32_t r;
    asm("lop3.b32 %0, %1, %2, %3, 0xE4;" : "=r"(r) : "r"(a), "r"(b), "r"(m));
    return r;
}
__device__ __forceinline__ uint32_t pack_h2(float lo, float hi) {
    uint32_t r;
    asm("cvt.rn.f16x2.f32 %0, %1, %2;" : "=r"(r) : "f"(hi), "f"(lo));
    return r;
}
__device__ __forceinline__ uint32_t mul_h2(uint32_t a, uint32_t b) {
    uint32_t r;
    asm("mul.rn.f16x2 %0, %1, %2;" : "=r"(r) : "r"(a), "r"(b));
    return r;
}
__device__ __forceinline__ uint32_t lds32nv(uint32_t a) {
    uint32_t v;
    asm volatile("ld.shared.u32 %0, [%1];" : "=r"(v) : "r"(a));
    return v;
}
__device__ __forceinline__ uint32_t lds16nv(uint32_t a) {
    uint32_t v;
    asm volatile("ld.shared.u16 %0, [%1];" : "=r"(v) : "r"(a));
    return v;
}
#define ST_Q "st.relaxed.gpu.global"
__device__ __forceinline__ void stg_q128(void* p, uint32_t a, uint32_t b, uint32_t c, uint32_t d, bool on) {
    asm volatile("{.reg .pred q; setp.ne.u32 q, %5, 0; @q " ST_Q ".v4.u32 [%0], {%1,%2,%3,%4};}"
                 ::"l"(p), "r"(a), "r"(b), "r"(c), "r"(d), "r"((uint32_t)on) : "memory");
}
__device__ __forceinline__ void stg_q64(void* p, uint32_t a, uint32_t b, bool on) {
    asm volatile("{.reg .pred q; setp.ne.u32 q, %3, 0; @q " ST_Q ".v2.u32 [%0], {%1,%2};}"
                 ::"l"(p), "r"(a), "r"(b), "r"((uint32_t)on) : "memory");
}
__device__ __forceinline__ void st_rlx_if(uint32_t* p, uint32_t v, bool on) {
    asm volatile("{.reg .pred q; setp.ne.u32 q, %2, 0; @q st.relaxed.gpu.global.u32 [%0], %1;}" ::"l"(p), "r"(v), "r"((uint32_t)on) : "memory");
}
__device__ __forceinline__ void ldq128_keep(uint4& v, const void* p, bool on) {
    asm volatile("{.reg .pred q; setp.ne.u32 q, %5, 0; @q ld.relaxed.gpu.global.v4.u32 {%0,%1,%2,%3}, [%4];}"
                 : "+r"(v.x), "+r"(v.y), "+r"(v.z), "+r"(v.w) : "l"(p), "r"((uint32_t)on) : "memory");
}
__device__ __forceinline__ void atoms_add_keep(uint32_t& o, uint32_t a, uint32_t v, bool on) {
    asm volatile("{.reg .pred q; setp.ne.u32 q, %3, 0; @q atom.shared.add.u32 %0, [%1], %2;}" : "+r"(o) : "r"(a), "r"(v), "r"((uint32_t)on) : "memory");
}
__device__ __forceinline__ void reds_add(uint32_t a, uint32_t v) { asm volatile("red.shared.add.u32 [%0], %1;" ::"r"(a), "r"(v) : "memory"); }
__device__ __forceinline__ void sts32_if(uint32_t a, uint32_t v, bool on) {
    asm volatile("{.reg .pred q; setp.ne.u32 q, %2, 0; @q st.shared.u32 [%0], %1;}" ::"r"(a), "r"(v), "r"((uint32_t)on) : "memory");
}
__device__ __forceinline__ void sts64_if(uint32_t a, uint32_t x, uint32_t y, bool on) {
    asm volatile("{.reg .pred q; setp.ne.u32 q, %3, 0; @q st.shared.v2.u32 [%0], {%1,%2};}" ::"r"(a), "r"(x), "r"(y), "r"((uint32_t)on) : "memory");
}
__device__ __forceinline__ void lds128_keep(uint4& v, uint32_t a, bool on) {
    asm volatile("{.reg .pred q; setp.ne.u32 q, %5, 0; @q ld.volatile.shared.v4.u32 {%0,%1,%2,%3}, [%4];}"
                 : "+r"(v.x), "+r"(v.y), "+r"(v.z), "+r"(v.w) : "r"(a), "r"((uint32_t)on) : "memory");
}
__device__ __forceinline__ void or3_if(uint32_t& x, uint32_t a, uint32_t b, bool on) {
    asm("{.reg .pred q; setp.ne.u32 q, %3, 0; @q lop3.b32 %0, %0, %1, %2, 0xfe;}" : "+r"(x) : "r"(a), "r"(b), "r"((uint32_t)on));
}
__device__ __forceinline__ uint32_t clk() {
    uint32_t t;
    asm volatile("mov.u32 %0, %%clock;" : "=r"(t) :: "memory");
    return t;
}
__device__ __forceinline__ void sg_add(int row, float a, float b, float c, float d) {
    red_v4(g_Sg + row, a, b, c, d);
    st_rlx(g_dirty + (row >> 5), 1u);
}
__device__ __forceinline__ void slow_add(const uint2* m, uint32_t sb, int in, int out, float c) {
    const uint2 r = __ldg(m + in);
    const float x[4] = {bflo(r.x), bfhi(r.x), bflo(r.y), bfhi(r.y)};
    float y[4] = {0.f, 0.f, 0.f, 0.f};
#pragma unroll
    for (int k = 0; k < 4; k++) {
        const uint4 q = lds128(sb + SM_W + 320 + k * 16);
        y[0] = k ? y[0] + x[k] * __uint_as_float(q.x) : x[k] * __uint_as_float(q.x);
        y[1] = k ? y[1] + x[k] * __uint_as_float(q.y) : x[k] * __uint_as_float(q.y);
        y[2] = k ? y[2] + x[k] * __uint_as_float(q.z) : x[k] * __uint_as_float(q.z);
        y[3] = k ? y[3] + x[k] * __uint_as_float(q.w) : x[k] * __uint_as_float(q.w);
    }
    const uint32_t lo = pack_bf2(y[0], y[1]), hi = pack_bf2(y[2], y[3]);
    sg_add(out, c * bflo(lo), c * bfhi(lo), c * bflo(hi), c * bfhi(hi));
}

struct Mat4 { uint32_t b[4]; };
__device__ __forceinline__ Mat4 load_mat4(const __nv_bfloat16* w, int lane) {
    const unsigned short* u = (const unsigned short*)w + (lane >> 2 & 1);
    const bool on = lane >> 3 == (lane & 3);
    Mat4 m;
#pragma unroll
    for (int k = 0; k < 4; k++) m.b[k] = on ? u[(k & 1) * 8 + (k & 2)] | (uint32_t)u[(k & 1) * 8 + 4 + (k & 2)] << 16 : 0u;
    return m;
}
__device__ __forceinline__ void mul4(const uint4& x, const Mat4& m, float (&y)[8]) {
#pragma unroll
    for (int h = 0; h < 2; h++)
        asm("mma.sync.aligned.m16n8k16.row.col.f32.bf16.bf16.f32 {%0,%1,%2,%3}, {%4,%5,%6,%7}, {%8,%9}, {%10,%10,%10,%10};"
            : "=f"(y[2 * h]), "=f"(y[2 * h + 1]), "=f"(y[4 + 2 * h]), "=f"(y[5 + 2 * h])
            : "r"(x.x), "r"(x.z), "r"(x.y), "r"(x.w), "r"(m.b[2 * h]), "r"(m.b[2 * h + 1]), "f"(0.f));
}

struct Scale { uint32_t eb[4]; bool allslow; };
__device__ __forceinline__ void md_stats(const uint4& in, const Mat4& wd, int lane) {
    float y[8];
    mul4(in, wd, y);
    uint32_t mx[4], se[4];
#pragma unroll
    for (int c = 0; c < 4; c++) {
        uint32_t a = __float_as_uint(y[c]) & 0x7fffffffu, b = __float_as_uint(y[4 + c]) & 0x7fffffffu;
        if (a >= 0x7f800000u) a = 0;
        if (b >= 0x7f800000u) b = 0;
        mx[c] = __reduce_max_sync(0xffffffffu, max(a, b));
        se[c] = __reduce_add_sync(0xffffffffu, (a >> 23) + (b >> 23) + (a ? 1u << 20 : 0u) + (b ? 1u << 20 : 0u));
    }
    if (lane < 4) {
        asm volatile("red.shared.max.u32 [%0], %1;" ::"r"(SB + SM_STAT + lane * 4), "r"(lane == 0 ? mx[0] : lane == 1 ? mx[1] : lane == 2 ? mx[2] : mx[3]) : "memory");
        reds_add(SB + SM_STAT + 16 + lane * 4, lane == 0 ? se[0] : lane == 1 ? se[1] : lane == 2 ? se[2] : se[3]);
    }
}
__device__ __forceinline__ Scale get_scale(uint32_t sb) {
    Scale s;
    s.allslow = false;
#pragma unroll
    for (int k = 0; k < 4; k++) {
        const uint32_t mx = lds32(sb + SM_STAT + 4 * k), se = lds32(sb + SM_STAT + 16 + 4 * k);
        const uint32_t mean = (uint32_t)__fdividef((float)(se & 0xfffffu), (float)max(se >> 20, 1u));
        uint32_t eb = min(min((mx + 0x6e0000u) >> 23, mean + 5u), 227u);
        if (eb < 27u) { s.allslow = s.allslow || mx != 0; eb = 27u; }
        if (eb > 170u) s.allslow = true;
        s.eb[k] = eb;
    }
    return s;
}

__device__ __forceinline__ uint32_t probe_rt(uint32_t* p) {
    uint32_t best = 0xffffffffu;
#pragma unroll 1
    for (int r = 0; r < CFG_PROBES; r++) {
        const uint32_t t0 = clock();
        uint32_t v;
        asm volatile("atom.relaxed.gpu.global.add.u32 %0, [%1], 1;" : "=r"(v) : "l"(p) : "memory");
        if (v > 100000u) __trap();
        const uint32_t t1 = clock();
        best = min(best, t1 - t0);
    }
    return best;
}
__device__ __forceinline__ uint32_t* pub_ptr(const Params& p, int blk, uint32_t sel) {
    const int pr = blk / 44;
    return (uint32_t*)(p.ring + PROBE_OFF + (pr ? 4096u << pr : 0u) + (sel << 12) + 2176 + (blk - pr * 44) * 32);
}
__device__ __forceinline__ void probe(const Params& p, uint32_t sb, int w, int lane) {
    const int blk = blockIdx.x, pr = w >> 1;
    uint32_t off = PROBE_OFF + blk * 16 + (pr ? 4096u << pr : 0u);
    if (pr == 7) off = blk < NWIN ? blk * WIN + 4064 : PROBE_OFF + 3584 + blk % 16 * 32;
    off += (w & 1) * 4096;
    if (lane < 8) st_rlx((uint32_t*)(p.ring + (off & ~31u)) + lane, 0u);
    if (lane == 0) sts32(sb + SM_PROBE + w * 4, probe_rt((uint32_t*)(p.ring + off)));
}
__device__ __forceinline__ void assign_role(const Params& p, uint32_t sb, int lane) {
    {
        const bool x = lane < 8 && lds32(sb + SM_PROBE + lane * 8 + 4) < lds32(sb + SM_PROBE + lane * 8);
        const uint32_t near = __ballot_sync(0xffffffffu, x), bits = near & 1 ? ~near | 1u : near;
        const uint32_t tag = (lds32(sb + SM_MISC + 16) + 1) << 30;
        if (lane < 16) st_rlx(pub_ptr(p, blockIdx.x, lane >> 3) + (lane & 7), tag | (bits & 0xffu));
        constexpr int K = (NCTA + 31) / 32;
        __nanosleep(CFG_P0);
        uint32_t v[K], bad;
        int guard = 0;
        do {
            bad = 0;
#pragma unroll
            for (int k = 0; k < K; k++) {
                const int b = min(lane + 32 * k, NCTA - 1);
                v[k] = ld_rlx(pub_ptr(p, b, near >> (b / 44) & 1));
                bad |= v[k] ^ tag;
            }
            bad = __any_sync(0xffffffffu, bad >> 30);
            if (bad) __nanosleep(CFG_PSLEEP);
            if (++guard > GUARD) __trap();
        } while (bad);
#pragma unroll
        for (int k = 0; k < K; k++) sts32(sb + SM_PUB + (lane + 32 * k) * 4, v[k]);
    }
    __syncwarp();
    constexpr int NP = NCTA / 2, NTAB = H2 + H3;
    const int me = blockIdx.x >> 1, odd = blockIdx.x & 1;
    uint32_t pp[3], key[3];
    int n1 = 0;
#pragma unroll
    for (int k = 0; k < 3; k++) {
        const int i = lane + 32 * k;
        pp[k] = lds32(sb + SM_PUB + min(i, NP - 1) * 8) & 1;
        key[k] = (i * CFG_KM % CFG_KN) << 8 | i;
        n1 += 2 * __popc(__ballot_sync(0xffffffffu, i < NP && pp[k]));
    }
    bool fixed = n1 < NTAB || NCTA - n1 < NTAB;
    if (fixed) {
        n1 = NP / 2 * 2;
        pp[0] = pp[1] = pp[2] = lane & 1;
    }
    const uint32_t mine = __shfl_sync(0xffffffffu, (me < 32 ? key[0] : me < 64 ? key[1] : key[2]) * 2 + (me < 32 ? pp[0] : me < 64 ? pp[1] : pp[2]), me & 31);
    const int part = mine & 1;
    int pos = odd;
#pragma unroll
    for (int k = 0; k < 3; k++) pos += 2 * __popc(__ballot_sync(0xffffffffu, lane + 32 * k < NP && pp[k] == (uint32_t)part && key[k] < mine / 2));
    const int role = pos < H2 ? 1 : pos < NTAB ? 2 : 0;
    const int id = pos < H2 ? part * H2 + pos : pos < NTAB ? part * H3 + pos - H2 : (part ? NCTA - n1 - NTAB : 0) + pos - NTAB;
    const uint32_t v = lds32(sb + SM_PUB + lane * 4);
    uint32_t lin = 0;
#pragma unroll
    for (int b = 0; b < 6; b++) lin |= (__popc(__ballot_sync(0xffffffffu, (v >> (b + 1)) & 1)) > 16 ? 1u : 0u) << b;
    if (lane == 0) {
        sts32(sb + SM_MISC, role << 8 | id);
        sts32(sb + SM_MISC + 4, lin);
        sts32(sb + SM_MISC + 8, NCTA - n1 - NTAB);
        sts32(sb + SM_MISC + 20, part);
        sts32(sb + SM_MISC + 12, role == 0 ? id : role == 1 ? N1 + id : N1 + N2 + id);
    }
}
__device__ __forceinline__ uint32_t sel_of(uint32_t sb, int widx, uint32_t k, int part) {
    return (__popc(k & lds32(sb + SM_MISC + 4)) ^ (lds32(sb + SM_PUB + widx * 4) >> 7) ^ part) & 1;
}
__device__ __forceinline__ uint32_t gran_off(uint32_t sb, int widx, int k, int part) { return (2 * k + sel_of(sb, widx, k, part)) << 12; }
__device__ __forceinline__ uint32_t q1a_off(uint32_t sb, int src, int blk, int part) { return gran_off(sb, 2 * blk + part, src >> 1, part) + (src & 1) * 2048; }
__device__ __forceinline__ uint32_t q1h_off(uint32_t sb, int src, int blk, int part) { return gran_off(sb, 2 * blk + part, 32 + (src >> 2), part) + (src & 3) * 1024; }
__device__ __forceinline__ uint32_t* ctl_word(const Params& p, uint32_t sb, int k, int word, int part) {
    const int widx = CWIN + lds32(sb + SM_MISC + 16);
    return (uint32_t*)(p.ring + (widx * WIN + ((2 * k + sel_of(sb, widx, k, part)) << 12))) + word;
}
__device__ __forceinline__ uint32_t* cred1_of(const Params& p, uint32_t sb, int src) { return ctl_word(p, sb, src >> 3, (src & 7) * 128, src >= (int)lds32(sb + SM_MISC + 8)); }
__device__ __forceinline__ uint32_t* fin1_of(const Params& p, uint32_t sb, int dst) { return ctl_word(p, sb, 8 + (dst >> 3), (dst & 7) * 128, dst / H2); }
__device__ __forceinline__ uint32_t* cred2_of(const Params& p, uint32_t sb, int src) { return ctl_word(p, sb, 16 + (src >> 3), (src & 7) * 128, src / H2); }
__device__ __forceinline__ uint32_t* fin2_of(const Params& p, uint32_t sb, int dst) { return ctl_word(p, sb, 24 + (dst >> 3), (dst & 7) * 128, dst / H3); }
__device__ __forceinline__ uint32_t* rdy_of(const Params& p, uint32_t sb, int word, int part) { return ctl_word(p, sb, 28, word, part); }
__device__ __forceinline__ uint32_t q2_off(uint32_t sb, int blk, int dst) {
    return (N2 + dst) * WIN + gran_off(sb, N2 + dst, (blk >> 1) * 4 + (blk & 1), dst / H3);
}
template <bool IS1>
__device__ __forceinline__ void clear_queues(const Params& p, uint32_t sb, int id, int lane) {
    constexpr int NA = (N1 + 1) / 2, NG = NA + (N1 + 3) / 4, N = IS1 ? NG * N2 : NI * 2;
    if (IS1) {
#pragma unroll 1
        for (int k = 0; k < 8; k++) sts128(sb + SM_ZERO + (k * 32 + lane) * 16, make_uint4(0, 0, 0, 0));
        if (lane == 0) spin_ge(rdy_of(p, sb, 320, lds32(sb + SM_MISC + 20)), NTAIL);
    }
    __syncwarp();
    fence_async_smem();
    for (int k = IS1 ? id + (lane < CFG_CLN ? lane : N) * N1 : lane; k < N; k += IS1 ? CFG_CLN * N1 : 32) {
        if (IS1 && k >= CFG_CLN * N1) __nanosleep(CFG_CLS);
        const int wi = k / NG, g = k - wi * NG;
        const uint32_t off = IS1 ? wi * WIN + gran_off(sb, wi, g < NA ? g : 32 + g - NA, wi & 1) : q2_off(sb, k >> 1, id) + (k & 1) * 16384;
        bulk_store(p.ring + off, sb + SM_ZERO, 4096);
    }
    asm volatile("cp.async.bulk.commit_group;" ::: "memory");
    asm volatile("cp.async.bulk.wait_group 0;" ::: "memory");
    TR(21, IS1 && lane == 0);
    if (!IS1) {
        fence_async_all();
        __syncwarp();
        fence_gpu();
        if (lane < NI) red_rlx(rdy_of(p, sb, id / H3 * H2 + lane, id / H3), 1u);
    }
    __syncwarp();
}

struct In8 { uint4 a[2], o[2]; uint2 g[2]; };
__device__ __forceinline__ void p1_load(const Params& p, In8& r, int i4) {
#pragma unroll
    for (int u = 0; u < 2; u++) {
        [[maybe_unused]] uint32_t x, y;
        asm volatile("tex.1d.v4.u32.s32 {%0,%1,%2,%3}, [%4, {%5}];" : "=r"(r.a[u].x), "=r"(r.a[u].y), "=r"(r.a[u].z), "=r"(r.a[u].w) : "l"(p.t_in), "r"(i4 + u * 32));
        asm volatile("tex.1d.v4.u32.s32 {%0,%1,%2,%3}, [%4, {%5}];" : "=r"(r.o[u].x), "=r"(r.o[u].y), "=r"(r.o[u].z), "=r"(r.o[u].w) : "l"(p.t_out), "r"(i4 + u * 32));
        asm volatile("tex.1d.v4.u32.s32 {%0,%1,%2,%3}, [%4, {%5}];" : "=r"(r.g[u].x), "=r"(r.g[u].y), "=r"(x), "=r"(y) : "l"(p.t_ang), "r"(i4 + u * 32));
    }
}
__device__ __forceinline__ uint32_t imad(uint32_t a, uint32_t b, uint32_t c) {
    uint32_t r;
    asm("mad.lo.u32 %0, %1, %2, %3;" : "=r"(r) : "r"(a), "r"(b), "r"(c));
    return r;
}
__device__ __forceinline__ unsigned char* ring_ptr(const Params& p, uint32_t lo) {
    uint64_t r;
    asm("mov.b64 %0, {%1, %2};" : "=l"(r) : "r"(lo), "r"(p.ring_hi));
    return (unsigned char*)r;
}
__device__ __forceinline__ uint32_t keep32(uint32_t x) {
    return __shfl_sync(0xffffffffu, x, threadIdx.x & 31);
}
__device__ __forceinline__ uint32_t opaque32(uint32_t x) {
    asm volatile("" : "+r"(x));
    return x;
}
template <typename T> __device__ __forceinline__ T* opaque(T* p) {
    asm volatile("" : "+l"(p));
    return p;
}
template <int LUT> __device__ __forceinline__ uint32_t lop3(uint32_t a, uint32_t b, uint32_t c) {
    uint32_t r;
    asm("lop3.b32 %0, %1, %2, %3, %4;" : "=r"(r) : "r"(a), "r"(b), "r"(c), "n"(LUT));
    return r;
}
__device__ __forceinline__ uint32_t dp4(uint32_t a, uint32_t b, uint32_t c) {
    uint32_t r;
    asm("dp4a.u32.u32 %0, %1, %2, %3;" : "=r"(r) : "r"(a), "r"(b), "r"(c));
    return r;
}
__device__ __forceinline__ uint32_t dp2(uint32_t a, uint32_t b, uint32_t c) {
    uint32_t r;
    asm("dp2a.lo.u32.u32 %0, %1, %2, %3;" : "=r"(r) : "r"(a), "r"(b), "r"(c));
    return r;
}
__device__ __forceinline__ void p1_put(uint32_t sb, uint32_t wa, uint32_t wb, uint32_t old, bool on) {
    asm volatile("{.reg .pred q; setp.ne.u32 q, %3, 0; @q st.shared.v2.u32 [%0], {%1,%2};}"
                 ::"r"(sb + A_ST + prmt(old, wb, 0xf762)), "r"(wa), "r"(prmt(wb, old, 0x7210)), "r"((uint32_t)on) : "memory");
}
__device__ __forceinline__ void p1_slow_tile(const Params& p, uint32_t sb, int i4) {
    const float f = __bfloat162float(p.freq[0]);
#pragma unroll 1
    for (int u = 0; u < 8; u++) {
        const int k4 = i4 + (u >> 2) * 32;
        if (k4 < p.n4) {
            const size_t t = (size_t)k4 * 4 + (u & 3);
            const float x = __bfloat162float(__float2bfloat16(f * __bfloat162float(p.angle[t])));
            slow_add(p.m, sb, p.idx_in[t], p.idx_out[t], __bfloat162float(__float2bfloat16(cosf(x))));
        }
    }
}
__device__ __forceinline__ void role_p1(const Params& p, uint32_t sb, int id, int w, int lane) {
    lane = keep32(lane);
    const uint32_t f2 = (uint32_t)__bfloat16_as_ushort(p.freq[0]) * 0x10001u;
    constexpr int TG = CFG_TG, NTK = P1W;
    static_assert(NTK <= 16, "tickets");
    const int tc = (w + id) % NTK, first = (N1 * P1W + tc) * (TG * 64);
    uint32_t* const tickets = opaque(ctl_word(p, sb, 29 + tc / 8, tc % 8 * 128 + lane, tc & 1));
    auto draw = [&]() {
        uint32_t t = 0;
        asm volatile("{.reg .pred q; setp.eq.u32 q, %2, 0; @q atom.relaxed.gpu.global.add.u32 %0, [%1], 1;}" : "+r"(t) : "l"(tickets), "r"(lane) : "memory");
        return t;
    };
    int i4 = (id * P1W + w) * (TG * 64);
    In8 r;
    ACC_DECL
    uint32_t tk = draw();
    p1_load(p, r, i4 + lane);
    while (i4 < p.n4) {
        const int cur = i4;
        i4 += 64;
        if (i4 % (TG * 64) == 0) {
            i4 = min(__shfl_sync(0xffffffffu, tk, 0), 0x7fffffffu / (NTK * TG * 64) - N1 * P1W / NTK - 2) * (NTK * TG * 64) + first;
            tk = draw();
        }
        uint32_t wa[8], wb[8], x2[4];
        x2[0] = mul_bf2(r.g[0].x, f2); x2[1] = mul_bf2(r.g[0].y, f2);
        x2[2] = mul_bf2(r.g[1].x, f2); x2[3] = mul_bf2(r.g[1].y, f2);
        const uint32_t mx = maxabs_bf2(maxabs_bf2(x2[0], x2[1]), maxabs_bf2(x2[2], x2[3]));
        const bool fast = __all_sync(0xffffffffu, cur + 64 <= p.n4 && ((mx & 0x7fffu) <= 0x4300u) && ((mx & 0x7fff0000u) <= 0x43000000u));
        {
            const uint32_t in[8] = {r.a[0].x, r.a[0].y, r.a[0].z, r.a[0].w, r.a[1].x, r.a[1].y, r.a[1].z, r.a[1].w};
            const uint32_t ou[8] = {r.o[0].x, r.o[0].y, r.o[0].z, r.o[0].w, r.o[1].x, r.o[1].y, r.o[1].z, r.o[1].w};
#pragma unroll
            for (int j = 0; j < 8; j += 2) {
                const uint32_t ch = mul_h2(pack_h2(__cosf(bflo(x2[j >> 1])), __cosf(bfhi(x2[j >> 1]))), 0x24002400u);
#pragma unroll
                for (int k = j; k < j + 2; k++) {
                    const uint32_t blk = __umulhi(in[k], p.magic2), il = imad(blk, p.nrows2, in[k]);
                    wa[k] = k & 1 ? bitsel(ch, il, 0xffff0000u) : imad(ch, 65536u, il);
                    wb[k] = imad(blk, 1u << 21, imad(ou[k] >> 5, 1u - (1u << 21), ou[k] << 16));
                }
            }
        }
        p1_load(p, r, i4 + lane);
        if (fast) {
            uint32_t old[8], any = 0;
#pragma unroll
            for (int j = 0; j < 8; j++) old[j] = atoms_add(dp2(wb[j], 0x400u, 0u) + (sb + A_CNT), 0x80001u);
#pragma unroll
            for (int j = 0; j < 8; j++) any |= old[j];
            if (!__any_sync(0xffffffffu, any & 0xffe0u)) {
#pragma unroll
                for (int j = 0; j < 8; j++) p1_put(sb, wa[j], wb[j], old[j], true);
            } else {
                uint32_t pend = 0;
#pragma unroll
                for (int j = 0; j < 8; j++) { p1_put(sb, wa[j], wb[j], old[j], !(old[j] & 0xffe0u)); if (old[j] & 0xffe0u) pend |= 1u << j; }
                ACC(0, 1)
                for (int guard = 0; __any_sync(0xffffffffu, pend); guard++) {
                    __nanosleep(CFG_BSLEEP);
                    ACC(1, 1)
#pragma unroll
                    for (int j = 0; j < 8; j++) {
                        if (__any_sync(0xffffffffu, pend >> j & 1)) {
                            const uint32_t c = lds32v(sb + A_CNT + (pend >> j & 1 ? wb[j] >> 16 : 0) * 4);
                            const bool go = (pend >> j & 1) && (((old[j] >> 19) - (c >> 19) + c) & 8191u) < 32u;
                            p1_put(sb, wa[j], wb[j], old[j], go);
                            if (go) pend &= ~(1u << j);
                        }
                    }
                    if (guard > GUARD) __trap();
                }
            }
        } else {
            p1_slow_tile(p, sb, cur + lane);
            __syncwarp();
        }
    }
    __syncwarp();
    mbar_arrive_if(sb + SM_DONE, lane == 0);
    ACC_SAVE
}

__device__ __forceinline__ void role_flush(const Params& p, uint32_t sb, int id, int f, int lane) {
    lane = keep32(lane);
    const int half = lane >> 4, o = lane >> 2, q = lane & 3;
    const uint32_t hm = keep32(half ? 0xffff0000u : 0xffffu), lth = keep32(((1u << lane) - 1) & hm);
    const uint32_t list = sb + A_LIST + f * LISTB, cnt = keep32(sb + A_CNT + (f * GPW * 32 + lane) * 4);
    const uint32_t cred = opaque32(sb + SM_CRED + (half * 32 + f * GPW) * 4);
    const uint32_t pa = opaque32(p.ring_lo + (id >> 1) * 8192 + (id & 1) * 2048 + q * 16);
    const uint32_t ph = opaque32(p.ring_lo + (32 + (id >> 2)) * 8192 + (id & 3) * 1024 + q * 8 - 2048);
    const uint32_t sa = q * 16 + (o & 1) * 64;
    uint32_t qo[GPW], hs[GPW], cr[4] = {0, 0, 0, 0};
#pragma unroll
    for (int g = 0; g < GPW; g++) {
        const int blk = f * GPW + g;
        qo[g] = 32u << 25;
        const uint32_t sa = sel_of(sb, 2 * blk + half, id >> 1, half), sh = sel_of(sb, 2 * blk + half, 32 + (id >> 2), half);
        hs[g] = sa << 31 | (2 * sh + 1 - sa) << 22 | 1u << 24 | (lane & 15) << 15 | (blk * 32 + lane) * 2;
    }
    uint4 x[KR] = {}, y[KR] = {};
    uint32_t c[GPW] = {};
    auto scan = [&]() {
#pragma unroll
        for (int g = 0; g < GPW; g++) c[g] = lds32v(cnt + g * 128);
    };
    auto credits = [&]() {
        if (GPW == 4) { const uint4 v = lds128(cred); cr[0] = v.x; cr[1] = v.y; cr[2] = v.z; cr[3] = v.w; }
        else { const uint2 v = lds64v(cred); cr[0] = v.x; cr[1] = v.y; }
    };
    ACC_DECL
    int guard = 0;
    bool idle = false, done = false;
    while (true) {
        uint32_t fr[GPW], rank[GPW], num = 0, left = 0;
        bool ok[GPW];
        if (idle && !done && __all_sync(0xffffffffu, mbar_test(sb + SM_DONE, 0))) {
            done = true;
            TR(17, f == 0 && lane == 0);
#pragma unroll
            for (int g = 0; g < GPW; g++) {
                const uint32_t u = lds32v(cnt + g * 128) & 31u, hd = hs[g] ^ (u & 16u ? imad(hs[g], 1u << 24, 1u) & 0x01000001u : 0u);
#pragma unroll 2
                for (uint32_t j = 0, k; k = (j + lane) & 15u, j < 16; j++)
                    sts64_if(sb + A_ST + ((hd & 0x7ffu) << 7) + k * 8, p.rows2, (lane * 16 + k) | (hd & 0x1000000u), (u & 15u) && k >= (u & 15u));
                reds_add(cnt + g * 128, ((0u - u) & 15u) * 0x80001u);
            }
            __syncwarp();
            scan();
        }
#pragma unroll
        for (int g = 0; g < GPW; g++) {
            const bool isfull = c[g] & 0xfff0u;
            rank[g] = __popc(__ballot_sync(0xffffffffu, isfull) & lth);
            ok[g] = isfull && (int)(rank[g] << 25) < (int)(cr[g] - qo[g] + (63u << 25));
            ACC(2, __popc(__ballot_sync(0xffffffffu, isfull && !ok[g])))
        }
#pragma unroll
        for (int g = 0; g < GPW; g++) {
            const uint32_t m = __ballot_sync(0xffffffffu, ok[g]), n = __popc(m & hm), all = __popc(m), e = num + rank[g] + (half ? all - n : 0u);
            sts32_if(KR == 2 ? list + (e & 48u) * 4 + (e & 7u) * 8 + (e >> 1 & 4u) : imad(e, 4u, list), bitsel(imad(rank[g], 1u << 25, qo[g]), hs[g], 0x7e000000u), ok[g]);
            if (ok[g]) hs[g] ^= imad(hs[g], 1u << 24, 1u) & 0x01000001u;
            fr[g] = ok[g] ? 0u - 16u : 0u;
            left |= c[g] + fr[g];
            qo[g] = imad(n, 1u << 25, qo[g]);
            num += all;
        }
        __syncwarp();
        ACC(0, 1) ACC(1, num)
        if (num) {
            uint32_t la = list + o * (KR == 2 ? 8 : 4);
            int todo = (int)num - o, rest = num;
            do {
                uint32_t d[KR];
                if (KR == 2) { const uint2 v = lds64v(la); d[0] = v.x; d[KR - 1] = v.y; }
                else {
#pragma unroll
                    for (int k = 0; k < KR; k++) d[k] = lds32v(la + 32 * k);
                }
                while (true) {
                    uint32_t bad = 0;
#pragma unroll
                    for (int k = 0; k < KR; k++) {
                        const uint32_t m = d[k] & 0x7ffu;
                        lds128_keep(x[k], imad(m, 128u, sa) + (sb + A_ST), todo > 8 * k);
                        lds128_keep(y[k], imad(m, 128u, sa ^ 64) + (sb + A_ST), todo > 8 * k);
                    }
#pragma unroll
                    for (int k = 0; k < KR; k++)
                        or3_if(bad, lop3<0x7e>(x[k].y, x[k].w, d[k]), lop3<0x7e>(y[k].y, y[k].w, d[k]), todo > 8 * k);
                    if (!__any_sync(0xffffffffu, (int)imad(bad, 128u, 0u) < 0)) break;
                    if (++guard > GUARD) __trap();
                }
#pragma unroll
                for (int k = 0; k < KR; k++) {
                    const uint32_t mi = d[k] & 0x7e0u, dm = d[k] & 0xbec00000u;
                    x[k].x = bitsel(d[k], x[k].x, 0x40078000u);
                    x[k].y = prmt(x[k].y, x[k].w, 0x5410);
                    x[k].w = prmt(y[k].y, y[k].w, 0x5410);
                    y[k].x = bitsel(d[k], y[k].x, 0x40000000u);
                    y[k].y = y[k].z;
                    stg_q128(ring_ptr(p, dp4(dm, 0x20000000u, imad(mi, WIN / 32, pa))), x[k].x, x[k].y, x[k].z, x[k].w, todo > 8 * k);
                    stg_q64(ring_ptr(p, dp4(dm, 0x10200000u, imad(mi, WIN / 32, ph))), y[k].x, y[k].y, todo > 8 * k);
                }
                la += 32 * KR;
                todo -= 8 * KR;
                rest -= 8 * KR;
            } while (rest > 0);
#pragma unroll
            for (int g = 0; g < GPW; g++) c[g] = atoms_add(cnt + g * 128, fr[g]) + fr[g];
            credits();
            idle = num <= CFG_TH;
            if (done && !__any_sync(0xffffffffu, left & 0xffffu)) break;
            if (idle) { __nanosleep(CFG_TS); scan(); credits(); }
        } else {
            if (done && !__any_sync(0xffffffffu, left & 0xffffu)) break;
            idle = true;
            __nanosleep(CFG_FSLEEP);
            scan();
            credits();
            if (++guard > GUARD) __trap();
        }
    }
#pragma unroll
    for (int g = 0; g < GPW; g++) st_rlx_if(fin1_of(p, sb, half * H2 + f * GPW + g) + id, qo[g] - (32u << 25) + 1u, (lane & 15) == 0 && f * GPW + g < NI);
    mbar_arrive_if(sb + SM_DONE2, lane == 0);
    TR(18, f == 0 && lane == 0);
    ACC_SAVE
}
__device__ __forceinline__ void role_credit1(const Params& p, uint32_t sb, int id, int lane) {
    const uint32_t* const cred = cred1_of(p, sb, id) + lane * 2;
    for (int guard = 0; !__all_sync(0xffffffffu, mbar_test(sb + SM_DONE2, 0)); guard++) {
        const uint2 v = ldg_q64(cred);
        sts64(sb + SM_CRED + lane * 8, v.x, v.y);
        __nanosleep(CFG_C1SLEEP);
        if (guard > GUARD) __trap();
    }
}

__device__ __forceinline__ float h2f(uint32_t h) {
    float f;
    asm("{.reg .b16 t; cvt.u16.u32 t, %1; cvt.f32.f16 %0, t;}" : "=f"(f) : "r"(h));
    return f;
}
__device__ __forceinline__ void p2_slow(const Params& p, uint32_t sb, const uint32_t* tmp, int row0, uint32_t dst) {
#pragma unroll 1
    for (int j = 0; j < 4; j++)
        if (tmp[8 + j] & 0x40u) slow_add(p.m, sb, row0 + (tmp[j] & 0x7fffu), (tmp[4 + j] & 0x7fffu) * 32 + dst, h2f(tmp[j] >> 16) * 64.0f);
}
__device__ __forceinline__ uint32_t mul_h2_hi(uint32_t a, uint32_t b) {
    uint32_t r;
    asm("{.reg .b16 l, h; .reg .b32 t; mov.b32 {l, h}, %2; mov.b32 t, {h, h}; mul.rn.f16x2 %0, %1, t;}" : "=r"(r) : "r"(a), "r"(b));
    return r;
}
template <bool CHECK>
__device__ __forceinline__ void role_p2(const Params& p, uint32_t sb, int id, int w, int lane) {
    lane = keep32(lane);
    const int part = id / H2, blk = id - part * H2, row0 = blk * p.rows2;
    const int o = lane >> 2, q = lane & 3;
    uint32_t* const cbase = (uint32_t*)(p.ring + (CWIN + lds32(sb + SM_MISC + 16)) * WIN);
    const uint32_t cred = opaque32((uint32_t)(uintptr_t)(cbase + part * 32 + blk));
    const uint32_t pa = opaque32(p.ring_lo + (2 * blk + part) * WIN + q * 16), ph = opaque32(pa - q * 8);
    const uint32_t po = opaque32(p.ring_lo + (q2_off(sb, blk, part * H3) & ~4096u) + q * 16 + (o & 1) * 64);
    const uint32_t sel = __ballot_sync(0xffffffffu, q2_off(sb, blk, part * H3 + (lane & 15)) & 4096u) << 12;
    const uint32_t* const fins = fin1_of(p, sb, id);
    uint32_t st[QPW] = {}, sq[QPW] = {};
    uint4 qa[NBT];
    uint2 qh[NBT];
    auto load = [&](int k) {
        qa[k] = ldg_q128(ring_ptr(p, pa + (bitsel(sq[k], st[k] >> 19, 0x7f800u) & 0x7ffc0u)));
        qh[k] = ldg_q64(ring_ptr(p, ph + (bitsel(sq[k] >> 9, st[k] >> 20, 0x7fc00u) & 0x7ffe0u)));
    };
#pragma unroll
    for (int k = 0; k < QPW; k++) {
        const int src = w * QPW + k;
        st[k] = o << 25 | (src < N1 ? 1u : 5u);
        sq[k] = src < N1 ? q1h_off(sb, src, blk, part) << 9 | q1a_off(sb, src, blk, part) | (uint32_t)(cred1_of(p, sb, src) - cbase) / 8 : 0x7e000u * 513u;
    }
#pragma unroll
    for (int k = 0; k < NBT; k++) load(k);
    ACC_DECL
    int guard = 0;
    uint32_t streak = 0;
    while (true) {
        uint32_t nn[NBT], xx[NBT][4], hh[NBT][2], dd[NBT], any = 0;
        bool last = false;
#pragma unroll
        for (int k = 0; k < NBT; k++) {
            const uint4 a = qa[k];
            const uint2 h = qh[k];
            uint32_t n = 8;
            const uint32_t miss = __ballot_sync(0xffffffffu, (int)imad((a.x ^ st[k]) & (h.x ^ st[k]), 2u, 0u) >= 0);
            if (miss) {
                n = (__ffs(miss) - 1) >> 2;
                if (!__any_sync(0xffffffffu, st[k] & 8u)) { if (streak < CFG_PSTREAK) n &= CFG_PMASK; }
                else if (!__any_sync(0xffffffffu, ((st[k] >> 6) + ((n - o) << 19) ^ st[k]) & 0x1f80000u)) { st[k] |= 4u; last = true; }
            }
            ACC(1, n == 0) ACC(2, n != 0) ACC(3, n)
            st[k] = imad(n, 1u << 25, st[k]);
            st_rlx_if((uint32_t*)ring_ptr(p, imad(sq[k] & 0x7f0u, 32u, cred)), st[k], lane == 0 && n);
            xx[k][0] = bitsel(a.x, 0x00040000u, 0xbff87fffu); xx[k][1] = a.z; xx[k][2] = h.x & 0xbfffffffu; xx[k][3] = h.y;
            hh[k][0] = a.y; hh[k][1] = a.w; dd[k] = a.x >> 13 & 0x3cu; nn[k] = n;
            any |= n;
        }
        if (!any) {
#pragma unroll
            for (int k = 0; k < QPW; k++) {
                const uint32_t fin = ld_rlx(fins + ((sq[k] >> 12 & 62u) | (sq[k] >> 11 & 1u)));
                if (fin & 1u) st[k] |= (fin >> 6 & 0x1f80000u) | ((fin ^ (st[k] - (o << 25))) >> 25 ? 8u : 12u);
            }
            last = true;
            if (++guard > GUARD) __trap();
            streak++;
        } else streak = 0;
        if (last) {
            uint32_t all = 4u;
#pragma unroll
            for (int k = 0; k < QPW; k++) all &= st[k];
            last = __all_sync(0xffffffffu, all);
        }
        {
            uint32_t t[QPW], u[QPW];
#pragma unroll
            for (int k = 0; k < QPW; k++) { t[k] = st[(k + NBT) % QPW]; u[k] = sq[(k + NBT) % QPW]; }
#pragma unroll
            for (int k = 0; k < QPW; k++) { st[k] = t[k]; sq[k] = u[k]; }
        }
#pragma unroll
        for (int k = 0; k < NBT; k++) load(k);
#pragma unroll
      for (int k = 0; k < NBT; k++) {
        if (nn[k]) {
            const uint32_t* const x = xx[k];
            const uint32_t h0 = hh[k][0], h1 = hh[k][1], d4 = dd[k];
            const bool v = o < nn[k];
            uint32_t old = 0, ta[4], tb[4], w0[4], w1[4];
            atoms_add_keep(old, sb + SM_CNT2 + d4, 0x10001u, q == 0 && v);
#pragma unroll
            for (int j = 0; j < 4; j++) {
                ta[j] = lds32nv(dp2(x[j], 4u, 0u) + (sb + B_TA));
                tb[j] = lds16nv(dp2(x[j], 2u, 0u) + (sb + B_TB));
            }
            old = __shfl_sync(0xffffffffu, old, lane & 28);
            const uint32_t tag = old << 8 & 0x40000000u;
#pragma unroll
            for (int j = 0; j < 4; j++) {
                const uint32_t z = prmt(j & 2 ? h1 : h0, 0, j & 1 ? 0x4342 : 0x4140);
                const uint32_t t23 = prmt((ta[j] & 0x60076007u) * 2050u, tb[j], 0x5341) & 0xfffcffffu;
                w0[j] = (imad(z, 128u, j & 1 ? 0u : tag) & 0x78007800u) | mul_h2_hi(ta[j] & 0x9ff89ff8u, x[j]);
                w1[j] = (imad(z, 2048u, 0u) & 0x78007800u) | mul_h2_hi(t23, x[j]);
            }
            if (CHECK && v && ((tb[0] | tb[1] | tb[2] | tb[3]) & 0x40u)) {
                uint32_t tmp[12];
#pragma unroll
                for (int j = 0; j < 4; j++) {
                    tmp[j] = x[j]; tmp[4 + j] = (j & 2 ? h1 : h0) >> (j & 1 ? 16 : 0); tmp[8 + j] = tb[j];
                    if (tb[j] & 0x40u) { w0[j] &= 0x78007800u; w1[j] &= 0x78007800u; }
                }
                p2_slow(p, sb, tmp, row0, part * H3 + d4 / 4);
            }
            const uint32_t off = (bitsel(old >> 9, old >> 7, 0x0f80u) & 0x4f80u) + imad(d4, WIN / 4, (sel >> (d4 / 4) & 4096u) + po);
            bool wait = old & (0x10000u - NQ2);
            if (!__any_sync(0xffffffffu, wait)) {
                stg_q128(ring_ptr(p, off), w0[0], w1[0], w0[1], w1[1], v);
                stg_q128(ring_ptr(p, off ^ 64u), w0[2], w1[2], w0[3], w1[3], v);
            } else {
                bool pend = v;
                ACC(0, 1)
                for (int g2 = 0;; g2++) {
                    stg_q128(ring_ptr(p, off), w0[0], w1[0], w0[1], w1[1], pend && !wait);
                    stg_q128(ring_ptr(p, off ^ 64u), w0[2], w1[2], w0[3], w1[3], pend && !wait);
                    pend = wait;
                    if (!__any_sync(0xffffffffu, pend)) break;
                    __nanosleep(CFG_BSLEEP);
                    const uint32_t c = lds32v(sb + SM_CNT2 + d4);
                    wait = pend && (((old >> 16) - (c >> 16) + c) & 0xffffu) >= NQ2;
                    if (g2 > GUARD) __trap();
                }
            }
        }
      }
        if (last) break;
    }
    TR(17, w == 0 && lane == 0);
    __syncwarp();
    uint32_t rank = 0;
    if (lane == 0) { __threadfence_block(); rank = atoms_add(sb + SM_FIN, 1u); __threadfence_block(); }
    if (__shfl_sync(0xffffffffu, rank, 0) == P2W - 1 && lane < 16)
        st_rlx(fin2_of(p, sb, part * H3 + lane) + blk, FIN | (((lds32v(sb + SM_CNT2 + lane * 4) >> 16) - NQ2) & 0xffffu));
    __syncwarp();
    mbar_arrive_if(sb + SM_DONE, lane == 0);
    ACC_SAVE
}
__device__ __forceinline__ void role_credit(const Params& p, uint32_t sb, int id, int lane) {
    const uint32_t* const cred = cred2_of(p, sb, id) + (lane & 15);
    uint32_t last = 0;
    for (int guard = 0;; guard++) {
        if (__all_sync(0xffffffffu, mbar_test(sb + SM_DONE, 0))) break;
        const uint32_t c = ld_rlx(cred);
        if (lane < 16 && c != last) reds_add(sb + SM_CNT2 + lane * 4, 0u - ((c - last) & 0xffffu));
        last = c;
        __nanosleep(CFG_CSLEEP);
        if (guard > GUARD) __trap();
    }
}

__device__ __forceinline__ void p3_wrap(uint32_t sb, int id, const uint32_t* tmp) {
    const Scale sc = get_scale(sb);
#pragma unroll 1
    for (int j = 0; j < 8; j++) {
        const uint32_t old = tmp[4 + j], v = tmp[12 + j], nw = old + v, t = (old ^ nw) & (v ^ nw);
        if (t & 0x80008000u) {
            const float k = (t & 0x8000u) ? ((v & 0x8000u) ? -1.0f : 1.0f) : 0.0f;
            const float q = (t & 0x80000000u) ? ((int)v < 0 ? -65536.0f : 65536.0f) : 0.0f;
            const uint32_t e0 = (j & 1) ? sc.eb[2] : sc.eb[0], e1 = (j & 1) ? sc.eb[3] : sc.eb[1];
            const float lo = k * 65536.0f * __uint_as_float((e0 - 10) << 23), hi = (q - k) * __uint_as_float((e1 - 10) << 23);
            if (j & 1) sg_add(tmp[j >> 1] * 32 + id, 0.f, 0.f, lo, hi);
            else sg_add(tmp[j >> 1] * 32 + id, lo, hi, 0.f, 0.f);
        }
    }
}
__device__ __forceinline__ uint32_t p3_val(uint32_t w) {
    const uint32_t mk = prmt(w, 0, 0xBB99);
    return ((w & 0x07ff07ffu) ^ mk) - mk;
}
__device__ __forceinline__ void role_p3(const Params& p, uint32_t sb, int id, int w, int lane) {
    lane = keep32(lane);
    uint32_t* const cred = opaque(cred2_of(p, sb, id / H3 * H2 + w) + id % H3);
    const uint32_t pq = opaque32(p.ring_lo + q2_off(sb, w, id) + lane * 16);
    auto off = [&](uint32_t n) { return (n & 1u) << 11 | (n & 2u) << 13; };
    const uint32_t pp = opaque32(pq - lane * 16 + 112);
    const uint32_t* const finp = opaque(fin2_of(p, sb, id) + w);
    auto tag_of = [&](uint32_t n) { return ~n << 28; };
    uint32_t n = 0, fin = 0, pr = 0, pk = 0;
    uint4 v[4] = {};
    bool have = false, last = false;
    ACC_DECL
    int guard = 0;
    while (true) {
        const uint32_t ex = tag_of(n);
        const bool ok = have && !__any_sync(0xffffffffu, ((v[0].x ^ ex) | (v[1].x ^ ex) | (v[2].x ^ ex) | (v[3].x ^ ex)) & 0x40000000u);
        if (ok) n++;
        const bool ready = (ok || !have) && __all_sync(0xffffffffu, !((pr ^ tag_of(n)) & 0x40000000u));
        st_rlx_if(cred, n * 16, lane == 0 && ok);
        if (!ok && !ready && __all_sync(0xffffffffu, fin & FIN)) {
            const uint32_t left = __shfl_sync(0xffffffffu, (fin - n * 16) & 0xffffu, 0);
            if (left - 1u > 0x8000u) break;
            if (left < 16u) {
#pragma unroll
                for (int u = 0; u < 4; u++) {
                    v[u] = make_uint4(ex & 0x40000000u, 0, 0, 0);
                    ldq128_keep(v[u], ring_ptr(p, pq + off(n)) + u * 512, u * 4 + (lane >> 3) < left);
                }
                have = last = !__any_sync(0xffffffffu, ((v[0].x ^ ex) | (v[1].x ^ ex) | (v[2].x ^ ex) | (v[3].x ^ ex)) & 0x40000000u);
                pr = ~tag_of(n + have);
                if (++guard > GUARD) __trap();
                continue;
            }
        }
        uint32_t row[8], val[16];
#pragma unroll
        for (int u = 0; u < 4; u++) {
            const uint4 x = v[u];
            row[2 * u] = prmt(bitsel(x.x << 1, x.y >> 3, 0x7000f000u), 0, 0x4431);
            row[2 * u + 1] = prmt(bitsel(x.z << 1, x.w >> 3, 0x7000f000u), 0, 0x4431);
            val[4 * u] = p3_val(x.x); val[4 * u + 1] = p3_val(x.y);
            val[4 * u + 2] = p3_val(x.z); val[4 * u + 3] = p3_val(x.w);
        }
#pragma unroll
        for (int u = 0; u < 4; u++) ldq128_keep(v[u], ring_ptr(p, pq + off(n)) + u * 512, ready);
        pk = ready ? CFG_PK1 * 128 : ok ? CFG_PK2 * 128 : have ? 15 * 128 : max(pk, CFG_PK3 * 128u);
        pr = ld_rlx((const uint32_t*)ring_ptr(p, pp + off(n + ready) + pk));
        ACC(2, have && !ok)
        have = ready;
        if (!ok) {
            ACC(1, 1)
            fin = ld_rlx(finp);
            if (++guard > GUARD) __trap();
        } else {
#pragma unroll
            for (int u = 0; u < 4; u += 2) {
                uint32_t old[8], chk = 0;
#pragma unroll
                for (int j = 0; j < 4; j++) {
                    old[2 * j] = atoms_add(sb + C_S + row[2 * u + j] * 4, val[4 * u + 2 * j]);
                    old[2 * j + 1] = atoms_add(sb + C_S + ROWS3_MAX * 4 + row[2 * u + j] * 4, val[4 * u + 2 * j + 1]);
                }
#pragma unroll
                for (int j = 0; j < 8; j++) {
                    const uint32_t nw = old[j] + val[4 * u + j];
                    chk |= (old[j] ^ nw) & (val[4 * u + j] ^ nw);
                }
                if (chk & 0x80008000u) {
                    uint32_t tmp[20];
#pragma unroll
                    for (int j = 0; j < 8; j++) { tmp[j >> 1] = row[2 * u + (j >> 1)]; tmp[4 + j] = old[j]; tmp[12 + j] = val[4 * u + j]; }
                    p3_wrap(sb, id, tmp);
                }
            }
            __syncwarp();
            if (last) break;
        }
    }
    ACC_SAVE
}

__device__ __forceinline__ void row_gates(const float* sw, const uint32_t* c2, uint32_t dbits, float4& gs, float4& gr) {
    const uint32_t d2 = dbits * 0x10001u;
    gs = gr = make_float4(0.f, 0.f, 0.f, 0.f);
#pragma unroll
    for (int r2 = 0; r2 < 4; r2++) {
        uint32_t df = sub_bf2(d2, c2[r2]);
        uint32_t ar = mul_bf2(mul_bf2(df, df), 0xC120C120u);
        uint32_t rb = pack_bf2(__expf(bflo(ar)), __expf(bfhi(ar)));
        const float r0 = bflo(rb), r1 = bfhi(rb);
        const float4 s0 = *(const float4*)(sw + r2 * 8), s1 = *(const float4*)(sw + r2 * 8 + 4);
        const float4 q0 = *(const float4*)(sw + 32 + r2 * 8), q1 = *(const float4*)(sw + 32 + r2 * 8 + 4);
        gs.x += r0 * s0.x + r1 * s1.x; gs.y += r0 * s0.y + r1 * s1.y;
        gs.z += r0 * s0.z + r1 * s1.z; gs.w += r0 * s0.w + r1 * s1.w;
        gr.x += r0 * q0.x + r1 * q1.x; gr.y += r0 * q0.y + r1 * q1.y;
        gr.z += r0 * q0.z + r1 * q1.z; gr.w += r0 * q0.w + r1 * q1.w;
    }
}
__device__ __forceinline__ uint2 finish_row(const float* wu, const float4& gs, const float4& gr, const float S[4], uint2 mrow) {
    const float a[4] = {S[0] * gs.x, S[1] * gs.y, S[2] * gs.z, S[3] * gs.w};
    float u[4] = {0, 0, 0, 0};
#pragma unroll
    for (int k = 0; k < 4; k++) {
        u[0] += a[k] * wu[4 * k]; u[1] += a[k] * wu[4 * k + 1]; u[2] += a[k] * wu[4 * k + 2]; u[3] += a[k] * wu[4 * k + 3];
    }
    return make_uint2(pack_bf2(bflo(mrow.x) + u[0] * gr.x, bfhi(mrow.x) + u[1] * gr.y),
                      pack_bf2(bflo(mrow.y) + u[2] * gr.z, bfhi(mrow.y) + u[3] * gr.w));
}
__device__ __forceinline__ void load_tail_weights(const Params& p, float* sw, int tid) {
    if (tid < 32) sw[tid] = __bfloat162float(p.w_sbf[tid]);
    else if (tid < 64) sw[tid] = __bfloat162float(p.w_rbf[tid - 32]);
    else if (tid < 80) sw[tid] = __bfloat162float(p.w_up[tid - 64]);
    else if (tid < 96) sw[tid] = __bfloat162float(p.w_down[tid - 80]);
}
__device__ __forceinline__ float exp_ftz(float x) {
    float r;
    asm("ex2.approx.ftz.f32 %0, %1;" : "=f"(r) : "f"(x * 1.4426950408889634f));
    return r;
}
__device__ __forceinline__ void tail_rows(const Params& p, int tidx, int w, int lane) {
    constexpr uint32_t sb = SB;
    if (w == NW - 1 && lane < 2) {
        fence_gpu();
        red_rlx(rdy_of(p, sb, 320, lane), 1u);
    }
    if (w >= NPC * WPP) return;
    const int pc = w / WPP, r0 = pc * RPC + (tidx * WPP + w - pc * WPP) * 8, e0 = r0 * 32;
    const uint32_t G = sb + T_G + w * TWB, M = G + 4096, D = M + 2048;
    cp16z(D + lane * 16, p.dist + e0 + lane * 8, min(max(p.E - e0 - lane * 8, 0), 8) * 2);
#pragma unroll
    for (int k = 0; k < 4; k++) cp16(M + (k * 32 + lane) * 16, p.m + e0 + (k * 32 + lane) * 2, e0 + (k * 32 + lane) * 2 < p.E);
    cp_commit();
    const Scale sc = get_scale(sb);
    const float lsb[4] = {__uint_as_float((sc.eb[0] - 10) << 23), __uint_as_float((sc.eb[1] - 10) << 23),
                          __uint_as_float((sc.eb[2] - 10) << 23), __uint_as_float((sc.eb[3] - 10) << 23)};
    {
        const int g = lane >> 2, t = lane & 3;
        const uint32_t c2 = ((const uint32_t*)p.centers)[t];
        const unsigned short* wg = (const unsigned short*)(g < 4 ? p.w_sbf : p.w_rbf) + t * 8 + (g & 3);
        const uint32_t b = wg[0] | (uint32_t)wg[4] << 16;
        cp_wait<0>();
        __syncwarp();
        TR(19, w == 0 && lane == 0 && b + c2 != 0x12345);
#pragma unroll 2
        for (int k = 0; k < 16; k++) {
            const uint32_t dv = lds32(D + (k * 8 + g) * 4);
            uint32_t a[2];
#pragma unroll
            for (int h = 0; h < 2; h++) {
                const uint32_t df = sub_bf2(prmt(dv, 0, h ? 0x3232 : 0x1010), c2);
                const uint32_t ar = mul_bf2(mul_bf2(df, df), 0xC120C120u);
                a[h] = pack_bf2(exp_ftz(bflo(ar)), exp_ftz(bfhi(ar)));
            }
            float d[4];
            asm("mma.sync.aligned.m16n8k8.row.col.f32.bf16.bf16.f32 {%0,%1,%2,%3}, {%4,%5}, {%6}, {%7,%7,%7,%7};"
                : "=f"(d[0]), "=f"(d[1]), "=f"(d[2]), "=f"(d[3]) : "r"(a[0]), "r"(a[1]), "r"(b), "f"(0.f));
            const uint32_t at = G + (k * 16 + g * 2) * 16 + t * 4;
            sts32(at, pack_bf2(d[0], d[1]));
            sts32(at + 16, pack_bf2(d[2], d[3]));
        }
    }
    __syncwarp();
    TR(2, w == 0 && lane == 0);
    float wu[16];
#pragma unroll
    for (int k = 0; k < 4; k++) *(uint4*)(wu + 4 * k) = lds128(sb + SM_W + 256 + 16 * k);
    uint32_t dirty = 0;
#pragma unroll 1
    for (int pass = CFG_DRY ? 0 : 1; pass < 2; pass++) {
        if (pass) {
            if (w == pc * WPP && lane < 2) spin_ge(rdy_of(p, sb, lane ? 320 : 160 + 32 * pc, lds32(sb + SM_MISC + 20)), lane ? NTAIL : N3);
            __syncwarp();
            bar_sync(1 + pc, WPP * 32);
            TR(3, w == 0 && lane == 0);
            TR(10, w == NPC * WPP - 1 && lane == 0);
            if (r0 >= (int)p.rows3) return;
        }
        uint4 sv[4] = {};
#pragma unroll
        for (int u = 0; u < 4; u++) ldq128_keep(sv[u], &g_S[0][u * 16 + (lane >> 1)][r0 + (lane & 1) * 4], pass);
        if (pass && lane < 8 && (r0 + lane) * 32 < p.E && (dirty = ld_rlx(g_dirty + r0 + lane))) st_rlx(g_dirty + r0 + lane, 0u);
        dirty = __ballot_sync(0xffffffffu, dirty != 0);
        uint32_t xs[8] = {sv[0].x, sv[0].y, sv[0].z, sv[0].w, sv[1].x, sv[1].y, sv[1].z, sv[1].w};
        uint32_t ys[8] = {sv[2].x, sv[2].y, sv[2].z, sv[2].w, sv[3].x, sv[3].y, sv[3].z, sv[3].w};
        asm volatile("" : "+r"(lane));
        auto finish = [&](int k, uint32_t x, uint32_t y, bool extra) {
            const int i = (lane & 1) * 128 + (lane >> 1) + (k & 3) * 32 + (k >> 2) * 16, e = e0 + i;
            float S[4];
            const uint32_t tx = x + 0x80008000u, ty = y + 0x80008000u;
            S[0] = (__uint_as_float(prmt(tx, 0x4b000000u, 0x7610)) - 8421376.0f) * lsb[0];
            S[1] = (__uint_as_float(prmt(tx, 0x4b000000u, 0x7632)) - 8421376.0f) * lsb[1];
            S[2] = (__uint_as_float(prmt(ty, 0x4b000000u, 0x7610)) - 8421376.0f) * lsb[2];
            S[3] = (__uint_as_float(prmt(ty, 0x4b000000u, 0x7632)) - 8421376.0f) * lsb[3];
            if (extra && e < p.E) {
                const float4 g = __ldcg(g_Sg + e);
                S[0] += g.x; S[1] += g.y; S[2] += g.z; S[3] += g.w;
                __stcg(g_Sg + e, make_float4(0.f, 0.f, 0.f, 0.f));
            }
            const uint4 g = lds128(G + i * 16);
            const uint2 o = finish_row(wu, make_float4(bflo(g.x), bfhi(g.x), bflo(g.y), bfhi(g.y)), make_float4(bflo(g.z), bfhi(g.z), bflo(g.w), bfhi(g.w)), S,
                                       lds64v(M + i * 8));
            asm volatile("{.reg .pred q; setp.ne.u32 q, %3, 0; @q st.global.v2.u32 [%0], {%1,%2};}"
                         ::"l"(p.out + e), "r"(o.x), "r"(o.y), "r"((uint32_t)(pass && e < p.E)));
        };
        if (!dirty) {
#pragma unroll
            for (int k = 0; k < 8; k++) finish(k, xs[k], ys[k], false);
        } else {
#pragma unroll 1
            for (int k = 0; k < 8; k++) {
                finish(k, xs[0], ys[0], dirty >> ((lane & 1) * 4 + (k & 3)) & 1);
#pragma unroll
                for (int j = 0; j < 7; j++) { xs[j] = xs[j + 1]; ys[j] = ys[j + 1]; }
            }
        }
    }
    TR(9, w == 0 && lane == 0);
    TR(11, w == NPC * WPP - 1 && lane == 0);
}

#define CFG_MAP1 1
__global__ void __launch_bounds__(NT, 1) k_main(const __grid_constant__ Params p) {
    extern __shared__ __align__(1024) unsigned char smem[];
    constexpr uint32_t sb = SB;
    if ((uint32_t)__cvta_generic_to_shared(smem) != SB) __trap();
    const int tid = threadIdx.x, w = __shfl_sync(0xffffffffu, tid >> 5, 0), lane = tid & 31;
    if (w < NPROBE) probe(p, sb, w, lane);
    else {
        if (tid == NT - 1) sts32(sb + SM_MISC + 16, ld_rlx(&g_epoch) & 1);
        if (tid >= NT - 32 && lane < 12) sts32(sb + SM_FIN + lane * 4, 0u);
        load_tail_weights(p, (float*)(smem + SM_W), tid - NPROBE * 32);
        const int k = blockIdx.x % (NCTA / 2) * 14 + lane;
        if (w == NW - 2 && lane < 14 && k < NT - 32) asm volatile("prefetch.global.L2 [%0];" ::"l"((const uint4*)p.m + k * (p.E / 2 / (NT - 32))));
    }
    cta_sync();
    if (w) {
        const uint4 in = __ldg((const uint4*)p.m + (tid - 32) * (p.E / 2 / (NT - 32)));
        const Mat4 wd = load_mat4(p.w_down, lane);
        for (int i = SM_DATA / 16 + tid - 32; i < ZEND / 16; i += NT - 32) ((uint4*)smem)[i] = make_uint4(0, 0, 0, 0);
        if (tid - 32 < 256) ((uint4*)(smem + SM_ZERO))[tid - 32] = make_uint4(0, 0, 0, 0);
        if (tid < 48) sts32(sb + SM_CNT2 + (tid - 32) * 4, NQ2 << 16);
        __syncwarp();
        if (CFG_PFD && tid == NT - 1) {
            __nanosleep(CFG_PFD);
            const uint32_t n = (p.E / 2 + NCTA - 1) / NCTA, o = blockIdx.x * n;
            if (o < (uint32_t)p.E / 2) asm volatile("cp.async.bulk.prefetch.L2.global [%0], %1;" ::"l"((const uint4*)p.m + o), "r"(min(n, p.E / 2 - o) * 16) : "memory");
        }
        __syncwarp();
        md_stats(in, wd, lane);
    } else assign_role(p, sb, lane);
    if (tid == 0) {
        mbar_init(sb + SM_DONE, lds32(sb + SM_MISC) >> 8 ? P2W : P1W);
        mbar_init(sb + SM_DONE2, NF);
    }
    cta_sync();
    const uint32_t rid = __shfl_sync(0xffffffffu, lds32(sb + SM_MISC), 0);
    const int role = rid >> 8, id = rid & 255;
    TR(5, tid == 0);
    if (role == 0) {
        const int ww = CFG_MAP1 == 0 ? ((w & 3) == 3 ? NW : (w >> 2) * 3 + (w & 3)) : CFG_MAP1 == 1 ? (w & 2 ? NW : (w >> 2) * 2 + (w & 1)) : w;
        const int sw = CFG_MAP1 == 0 ? ((w & 3) == 3 ? w >> 2 : NW) : CFG_MAP1 == 1 ? (w & 2 ? (w >> 2) * 2 + (w & 1) : NW) : w - P1W;
        static_assert(CFG_MAP1 == 0 ? (P1W <= NW / 4 * 3 && NF + 2 <= NW / 4) : CFG_MAP1 == 1 ? (P1W <= NW / 2 && NF + 2 <= NW / 2) : true, "warp map");
        for (int i = tid; i < NF * GPW * 32; i += NT) sts32(sb + A_CNT + i * 4, 1u << 24);
        if (tid < 64) sts32(sb + SM_CRED + tid * 4, 0u);
        cta_sync();
        TR(1, tid == 0);
        if (ww < P1W) role_p1(p, sb, id, ww, lane);
        else if (sw < NF) role_flush(p, sb, id, sw, lane);
        else if (sw == NF) role_credit1(p, sb, id, lane);
        else if (w == NW - 1) {
            uint4* owin = (uint4*)(p.ring + (CWIN + (lds32(sb + SM_MISC + 16) ^ 1)) * WIN);
            for (int i = id * 32 + lane; i < CPAIRS * 512; i += N1 * 32) __stcg(owin + i, make_uint4(0, 0, 0, 0));
            __syncwarp();
        }
    } else if (role == 1) {
        const int row0 = id % H2 * p.rows2;
        const int nrows = min((int)p.rows2, p.E - row0);
        constexpr int NTB = NT - 32, TBD = CFG_TBD;
        bool flagged = false;
        if (w < NW - 1) {
            const uint4* const src = (const uint4*)(p.m + row0);
            uint4 r2[TBD], nx[TBD];
            auto fetch = [&](int i) {
#pragma unroll
                for (int k = 0; k < TBD; k++)
                    asm volatile("ld.global.nc.v4.u32 {%0,%1,%2,%3}, [%4];" : "=r"(nx[k].x), "=r"(nx[k].y), "=r"(nx[k].z), "=r"(nx[k].w) : "l"(src + min(i + k * NTB, nrows / 2 - 1)));
            };
            fetch(tid);
            const Scale sc = get_scale(sb);
            const Mat4 wd = load_mat4(p.w_down, lane);
            Mat4 ws;
#pragma unroll
            for (int k = 0; k < 4; k++) ws.b[k] = mul_bf2(wd.b[k], ((246u - (lane & 4 ? sc.eb[(k & 2) + 1] : sc.eb[k & 2])) << 7) * 0x10001u);
#pragma unroll 1
            for (int i0 = tid; 2 * (i0 - lane) < nrows; i0 += TBD * NTB) {
#pragma unroll
                for (int k = 0; k < TBD; k++) r2[k] = make_uint4(nx[k].x, nx[k].z, nx[k].y, nx[k].w);
                fetch(i0 + TBD * NTB);
#pragma unroll
                for (int k = 0; k < TBD; k++) {
                    const int i = i0 + k * NTB;
                    float y[8];
                    mul4(make_uint4(r2[k].x, r2[k].z, r2[k].y, r2[k].w), ws, y);
                    uint32_t a[4], h[4], ta[2];
#pragma unroll
                    for (int j = 0; j < 4; j++) { a[j] = pack_h2(y[2 * j], y[2 * j + 1]); h[j] = a[j] + 0x00040004u; }
#pragma unroll
                    for (int j = 0; j < 2; j++) ta[j] = bitsel(h[2 * j], bitsel(h[2 * j + 1] >> 3, h[2 * j + 1] << 7, 0x00070007u), 0x9ff89ff8u);
                    uint32_t tb = prmt(h[1], h[3], 0x7531);
                    const uint32_t b0 = a[0] | a[1] | h[0] | h[1], b1 = a[2] | a[3] | h[2] | h[3];
                    if (__any_sync(0xffffffffu, ((b0 | b1) & 0x60006000u) || sc.allslow)) {
                        if ((b0 & 0x60006000u) || sc.allslow) { ta[0] = 0; tb = (tb & 0xffff0000u) | 0x40u; }
                        if ((b1 & 0x60006000u) || sc.allslow) { ta[1] = 0; tb = (tb & 0xffffu) | 0x400000u; }
                        flagged = true;
                    }
                    sts64_if(sb + B_TA + i * 8, ta[0], ta[1], 2 * i < nrows);
                    sts32_if(sb + B_TB + i * 4, tb, 2 * i < nrows);
                }
            }
            if (tid == 0) {
                sts32(sb + B_TA + p.rows2 * 4, 0u);
                sts16(sb + B_TB + p.rows2 * 2, 0u);
            }
            TR(8, tid == 0);
        } else if (lane == 0) spin_ge(rdy_of(p, sb, id, id / H2), H3);
        __syncwarp();
        flagged = __any_sync(0xffffffffu, __syncthreads_or(flagged));
        TR(1, tid == 0);
        if (w < P2W) {
            if (flagged) role_p2<true>(p, sb, id, w, lane);
            else role_p2<false>(p, sb, id, w, lane);
        } else if (w == P2W) role_credit(p, sb, id, lane);
    } else {
        if (w == 0) clear_queues<false>(p, sb, id, lane);
        if (tid >= 32 && tid < 33 + NPC) mbar_init(sb + SM_CNT2 + (tid - 32) * 8, 1);
        cta_sync();
        TR(1, tid == 0);
        if (w < P3W) role_p3(p, sb, id, w, lane);
        cta_sync();
        TR(2, tid == 0);
        if (w < NPC && lane == 0) {
            fence_async_smem();
            const int n = min(((int)p.rows3 + 7) / 8 * 8 - w * RPC, RPC);
            if (w >= CFG_DOUT) mbar_wait(sb + SM_CNT2 + (w + 1 - CFG_DOUT) * 8, 0);
            if (n > 0) {
                bulk_store(g_S[0][id] + w * RPC, sb + C_S + w * RPC * 4, n * 4);
                bulk_store(g_S[1][id] + w * RPC, sb + C_S + (ROWS3_MAX + w * RPC) * 4, n * 4);
            }
            asm volatile("cp.async.bulk.commit_group;" ::: "memory");
            asm volatile("cp.async.bulk.wait_group.read 0;" ::: "memory");
            mbar_arrive(sb + SM_CNT2 + w * 8 + 8);
            asm volatile("cp.async.bulk.wait_group 0;" ::: "memory");
            fence_gpu();
            red_rlx(rdy_of(p, sb, 160 + 32 * w, 0), 1u);
            red_rlx(rdy_of(p, sb, 160 + 32 * w, 1), 1u);
            if (id == 0 && w == 0) red_rlx(&g_epoch, 1u);
            TR(12 + w, true);
        }
        return;
    }
    cta_sync();
    TR(18, tid == 0 && role == 1);
    if (role == 0 && w == NW - 2) clear_queues<true>(p, sb, id, lane);
    tail_rows(p, role * N1 + id, w, lane);
}

__global__ void k_direct(const Params p, long long T) {
    float wd[16];
#pragma unroll
    for (int i = 0; i < 16; i++) wd[i] = __bfloat162float(p.w_down[i]);
    const float f = __bfloat162float(p.freq[0]);
    for (long long t = blockIdx.x * (long long)blockDim.x + threadIdx.x; t < T; t += (long long)gridDim.x * blockDim.x) {
        float x = __bfloat162float(__float2bfloat16(f * __bfloat162float(p.angle[t])));
        float c = __bfloat162float(__float2bfloat16(cosf(x)));
        uint2 md = down_row(__ldg(p.m + p.idx_in[t]), wd);
        red_v4(g_Sg + p.idx_out[t], c * bflo(md.x), c * bfhi(md.x), c * bflo(md.y), c * bfhi(md.y));
    }
}
__global__ void k_direct_tail(const Params p) {
    __shared__ __align__(16) float sw[96];
    load_tail_weights(p, sw, threadIdx.x);
    __syncthreads();
    uint32_t c2[4];
#pragma unroll
    for (int i = 0; i < 4; i++) c2[i] = ((const uint32_t*)p.centers)[i];
    for (int e = blockIdx.x * blockDim.x + threadIdx.x; e < p.E; e += gridDim.x * blockDim.x) {
        float4 g = __ldcg(g_Sg + e);
        __stcg(g_Sg + e, make_float4(0.f, 0.f, 0.f, 0.f));
        const float Sv[4] = {g.x, g.y, g.z, g.w};
        float4 gs, gr;
        row_gates(sw, c2, __bfloat16_as_ushort(p.dist[e]), gs, gr);
        p.out[e] = finish_row(sw + 64, gs, gr, Sv, __ldg(p.m + e));
    }
}

static bool pick_rows(int E, int n, int rows_max, int mult, uint32_t* rows, uint32_t* magic) {
    for (uint32_t r = (E + n - 1) / n; r <= (uint32_t)rows_max; r++) {
        if (r < 2 || r % mult) continue;
        uint64_t mg = ((1ull << 32) + r - 1) / r;
        uint64_t err = mg * r - (1ull << 32);
        if (err * (uint64_t)n < mg) { *rows = r; *magic = (uint32_t)mg; return true; }
    }
    return false;
}

}

extern "C" void kernel_launch(void* const* d_in, const int* in_sizes, int n_in, void* d_out, int out_size) {
    using namespace gs;
    (void)n_in; (void)out_size;
    Params p;
    p.m = (const uint2*)d_in[0];
    p.idx_in = (const int*)d_in[1];
    p.idx_out = (const int*)d_in[2];
    p.dist = (const __nv_bfloat16*)d_in[3];
    p.angle = (const __nv_bfloat16*)d_in[4];
    p.centers = (const __nv_bfloat16*)d_in[5];
    p.freq = (const __nv_bfloat16*)d_in[6];
    p.w_rbf = (const __nv_bfloat16*)d_in[7];
    p.w_sbf = (const __nv_bfloat16*)d_in[8];
    p.w_down = (const __nv_bfloat16*)d_in[9];
    p.w_up = (const __nv_bfloat16*)d_in[10];
    p.out = (uint2*)d_out;
    p.E = in_sizes[3];
    const long long T = in_sizes[1];
    p.n4 = (int)(T / 4);
    p.rows2 = p.magic2 = 0;
    p.ring = nullptr;

    static int sms = 0, rsv = 0;
    if (!sms) {
        int dev = 0;
        cudaGetDevice(&dev);
        cudaDeviceGetAttribute(&rsv, cudaDevAttrReservedSharedMemoryPerBlock, dev);
        cudaDeviceGetAttribute(&sms, cudaDevAttrMultiProcessorCount, dev);
        cudaFuncSetAttribute(k_main, cudaFuncAttributeMaxDynamicSharedMemorySize, SMEM_BYTES);
    }
    cudaStream_t st = cudaStreamPerThread;
    bool fast = (T % 4 == 0) && T > 0 && sms >= NCTA && rsv == (int)SB && p.E >= 65536 && p.E <= E_MAX &&
                p.E % 4 == 0 && (((uintptr_t)p.m | (uintptr_t)p.idx_in | (uintptr_t)p.idx_out | (uintptr_t)p.angle) & 15) == 0 &&
                pick_rows(p.E, NI, ROWS2_MAX, 2, &p.rows2, &p.magic2);
    p.nrows2 = 0u - p.rows2;
    p.rows3 = (p.E + 31) / 32;
    fast = fast && (p.rows2 * (NI - 1) + 2 <= (uint32_t)p.E);
    static const void* tkey[3] = {nullptr, nullptr, nullptr};
    static cudaTextureObject_t tex[3] = {0, 0, 0};
    static long long tlen = -1;
    const void* tptr[3] = {p.idx_in, p.idx_out, p.angle};
    for (int k = 0; fast && k < 3; k++) {
        if (tkey[k] == tptr[k] && tlen == T) continue;
        if (tkey[k]) cudaDestroyTextureObject(tex[k]);
        tkey[k] = nullptr;
        cudaResourceDesc rd = {};
        rd.resType = cudaResourceTypeLinear;
        rd.res.linear.devPtr = (void*)tptr[k];
        rd.res.linear.desc = cudaCreateChannelDesc(32, 32, k < 2 ? 32 : 0, k < 2 ? 32 : 0, cudaChannelFormatKindUnsigned);
        rd.res.linear.sizeInBytes = (size_t)T * (k < 2 ? 4 : 2);
        cudaTextureDesc td = {};
        td.readMode = cudaReadModeElementType;
        if (cudaCreateTextureObject(&tex[k], &rd, &td, nullptr) == cudaSuccess) tkey[k] = tptr[k];
        else { (void)cudaGetLastError(); fast = false; }
    }
    if (fast) tlen = T;
    p.t_in = tex[0]; p.t_out = tex[1]; p.t_ang = tex[2];
    if (fast) {
        void* ring = nullptr;
        cudaGetSymbolAddress(&ring, g_ring);
        uintptr_t a = ((uintptr_t)ring + WIN - 1) & ~(uintptr_t)(WIN - 1);
        if (a >> 32 != (a + RING_BYTES - 1) >> 32) a += RING_BYTES;
        p.ring = (unsigned char*)a;
        p.ring_lo = (uint32_t)a;
        p.ring_hi = (uint32_t)(a >> 32);
        k_main<<<NCTA, NT, SMEM_BYTES, st>>>(p);
    } else {
        k_direct<<<sms * 8, 256, 0, st>>>(p, T);
        k_direct_tail<<<sms * 4, 256, 0, st>>>(p);
    }
}
```

```cpp
#include <cuda_runtime.h>
#include <cuda_bf16.h>
#include <stdint.h>

#define CFG_N1 56
#define CFG_NI 22
#define CFG_NW 28
#define CFG_P1W 14
#define CFG_GPW 2
#define CFG_KR 1
#define CFG_QPW 3
#define CFG_TG 2
#define CFG_PMASK 8
#define CFG_PSTREAK 1
#define CFG_NBT 1
#define CFG_KM 5
#define CFG_KN 9
#define CFG_TBD 4
#define CFG_P0 500
#define CFG_PFD 200
#define CFG_C1SLEEP 200
#define CFG_PK1 6
#define CFG_PK2 8
#define CFG_PK3 11
#define CFG_CLN 8
#define CFG_CLS 500
#define CFG_DOUT 2
#define CFG_TH 14
#define CFG_TS 200
#define CFG_POLL 64
#define CFG_HINT 20000
#define CFG_BSLEEP 100
#define CFG_CSLEEP 200
#define CFG_FSLEEP 100
#define CFG_PSLEEP 100
#define CFG_DRY 1
#define CFG_PROBES 4

namespace gs {

constexpr int E_MAX = 640000;
constexpr int N1 = CFG_N1, NI = CFG_NI, N2 = 2 * NI, N3 = 32, NCTA = N1 + N2 + N3;
constexpr int H2 = NI, H3 = N3 / 2;
constexpr int NB = NI * N3;
constexpr int NW = CFG_NW, NT = NW * 32;
constexpr int GPW = CFG_GPW, NF = (NI + GPW - 1) / GPW;
constexpr int QPW = CFG_QPW, NBT = CFG_NBT;
constexpr int P1W = CFG_P1W, P2W = (N1 + QPW - 1) / QPW, P3W = NI;
constexpr int NQ2 = 64;
constexpr int ROWS2_MAX = ((E_MAX + NI - 1) / NI + 31) / 8 * 8;
constexpr int ROWS3_MAX = (E_MAX / 32 + 31) / 32 * 32;
constexpr int NTAIL = N1 + N2;
constexpr int NPC = 5, WPP = 5, RPC = NTAIL * WPP * 8;
constexpr int GUARD = 1 << 26;
static_assert(NCTA % 4 == 0 && NCTA <= 192, "roles come in CTA pairs, per partition");
static_assert((GPW == 2 || GPW == 4) && QPW >= NBT && QPW <= 4 && NI <= 32 && N1 <= 62, "queue ownership");
static_assert(P1W + NF + 2 <= NW && P2W + 2 <= NW && P3W + 5 <= NW && P1W * 256 + 64 < 8192, "warp roles");
static_assert(ROWS2_MAX + 8 <= 32768 && ROWS3_MAX <= 32768, "index bits");

constexpr uint32_t SB = 1024;
constexpr int SM_DONE = 0, SM_DONE2 = 8;
constexpr int SM_MISC = 16;
constexpr int SM_FIN = 48;
constexpr int SM_STAT = 64;
constexpr int SM_CNT2 = 128;
constexpr int SM_W = 256;
constexpr int SM_PUB = SM_W + 384;
constexpr int SM_PROBE = SM_PUB + 768;
constexpr int SM_CRED = 1792;
constexpr int SM_DATA = 2048;
constexpr int cmax(int a, int b) { return a > b ? a : b; }
constexpr int A_CNT = SM_DATA;
constexpr int KR = CFG_KR, LISTB = (GPW * 32 + 8 * KR) * 4;
constexpr int A_LIST = A_CNT + NF * GPW * 128;
constexpr int A_ST = (A_LIST + NF * LISTB + 127) / 128 * 128;
constexpr int A_END = A_ST + NB * 256;
constexpr int B_TB = SM_DATA;
constexpr int B_TA = SM_DATA + (ROWS2_MAX + 8) * 2;
constexpr int B_END = SM_DATA + (ROWS2_MAX + 8) * 6;
constexpr int C_S = SM_DATA;
constexpr int C_END = C_S + ROWS3_MAX * 8;
constexpr int T_G = SM_DATA, TWB = 4096 + 2048 + 512, T_END = T_G + NPC * WPP * TWB;
constexpr int ZEND = cmax(A_END, C_END);
constexpr int SM_ZERO = (cmax(C_END, T_END) + 127) / 128 * 128;
constexpr int SMEM_BYTES = cmax(cmax(A_END, B_END), SM_ZERO + 4096);
static_assert(SMEM_BYTES <= 232448 && SM_PROBE + 128 <= SM_CRED, "shared memory");
static_assert(NPC * RPC >= ROWS3_MAX && NPC * WPP + 2 <= NW, "tail");

constexpr uint32_t FIN = 0x80000000u;

constexpr uint32_t WIN = 524288;
constexpr int CWIN = N2 + N3, NWIN = CWIN + 2, CPAIRS = 31;
constexpr uint32_t PROBE_OFF = (uint32_t)NWIN * WIN;
constexpr int NPROBE = 16;
static_assert(NWIN <= NCTA && NPROBE <= NW, "windows");
constexpr size_t RING_BYTES = (size_t)PROBE_OFF + WIN;
__device__ __align__(128) unsigned char g_ring[2 * RING_BYTES + WIN];
__device__ __align__(128) uint32_t g_S[2][32][ROWS3_MAX];
__device__ __align__(128) float4 g_Sg[E_MAX];
__device__ uint32_t g_dirty[E_MAX / 32];
__device__ uint32_t g_epoch;

#define TR(ev, on)
#define ACC_DECL
#define ACC(i, n)
#define ACC_SAVE

struct Params {
    const uint2* m;
    const int* idx_in;
    const int* idx_out;
    const __nv_bfloat16* dist;
    const __nv_bfloat16* angle;
    const __nv_bfloat16* centers;
    const __nv_bfloat16* freq;
    const __nv_bfloat16* w_rbf;
    const __nv_bfloat16* w_sbf;
    const __nv_bfloat16* w_down;
    const __nv_bfloat16* w_up;
    uint2* out;
    unsigned char* ring;
    cudaTextureObject_t t_in, t_out, t_ang;
    int E, n4;
    uint32_t rows2, nrows2, magic2, rows3;
    uint32_t ring_lo, ring_hi;
};

__device__ __forceinline__ float bflo(uint32_t w) { return __uint_as_float(w << 16); }
__device__ __forceinline__ float bfhi(uint32_t w) { return __uint_as_float(w & 0xffff0000u); }
__device__ __forceinline__ uint32_t pack_bf2(float lo, float hi) {
    uint32_t r;
    asm("cvt.rn.bf16x2.f32 %0, %1, %2;" : "=r"(r) : "f"(hi), "f"(lo));
    return r;
}
__device__ __forceinline__ uint32_t mul_bf2(uint32_t a, uint32_t b) {
    uint32_t r;
    asm("mul.rn.bf16x2 %0, %1, %2;" : "=r"(r) : "r"(a), "r"(b));
    return r;
}
__device__ __forceinline__ uint32_t sub_bf2(uint32_t a, uint32_t b) {
    uint32_t r;
    asm("sub.rn.bf16x2 %0, %1, %2;" : "=r"(r) : "r"(a), "r"(b));
    return r;
}
__device__ __forceinline__ uint32_t maxabs_bf2(uint32_t a, uint32_t b) {
    uint32_t r;
    asm("max.NaN.xorsign.abs.bf16x2 %0, %1, %2;" : "=r"(r) : "r"(a), "r"(b));
    return r;
}
__device__ __forceinline__ void mbar_init(uint32_t a, uint32_t n) {
    asm volatile("mbarrier.init.shared::cta.b64 [%0], %1;" ::"r"(a), "r"(n) : "memory");
}
__device__ __forceinline__ void mbar_arrive(uint32_t a) {
    asm volatile("mbarrier.arrive.shared::cta.b64 _, [%0];" ::"r"(a) : "memory");
}
__device__ __forceinline__ void mbar_arrive_if(uint32_t a, bool on) {
    asm volatile("{.reg .pred q; setp.ne.u32 q, %1, 0; @q mbarrier.arrive.shared::cta.b64 _, [%0];}" ::"r"(a), "r"((uint32_t)on) : "memory");
}
__device__ __forceinline__ void mbar_wait(uint32_t a, uint32_t parity) {
    uint32_t ok;
    int guard = 0;
    do {
        asm volatile("{.reg .pred p; mbarrier.try_wait.parity.shared::cta.b64 p, [%1], %2, %3; selp.u32 %0, 1, 0, p;}"
                     : "=r"(ok) : "r"(a), "r"(parity), "r"(CFG_HINT) : "memory");
        if (!ok) {
            if (++guard > GUARD) __trap();
        }
    } while (!ok);
}
__device__ __forceinline__ void cta_sync() { __syncwarp(); __syncthreads(); }
__device__ __forceinline__ void bar_sync(int id, int n) { asm volatile("bar.sync %0, %1;" ::"r"(id), "r"(n) : "memory"); }
__device__ __forceinline__ bool mbar_test(uint32_t a, uint32_t parity) {
    uint32_t ok;
    asm volatile("{.reg .pred p; mbarrier.test_wait.parity.shared::cta.b64 p, [%1], %2; selp.u32 %0, 1, 0, p;}"
                 : "=r"(ok) : "r"(a), "r"(parity) : "memory");
    return ok;
}
__device__ __forceinline__ uint32_t ld_acq(const uint32_t* p) {
    uint32_t v;
    asm volatile("ld.acquire.gpu.global.u32 %0, [%1];" : "=r"(v) : "l"(p) : "memory");
    return v;
}
__device__ __forceinline__ uint32_t ld_rlx(const uint32_t* p) {
    uint32_t v;
    asm volatile("ld.relaxed.gpu.global.u32 %0, [%1];" : "=r"(v) : "l"(p) : "memory");
    return v;
}
__device__ __forceinline__ void st_rlx(uint32_t* p, uint32_t v) {
    asm volatile("st.relaxed.gpu.global.u32 [%0], %1;" ::"l"(p), "r"(v) : "memory");
}
__device__ __forceinline__ void red_rlx(uint32_t* p, uint32_t v) {
    asm volatile("red.relaxed.gpu.global.add.u32 [%0], %1;" ::"l"(p), "r"(v) : "memory");
}
__device__ __forceinline__ uint32_t spin_ge(const uint32_t* p, uint32_t target) {
    int guard = 0;
    while (ld_rlx(p) < target) {
        __nanosleep(CFG_POLL);
        if (++guard > GUARD) __trap();
    }
    return ld_acq(p);
}
__device__ __forceinline__ void fence_gpu() { asm volatile("fence.acq_rel.gpu;" ::: "memory"); }
__device__ __forceinline__ void fence_async_smem() { asm volatile("fence.proxy.async.shared::cta;" ::: "memory"); }
__device__ __forceinline__ void fence_async_all() { asm volatile("fence.proxy.async;" ::: "memory"); }
__device__ __forceinline__ void bulk_store(void* g, uint32_t s, uint32_t bytes) {
    asm volatile("cp.async.bulk.global.shared::cta.bulk_group [%0], [%1], %2;" ::"l"(g), "r"(s), "r"(bytes) : "memory");
}
__device__ __forceinline__ void cp16(uint32_t s, const void* g, bool on) {
    asm volatile("{.reg .pred q; setp.ne.u32 q, %2, 0; @q cp.async.cg.shared.global [%0], [%1], 16;}" ::"r"(s), "l"(g), "r"((uint32_t)on) : "memory");
}
__device__ __forceinline__ void cp16z(uint32_t s, const void* g, int bytes) {
    asm volatile("cp.async.cg.shared.global [%0], [%1], 16, %2;" ::"r"(s), "l"(g), "r"(bytes) : "memory");
}
__device__ __forceinline__ void cp_commit() { asm volatile("cp.async.commit_group;" ::: "memory"); }
template <int N> __device__ __forceinline__ void cp_wait() { asm volatile("cp.async.wait_group %0;" ::"n"(N) : "memory"); }
__device__ __forceinline__ uint32_t atoms_add(uint32_t a, uint32_t v) {
    uint32_t o;
    asm volatile("atom.shared.add.u32 %0, [%1], %2;" : "=r"(o) : "r"(a), "r"(v) : "memory");
    return o;
}
__device__ __forceinline__ void sts32(uint32_t a, uint32_t v) { asm volatile("st.shared.u32 [%0], %1;" ::"r"(a), "r"(v) : "memory"); }
__device__ __forceinline__ void sts16(uint32_t a, uint32_t v) { asm volatile("st.shared.u16 [%0], %1;" ::"r"(a), "h"((uint16_t)v) : "memory"); }
__device__ __forceinline__ void sts64(uint32_t a, uint32_t x, uint32_t y) { asm volatile("st.shared.v2.u32 [%0], {%1,%2};" ::"r"(a), "r"(x), "r"(y) : "memory"); }
__device__ __forceinline__ uint32_t lds32(uint32_t a) {
    uint32_t v;
    asm volatile("ld.shared.u32 %0, [%1];" : "=r"(v) : "r"(a) : "memory");
    return v;
}
__device__ __forceinline__ uint2 lds64v(uint32_t a) {
    uint2 v;
    asm volatile("ld.volatile.shared.v2.u32 {%0,%1}, [%2];" : "=r"(v.x), "=r"(v.y) : "r"(a) : "memory");
    return v;
}
__device__ __forceinline__ uint32_t lds32v(uint32_t a) {
    uint32_t v;
    asm volatile("ld.volatile.shared.u32 %0, [%1];" : "=r"(v) : "r"(a) : "memory");
    return v;
}
__device__ __forceinline__ uint4 lds128(uint32_t a) {
    uint4 v;
    asm volatile("ld.shared.v4.u32 {%0,%1,%2,%3}, [%4];" : "=r"(v.x), "=r"(v.y), "=r"(v.z), "=r"(v.w) : "r"(a) : "memory");
    return v;
}
__device__ __forceinline__ void sts128(uint32_t a, uint4 v) {
    asm volatile("st.shared.v4.u32 [%0], {%1,%2,%3,%4};" ::"r"(a), "r"(v.x), "r"(v.y), "r"(v.z), "r"(v.w) : "memory");
}
#define LD_Q "ld.relaxed.gpu.global"
__device__ __forceinline__ uint4 ldg_q128(const void* p) {
    uint4 v;
    asm volatile(LD_Q ".v4.u32 {%0,%1,%2,%3}, [%4];"
                 : "=r"(v.x), "=r"(v.y), "=r"(v.z), "=r"(v.w) : "l"(p) : "memory");
    return v;
}
__device__ __forceinline__ uint2 ldg_q64(const void* p) {
    uint2 v;
    asm volatile(LD_Q ".v2.u32 {%0,%1}, [%2];" : "=r"(v.x), "=r"(v.y) : "l"(p) : "memory");
    return v;
}
__device__ __forceinline__ void red_v4(float4* p, float a, float b, float c, float d) {
    asm volatile("red.global.add.v4.f32 [%0], {%1,%2,%3,%4};" ::"l"(p), "f"(a), "f"(b), "f"(c), "f"(d) : "memory");
}
__device__ __forceinline__ uint2 down_row(uint2 r, const float* wd) {
    float x0 = bflo(r.x), x1 = bfhi(r.x), x2 = bflo(r.y), x3 = bfhi(r.y);
    float y[4];
#pragma unroll
    for (int j = 0; j < 4; j++) y[j] = x0 * wd[j] + x1 * wd[4 + j] + x2 * wd[8 + j] + x3 * wd[12 + j];
    return make_uint2(pack_bf2(y[0], y[1]), pack_bf2(y[2], y[3]));
}
__device__ __forceinline__ uint32_t prmt(uint32_t a, uint32_t b, uint32_t s) {
    uint32_t r;
    asm("prmt.b32 %0, %1, %2, %3;" : "=r"(r) : "r"(a), "r"(b), "r"(s));
    return r;
}
__device__ __forceinline__ uint32_t bitsel(uint32_t a, uint32_t b, uint32_t m) {
    uint32_t r;
    asm("lop3.b32 %0, %1, %2, %3, 0xE4;" : "=r"(r) : "r"(a), "r"(b), "r"(m));
    return r;
}
__device__ __forceinline__ uint32_t pack_h2(float lo, float hi) {
    uint32_t r;
    asm("cvt.rn.f16x2.f32 %0, %1, %2;" : "=r"(r) : "f"(hi), "f"(lo));
    return r;
}
__device__ __forceinline__ uint32_t mul_h2(uint32_t a, uint32_t b) {
    uint32_t r;
    asm("mul.rn.f16x2 %0, %1, %2;" : "=r"(r) : "r"(a), "r"(b));
    return r;
}
__device__ __forceinline__ uint32_t lds32nv(uint32_t a) {
    uint32_t v;
    asm volatile("ld.shared.u32 %0, [%1];" : "=r"(v) : "r"(a));
    return v;
}
__device__ __forceinline__ uint32_t lds16nv(uint32_t a) {
    uint32_t v;
    asm volatile("ld.shared.u16 %0, [%1];" : "=r"(v) : "r"(a));
    return v;
}
#define ST_Q "st.relaxed.gpu.global"
__device__ __forceinline__ void stg_q128(void* p, uint32_t a, uint32_t b, uint32_t c, uint32_t d, bool on) {
    asm volatile("{.reg .pred q; setp.ne.u32 q, %5, 0; @q " ST_Q ".v4.u32 [%0], {%1,%2,%3,%4};}"
                 ::"l"(p), "r"(a), "r"(b), "r"(c), "r"(d), "r"((uint32_t)on) : "memory");
}
__device__ __forceinline__ void stg_q64(void* p, uint32_t a, uint32_t b, bool on) {
    asm volatile("{.reg .pred q; setp.ne.u32 q, %3, 0; @q " ST_Q ".v2.u32 [%0], {%1,%2};}"
                 ::"l"(p), "r"(a), "r"(b), "r"((uint32_t)on) : "memory");
}
__device__ __forceinline__ void st_rlx_if(uint32_t* p, uint32_t v, bool on) {
    asm volatile("{.reg .pred q; setp.ne.u32 q, %2, 0; @q st.relaxed.gpu.global.u32 [%0], %1;}" ::"l"(p), "r"(v), "r"((uint32_t)on) : "memory");
}
__device__ __forceinline__ void ldq128_keep(uint4& v, const void* p, bool on) {
    asm volatile("{.reg .pred q; setp.ne.u32 q, %5, 0; @q ld.relaxed.gpu.global.v4.u32 {%0,%1,%2,%3}, [%4];}"
                 : "+r"(v.x), "+r"(v.y), "+r"(v.z), "+r"(v.w) : "l"(p), "r"((uint32_t)on) : "memory");
}
__device__ __forceinline__ void atoms_add_keep(uint32_t& o, uint32_t a, uint32_t v, bool on) {
    asm volatile("{.reg .pred q; setp.ne.u32 q, %3, 0; @q atom.shared.add.u32 %0, [%1], %2;}" : "+r"(o) : "r"(a), "r"(v), "r"((uint32_t)on) : "memory");
}
__device__ __forceinline__ void reds_add(uint32_t a, uint32_t v) { asm volatile("red.shared.add.u32 [%0], %1;" ::"r"(a), "r"(v) : "memory"); }
__device__ __forceinline__ void sts32_if(uint32_t a, uint32_t v, bool on) {
    asm volatile("{.reg .pred q; setp.ne.u32 q, %2, 0; @q st.shared.u32 [%0], %1;}" ::"r"(a), "r"(v), "r"((uint32_t)on) : "memory");
}
__device__ __forceinline__ void sts64_if(uint32_t a, uint32_t x, uint32_t y, bool on) {
    asm volatile("{.reg .pred q; setp.ne.u32 q, %3, 0; @q st.shared.v2.u32 [%0], {%1,%2};}" ::"r"(a), "r"(x), "r"(y), "r"((uint32_t)on) : "memory");
}
__device__ __forceinline__ void lds128_keep(uint4& v, uint32_t a, bool on) {
    asm volatile("{.reg .pred q; setp.ne.u32 q, %5, 0; @q ld.volatile.shared.v4.u32 {%0,%1,%2,%3}, [%4];}"
                 : "+r"(v.x), "+r"(v.y), "+r"(v.z), "+r"(v.w) : "r"(a), "r"((uint32_t)on) : "memory");
}
__device__ __forceinline__ void or3_if(uint32_t& x, uint32_t a, uint32_t b, bool on) {
    asm("{.reg .pred q; setp.ne.u32 q, %3, 0; @q lop3.b32 %0, %0, %1, %2, 0xfe;}" : "+r"(x) : "r"(a), "r"(b), "r"((uint32_t)on));
}
__device__ __forceinline__ uint32_t clk() {
    uint32_t t;
    asm volatile("mov.u32 %0, %%clock;" : "=r"(t) :: "memory");
    return t;
}
__device__ __forceinline__ void sg_add(int row, float a, float b, float c, float d) {
    red_v4(g_Sg + row, a, b, c, d);
    st_rlx(g_dirty + (row >> 5), 1u);
}
__device__ __forceinline__ void slow_add(const uint2* m, uint32_t sb, int in, int out, float c) {
    const uint2 r = __ldg(m + in);
    const float x[4] = {bflo(r.x), bfhi(r.x), bflo(r.y), bfhi(r.y)};
    float y[4] = {0.f, 0.f, 0.f, 0.f};
#pragma unroll
    for (int k = 0; k < 4; k++) {
        const uint4 q = lds128(sb + SM_W + 320 + k * 16);
        y[0] = k ? y[0] + x[k] * __uint_as_float(q.x) : x[k] * __uint_as_float(q.x);
        y[1] = k ? y[1] + x[k] * __uint_as_float(q.y) : x[k] * __uint_as_float(q.y);
        y[2] = k ? y[2] + x[k] * __uint_as_float(q.z) : x[k] * __uint_as_float(q.z);
        y[3] = k ? y[3] + x[k] * __uint_as_float(q.w) : x[k] * __uint_as_float(q.w);
    }
    const uint32_t lo = pack_bf2(y[0], y[1]), hi = pack_bf2(y[2], y[3]);
    sg_add(out, c * bflo(lo), c * bfhi(lo), c * bflo(hi), c * bfhi(hi));
}

struct Mat4 { uint32_t b[4]; };
__device__ __forceinline__ Mat4 load_mat4(const __nv_bfloat16* w, int lane) {
    const unsigned short* u = (const unsigned short*)w + (lane >> 2 & 1);
    const bool on = lane >> 3 == (lane & 3);
    Mat4 m;
#pragma unroll
    for (int k = 0; k < 4; k++) m.b[k] = on ? u[(k & 1) * 8 + (k & 2)] | (uint32_t)u[(k & 1) * 8 + 4 + (k & 2)] << 16 : 0u;
    return m;
}
__device__ __forceinline__ void mul4(const uint4& x, const Mat4& m, float (&y)[8]) {
    asm("mma.sync.aligned.m16n8k16.row.col.f32.bf16.bf16.f32 {%0,%1,%2,%3}, {%8,%9,%10,%11}, {%12,%13}, {%16,%16,%16,%16};\n\t"
        "mma.sync.aligned.m16n8k16.row.col.f32.bf16.bf16.f32 {%4,%5,%6,%7}, {%8,%9,%10,%11}, {%14,%15}, {%16,%16,%16,%16};"
        : "=&f"(y[0]), "=&f"(y[1]), "=&f"(y[4]), "=&f"(y[5]), "=&f"(y[2]), "=&f"(y[3]), "=&f"(y[6]), "=&f"(y[7])
        : "r"(x.x), "r"(x.z), "r"(x.y), "r"(x.w), "r"(m.b[0]), "r"(m.b[1]), "r"(m.b[2]), "r"(m.b[3]), "f"(0.f));
}

struct Scale { uint32_t eb[4]; bool allslow; };
__device__ __forceinline__ void md_stats(const uint4& in, const Mat4& wd, int lane) {
    float y[8];
    mul4(in, wd, y);
    uint32_t mx[4], se[4];
#pragma unroll
    for (int c = 0; c < 4; c++) {
        uint32_t a = __float_as_uint(y[c]) & 0x7fffffffu, b = __float_as_uint(y[4 + c]) & 0x7fffffffu;
        if (a >= 0x7f800000u) a = 0;
        if (b >= 0x7f800000u) b = 0;
        mx[c] = __reduce_max_sync(0xffffffffu, max(a, b));
        se[c] = __reduce_add_sync(0xffffffffu, (a >> 23) + (b >> 23) + (a ? 1u << 20 : 0u) + (b ? 1u << 20 : 0u));
    }
    if (lane < 4) {
        asm volatile("red.shared.max.u32 [%0], %1;" ::"r"(SB + SM_STAT + lane * 4), "r"(lane == 0 ? mx[0] : lane == 1 ? mx[1] : lane == 2 ? mx[2] : mx[3]) : "memory");
        reds_add(SB + SM_STAT + 16 + lane * 4, lane == 0 ? se[0] : lane == 1 ? se[1] : lane == 2 ? se[2] : se[3]);
    }
}
__device__ __forceinline__ Scale get_scale(uint32_t sb) {
    Scale s;
    s.allslow = false;
#pragma unroll
    for (int k = 0; k < 4; k++) {
        const uint32_t mx = lds32(sb + SM_STAT + 4 * k), se = lds32(sb + SM_STAT + 16 + 4 * k);
        const uint32_t mean = (uint32_t)__fdividef((float)(se & 0xfffffu), (float)max(se >> 20, 1u));
        uint32_t eb = min(min((mx + 0x6e0000u) >> 23, mean + 5u), 227u);
        if (eb < 27u) { s.allslow = s.allslow || mx != 0; eb = 27u; }
        if (eb > 170u) s.allslow = true;
        s.eb[k] = eb;
    }
    return s;
}

__device__ __forceinline__ uint32_t probe_rt(uint32_t* p) {
    uint32_t best = 0xffffffffu;
#pragma unroll 1
    for (int r = 0; r < CFG_PROBES; r++) {
        const uint32_t t0 = clock();
        uint32_t v;
        asm volatile("atom.relaxed.gpu.global.add.u32 %0, [%1], 1;" : "=r"(v) : "l"(p) : "memory");
        if (v > 100000u) __trap();
        const uint32_t t1 = clock();
        best = min(best, t1 - t0);
    }
    return best;
}
__device__ __forceinline__ uint32_t* pub_ptr(const Params& p, int blk, uint32_t sel) {
    const int pr = blk / 44;
    return (uint32_t*)(p.ring + PROBE_OFF + (pr ? 4096u << pr : 0u) + (sel << 12) + 2176 + (blk - pr * 44) * 32);
}
__device__ __forceinline__ void probe(const Params& p, uint32_t sb, int w, int lane) {
    const int blk = blockIdx.x, pr = w >> 1;
    uint32_t off = PROBE_OFF + blk * 16 + (pr ? 4096u << pr : 0u);
    if (pr == 7) off = blk < NWIN ? blk * WIN + 4064 : PROBE_OFF + 3584 + blk % 16 * 32;
    off += (w & 1) * 4096;
    if (lane < 8) st_rlx((uint32_t*)(p.ring + (off & ~31u)) + lane, 0u);
    if (lane == 0) sts32(sb + SM_PROBE + w * 4, probe_rt((uint32_t*)(p.ring + off)));
}
__device__ __forceinline__ void assign_role(const Params& p, uint32_t sb, int lane) {
    {
        const bool x = lane < 8 && lds32(sb + SM_PROBE + lane * 8 + 4) < lds32(sb + SM_PROBE + lane * 8);
        const uint32_t near = __ballot_sync(0xffffffffu, x), bits = near & 1 ? ~near | 1u : near;
        const uint32_t tag = (lds32(sb + SM_MISC + 16) + 1) << 30;
        if (lane < 16) st_rlx(pub_ptr(p, blockIdx.x, lane >> 3) + (lane & 7), tag | (bits & 0xffu));
        constexpr int K = (NCTA + 31) / 32;
        __nanosleep(CFG_P0);
        uint32_t v[K], bad;
        int guard = 0;
        do {
            bad = 0;
#pragma unroll
            for (int k = 0; k < K; k++) {
                const int b = min(lane + 32 * k, NCTA - 1);
                v[k] = ld_rlx(pub_ptr(p, b, near >> (b / 44) & 1));
                bad |= v[k] ^ tag;
            }
            bad = __any_sync(0xffffffffu, bad >> 30);
            if (bad) __nanosleep(CFG_PSLEEP);
            if (++guard > GUARD) __trap();
        } while (bad);
#pragma unroll
        for (int k = 0; k < K; k++) sts32(sb + SM_PUB + (lane + 32 * k) * 4, v[k]);
    }
    __syncwarp();
    constexpr int NP = NCTA / 2, NTAB = H2 + H3;
    const int me = blockIdx.x >> 1, odd = blockIdx.x & 1;
    uint32_t pp[3], key[3];
    int n1 = 0;
#pragma unroll
    for (int k = 0; k < 3; k++) {
        const int i = lane + 32 * k;
        pp[k] = lds32(sb + SM_PUB + min(i, NP - 1) * 8) & 1;
        key[k] = (i * CFG_KM % CFG_KN) << 8 | i;
        n1 += 2 * __popc(__ballot_sync(0xffffffffu, i < NP && pp[k]));
    }
    bool fixed = n1 < NTAB || NCTA - n1 < NTAB;
    if (fixed) {
        n1 = NP / 2 * 2;
        pp[0] = pp[1] = pp[2] = lane & 1;
    }
    const uint32_t mine = __shfl_sync(0xffffffffu, (me < 32 ? key[0] : me < 64 ? key[1] : key[2]) * 2 + (me < 32 ? pp[0] : me < 64 ? pp[1] : pp[2]), me & 31);
    const int part = mine & 1;
    int pos = odd;
#pragma unroll
    for (int k = 0; k < 3; k++) pos += 2 * __popc(__ballot_sync(0xffffffffu, lane + 32 * k < NP && pp[k] == (uint32_t)part && key[k] < mine / 2));
    const int role = pos < H2 ? 1 : pos < NTAB ? 2 : 0;
    const int id = pos < H2 ? part * H2 + pos : pos < NTAB ? part * H3 + pos - H2 : (part ? NCTA - n1 - NTAB : 0) + pos - NTAB;
    const uint32_t v = lds32(sb + SM_PUB + lane * 4);
    uint32_t lin = 0;
#pragma unroll
    for (int b = 0; b < 6; b++) lin |= (__popc(__ballot_sync(0xffffffffu, (v >> (b + 1)) & 1)) > 16 ? 1u : 0u) << b;
    if (lane == 0) {
        sts32(sb + SM_MISC, role << 8 | id);
        sts32(sb + SM_MISC + 4, lin);
        sts32(sb + SM_MISC + 8, NCTA - n1 - NTAB);
        sts32(sb + SM_MISC + 20, part);
        sts32(sb + SM_MISC + 12, role == 0 ? id : role == 1 ? N1 + id : N1 + N2 + id);
    }
}
__device__ __forceinline__ uint32_t sel_of(uint32_t sb, int widx, uint32_t k, int part) {
    return (__popc(k & lds32(sb + SM_MISC + 4)) ^ (lds32(sb + SM_PUB + widx * 4) >> 7) ^ part) & 1;
}
__device__ __forceinline__ uint32_t gran_off(uint32_t sb, int widx, int k, int part) { return (2 * k + sel_of(sb, widx, k, part)) << 12; }
__device__ __forceinline__ uint32_t q1a_off(uint32_t sb, int src, int blk, int part) { return gran_off(sb, 2 * blk + part, src >> 1, part) + (src & 1) * 2048; }
__device__ __forceinline__ uint32_t q1h_off(uint32_t sb, int src, int blk, int part) { return gran_off(sb, 2 * blk + part, 32 + (src >> 2), part) + (src & 3) * 1024; }
__device__ __forceinline__ uint32_t* ctl_word(const Params& p, uint32_t sb, int k, int word, int part) {
    const int widx = CWIN + lds32(sb + SM_MISC + 16);
    return (uint32_t*)(p.ring + (widx * WIN + ((2 * k + sel_of(sb, widx, k, part)) << 12))) + word;
}
__device__ __forceinline__ uint32_t* cred1_of(const Params& p, uint32_t sb, int src) { return ctl_word(p, sb, src >> 3, (src & 7) * 128, src >= (int)lds32(sb + SM_MISC + 8)); }
__device__ __forceinline__ uint32_t* fin1_of(const Params& p, uint32_t sb, int dst) { return ctl_word(p, sb, 8 + (dst >> 3), (dst & 7) * 128, dst / H2); }
__device__ __forceinline__ uint32_t* cred2_of(const Params& p, uint32_t sb, int src) { return ctl_word(p, sb, 16 + (src >> 3), (src & 7) * 128, src / H2); }
__device__ __forceinline__ uint32_t* fin2_of(const Params& p, uint32_t sb, int dst) { return ctl_word(p, sb, 24 + (dst >> 3), (dst & 7) * 128, dst / H3); }
__device__ __forceinline__ uint32_t* rdy_of(const Params& p, uint32_t sb, int word, int part) { return ctl_word(p, sb, 28, word, part); }
__device__ __forceinline__ uint32_t q2_off(uint32_t sb, int blk, int dst) {
    return (N2 + dst) * WIN + gran_off(sb, N2 + dst, (blk >> 1) * 4 + (blk & 1), dst / H3);
}
template <bool IS1>
__device__ __forceinline__ void clear_queues(const Params& p, uint32_t sb, int id, int lane) {
    constexpr int NA = (N1 + 1) / 2, NG = NA + (N1 + 3) / 4, N = IS1 ? NG * N2 : NI * 2;
    if (IS1) {
#pragma unroll 1
        for (int k = 0; k < 8; k++) sts128(sb + SM_ZERO + (k * 32 + lane) * 16, make_uint4(0, 0, 0, 0));
        if (lane == 0) spin_ge(rdy_of(p, sb, 320, lds32(sb + SM_MISC + 20)), NTAIL);
    }
    __syncwarp();
    fence_async_smem();
    for (int k = IS1 ? id + (lane < CFG_CLN ? lane : N) * N1 : lane; k < N; k += IS1 ? CFG_CLN * N1 : 32) {
        if (IS1 && k >= CFG_CLN * N1) __nanosleep(CFG_CLS);
        const int wi = k / NG, g = k - wi * NG;
        const uint32_t off = IS1 ? wi * WIN + gran_off(sb, wi, g < NA ? g : 32 + g - NA, wi & 1) : q2_off(sb, k >> 1, id) + (k & 1) * 16384;
        bulk_store(p.ring + off, sb + SM_ZERO, 4096);
    }
    asm volatile("cp.async.bulk.commit_group;" ::: "memory");
    asm volatile("cp.async.bulk.wait_group 0;" ::: "memory");
    TR(21, IS1 && lane == 0);
    if (!IS1) {
        fence_async_all();
        __syncwarp();
        fence_gpu();
        if (lane < NI) red_rlx(rdy_of(p, sb, id / H3 * H2 + lane, id / H3), 1u);
    }
    __syncwarp();
}

struct In8 { uint4 a[2], o[2]; uint2 g[2]; };
__device__ __forceinline__ void p1_load(const Params& p, In8& r, int i4) {
#pragma unroll
    for (int u = 0; u < 2; u++) {
        [[maybe_unused]] uint32_t x, y;
        asm volatile("tex.1d.v4.u32.s32 {%0,%1,%2,%3}, [%4, {%5}];" : "=r"(r.a[u].x), "=r"(r.a[u].y), "=r"(r.a[u].z), "=r"(r.a[u].w) : "l"(p.t_in), "r"(i4 + u * 32));
        asm volatile("tex.1d.v4.u32.s32 {%0,%1,%2,%3}, [%4, {%5}];" : "=r"(r.o[u].x), "=r"(r.o[u].y), "=r"(r.o[u].z), "=r"(r.o[u].w) : "l"(p.t_out), "r"(i4 + u * 32));
        asm volatile("tex.1d.v4.u32.s32 {%0,%1,%2,%3}, [%4, {%5}];" : "=r"(r.g[u].x), "=r"(r.g[u].y), "=r"(x), "=r"(y) : "l"(p.t_ang), "r"(i4 + u * 32));
    }
}
__device__ __forceinline__ uint32_t imad(uint32_t a, uint32_t b, uint32_t c) {
    uint32_t r;
    asm("mad.lo.u32 %0, %1, %2, %3;" : "=r"(r) : "r"(a), "r"(b), "r"(c));
    return r;
}
__device__ __forceinline__ unsigned char* ring_ptr(const Params& p, uint32_t lo) {
    uint64_t r;
    asm("mov.b64 %0, {%1, %2};" : "=l"(r) : "r"(lo), "r"(p.ring_hi));
    return (unsigned char*)r;
}
__device__ __forceinline__ uint32_t keep32(uint32_t x) {
    return __shfl_sync(0xffffffffu, x, threadIdx.x & 31);
}
__device__ __forceinline__ uint32_t opaque32(uint32_t x) {
    asm volatile("" : "+r"(x));
    return x;
}
template <typename T> __device__ __forceinline__ T* opaque(T* p) {
    asm volatile("" : "+l"(p));
    return p;
}
template <int LUT> __device__ __forceinline__ uint32_t lop3(uint32_t a, uint32_t b, uint32_t c) {
    uint32_t r;
    asm("lop3.b32 %0, %1, %2, %3, %4;" : "=r"(r) : "r"(a), "r"(b), "r"(c), "n"(LUT));
    return r;
}
__device__ __forceinline__ uint32_t dp4(uint32_t a, uint32_t b, uint32_t c) {
    uint32_t r;
    asm("dp4a.u32.u32 %0, %1, %2, %3;" : "=r"(r) : "r"(a), "r"(b), "r"(c));
    return r;
}
__device__ __forceinline__ uint32_t dp2(uint32_t a, uint32_t b, uint32_t c) {
    uint32_t r;
    asm("dp2a.lo.u32.u32 %0, %1, %2, %3;" : "=r"(r) : "r"(a), "r"(b), "r"(c));
    return r;
}
__device__ __forceinline__ void p1_put(uint32_t sb, uint32_t wa, uint32_t wb, uint32_t old, bool on) {
    asm volatile("{.reg .pred q; setp.ne.u32 q, %3, 0; @q st.shared.v2.u32 [%0], {%1,%2};}"
                 ::"r"(sb + A_ST + prmt(old, wb, 0xf762)), "r"(wa), "r"(prmt(wb, old, 0x7210)), "r"((uint32_t)on) : "memory");
}
__device__ __forceinline__ void p1_slow_tile(const Params& p, uint32_t sb, int i4) {
    const float f = __bfloat162float(p.freq[0]);
#pragma unroll 1
    for (int u = 0; u < 8; u++) {
        const int k4 = i4 + (u >> 2) * 32;
        if (k4 < p.n4) {
            const size_t t = (size_t)k4 * 4 + (u & 3);
            const float x = __bfloat162float(__float2bfloat16(f * __bfloat162float(p.angle[t])));
            slow_add(p.m, sb, p.idx_in[t], p.idx_out[t], __bfloat162float(__float2bfloat16(cosf(x))));
        }
    }
}
__device__ __forceinline__ void role_p1(const Params& p, uint32_t sb, int id, int w, int lane) {
    lane = keep32(lane);
    const uint32_t f2 = (uint32_t)__bfloat16_as_ushort(p.freq[0]) * 0x10001u;
    constexpr int TG = CFG_TG, NTK = P1W;
    static_assert(NTK <= 16, "tickets");
    const int tc = (w + id) % NTK, first = (N1 * P1W + tc) * (TG * 64);
    uint32_t* const tickets = opaque(ctl_word(p, sb, 29 + tc / 8, tc % 8 * 128 + lane, tc & 1));
    auto draw = [&]() {
        uint32_t t = 0;
        asm volatile("{.reg .pred q; setp.eq.u32 q, %2, 0; @q atom.relaxed.gpu.global.add.u32 %0, [%1], 1;}" : "+r"(t) : "l"(tickets), "r"(lane) : "memory");
        return t;
    };
    int i4 = (id * P1W + w) * (TG * 64);
    In8 r;
    ACC_DECL
    uint32_t tk = draw();
    p1_load(p, r, i4 + lane);
    while (i4 < p.n4) {
        const int cur = i4;
        i4 += 64;
        if (i4 % (TG * 64) == 0) {
            i4 = min(__shfl_sync(0xffffffffu, tk, 0), 0x7fffffffu / (NTK * TG * 64) - N1 * P1W / NTK - 2) * (NTK * TG * 64) + first;
            tk = draw();
        }
        uint32_t wa[8], wb[8], x2[4];
        x2[0] = mul_bf2(r.g[0].x, f2); x2[1] = mul_bf2(r.g[0].y, f2);
        x2[2] = mul_bf2(r.g[1].x, f2); x2[3] = mul_bf2(r.g[1].y, f2);
        const uint32_t mx = maxabs_bf2(maxabs_bf2(x2[0], x2[1]), maxabs_bf2(x2[2], x2[3]));
        const bool fast = __all_sync(0xffffffffu, cur + 64 <= p.n4 && ((mx & 0x7fffu) <= 0x4300u) && ((mx & 0x7fff0000u) <= 0x43000000u));
        {
            const uint32_t in[8] = {r.a[0].x, r.a[0].y, r.a[0].z, r.a[0].w, r.a[1].x, r.a[1].y, r.a[1].z, r.a[1].w};
            const uint32_t ou[8] = {r.o[0].x, r.o[0].y, r.o[0].z, r.o[0].w, r.o[1].x, r.o[1].y, r.o[1].z, r.o[1].w};
#pragma unroll
            for (int j = 0; j < 8; j += 2) {
                const uint32_t ch = mul_h2(pack_h2(__cosf(bflo(x2[j >> 1])), __cosf(bfhi(x2[j >> 1]))), 0x24002400u);
#pragma unroll
                for (int k = j; k < j + 2; k++) {
                    const uint32_t blk = __umulhi(in[k], p.magic2), il = imad(blk, p.nrows2, in[k]);
                    wa[k] = k & 1 ? bitsel(ch, il, 0xffff0000u) : imad(ch, 65536u, il);
                    wb[k] = imad(blk, 1u << 21, imad(ou[k] >> 5, 1u - (1u << 21), ou[k] << 16));
                }
            }
        }
        p1_load(p, r, i4 + lane);
        if (fast) {
            uint32_t old[8], any = 0;
#pragma unroll
            for (int j = 0; j < 8; j++) old[j] = atoms_add(dp2(wb[j], 0x400u, 0u) + (sb + A_CNT), 0x80001u);
#pragma unroll
            for (int j = 0; j < 8; j++) any |= old[j];
            if (!__any_sync(0xffffffffu, any & 0xffe0u)) {
#pragma unroll
                for (int j = 0; j < 8; j++) p1_put(sb, wa[j], wb[j], old[j], true);
            } else {
                uint32_t pend = 0;
#pragma unroll
                for (int j = 0; j < 8; j++) { p1_put(sb, wa[j], wb[j], old[j], !(old[j] & 0xffe0u)); if (old[j] & 0xffe0u) pend |= 1u << j; }
                ACC(0, 1)
                for (int guard = 0; __any_sync(0xffffffffu, pend); guard++) {
                    __nanosleep(CFG_BSLEEP);
                    ACC(1, 1)
#pragma unroll
                    for (int j = 0; j < 8; j++) {
                        if (__any_sync(0xffffffffu, pend >> j & 1)) {
                            const uint32_t c = lds32v(sb + A_CNT + (pend >> j & 1 ? wb[j] >> 16 : 0) * 4);
                            const bool go = (pend >> j & 1) && (((old[j] >> 19) - (c >> 19) + c) & 8191u) < 32u;
                            p1_put(sb, wa[j], wb[j], old[j], go);
                            if (go) pend &= ~(1u << j);
                        }
                    }
                    if (guard > GUARD) __trap();
                }
            }
        } else {
            p1_slow_tile(p, sb, cur + lane);
            __syncwarp();
        }
    }
    __syncwarp();
    mbar_arrive_if(sb + SM_DONE, lane == 0);
    ACC_SAVE
}

__device__ __forceinline__ void role_flush(const Params& p, uint32_t sb, int id, int f, int lane) {
    lane = keep32(lane);
    const int half = lane >> 4, o = lane >> 2, q = lane & 3;
    const uint32_t hm = keep32(half ? 0xffff0000u : 0xffffu), lth = keep32(((1u << lane) - 1) & hm);
    const uint32_t list = sb + A_LIST + f * LISTB, cnt = keep32(sb + A_CNT + (f * GPW * 32 + lane) * 4);
    const uint32_t cred = opaque32(sb + SM_CRED + (half * 32 + f * GPW) * 4);
    const uint32_t pa = opaque32(p.ring_lo + (id >> 1) * 8192 + (id & 1) * 2048 + q * 16);
    const uint32_t ph = opaque32(p.ring_lo + (32 + (id >> 2)) * 8192 + (id & 3) * 1024 + q * 8 - 2048);
    const uint32_t sa = q * 16 + (o & 1) * 64;
    uint32_t qo[GPW], hs[GPW], cr[4] = {0, 0, 0, 0};
#pragma unroll
    for (int g = 0; g < GPW; g++) {
        const int blk = f * GPW + g;
        qo[g] = 32u << 25;
        const uint32_t sa = sel_of(sb, 2 * blk + half, id >> 1, half), sh = sel_of(sb, 2 * blk + half, 32 + (id >> 2), half);
        hs[g] = sa << 31 | (2 * sh + 1 - sa) << 22 | 1u << 24 | (lane & 15) << 15 | (blk * 32 + lane) * 2;
    }
    uint4 x[KR] = {}, y[KR] = {};
    uint32_t c[GPW] = {};
    auto scan = [&]() {
#pragma unroll
        for (int g = 0; g < GPW; g++) c[g] = lds32v(cnt + g * 128);
    };
    auto credits = [&]() {
        if (GPW == 4) { const uint4 v = lds128(cred); cr[0] = v.x; cr[1] = v.y; cr[2] = v.z; cr[3] = v.w; }
        else { const uint2 v = lds64v(cred); cr[0] = v.x; cr[1] = v.y; }
    };
    ACC_DECL
    int guard = 0;
    bool idle = false, done = false;
    while (true) {
        uint32_t fr[GPW], rank[GPW], num = 0, left = 0;
        bool ok[GPW];
        if (idle && !done && __all_sync(0xffffffffu, mbar_test(sb + SM_DONE, 0))) {
            done = true;
            TR(17, f == 0 && lane == 0);
#pragma unroll
            for (int g = 0; g < GPW; g++) {
                const uint32_t u = lds32v(cnt + g * 128) & 31u, hd = hs[g] ^ (u & 16u ? imad(hs[g], 1u << 24, 1u) & 0x01000001u : 0u);
#pragma unroll 2
                for (uint32_t j = 0, k; k = (j + lane) & 15u, j < 16; j++)
                    sts64_if(sb + A_ST + ((hd & 0x7ffu) << 7) + k * 8, p.rows2, (lane * 16 + k) | (hd & 0x1000000u), (u & 15u) && k >= (u & 15u));
                reds_add(cnt + g * 128, ((0u - u) & 15u) * 0x80001u);
            }
            __syncwarp();
            scan();
        }
#pragma unroll
        for (int g = 0; g < GPW; g++) {
            const bool isfull = c[g] & 0xfff0u;
            rank[g] = __popc(__ballot_sync(0xffffffffu, isfull) & lth);
            ok[g] = isfull && (int)(rank[g] << 25) < (int)(cr[g] - qo[g] + (63u << 25));
            ACC(2, __popc(__ballot_sync(0xffffffffu, isfull && !ok[g])))
        }
#pragma unroll
        for (int g = 0; g < GPW; g++) {
            const uint32_t m = __ballot_sync(0xffffffffu, ok[g]), n = __popc(m & hm), all = __popc(m), e = num + rank[g] + (half ? all - n : 0u);
            sts32_if(KR == 2 ? list + (e & 48u) * 4 + (e & 7u) * 8 + (e >> 1 & 4u) : imad(e, 4u, list), bitsel(imad(rank[g], 1u << 25, qo[g]), hs[g], 0x7e000000u), ok[g]);
            if (ok[g]) hs[g] ^= imad(hs[g], 1u << 24, 1u) & 0x01000001u;
            fr[g] = ok[g] ? 0u - 16u : 0u;
            left |= c[g] + fr[g];
            qo[g] = imad(n, 1u << 25, qo[g]);
            num += all;
        }
        __syncwarp();
        ACC(0, 1) ACC(1, num)
        if (num) {
            uint32_t la = list + o * (KR == 2 ? 8 : 4);
            int todo = (int)num - o, rest = num;
            do {
                uint32_t d[KR];
                if (KR == 2) { const uint2 v = lds64v(la); d[0] = v.x; d[KR - 1] = v.y; }
                else {
#pragma unroll
                    for (int k = 0; k < KR; k++) d[k] = lds32v(la + 32 * k);
                }
                while (true) {
                    uint32_t bad = 0;
#pragma unroll
                    for (int k = 0; k < KR; k++) {
                        const uint32_t m = d[k] & 0x7ffu;
                        lds128_keep(x[k], imad(m, 128u, sa) + (sb + A_ST), todo > 8 * k);
                        lds128_keep(y[k], imad(m, 128u, sa ^ 64) + (sb + A_ST), todo > 8 * k);
                    }
#pragma unroll
                    for (int k = 0; k < KR; k++)
                        or3_if(bad, lop3<0x7e>(x[k].y, x[k].w, d[k]), lop3<0x7e>(y[k].y, y[k].w, d[k]), todo > 8 * k);
                    if (!__any_sync(0xffffffffu, (int)imad(bad, 128u, 0u) < 0)) break;
                    if (++guard > GUARD) __trap();
                }
#pragma unroll
                for (int k = 0; k < KR; k++) {
                    const uint32_t mi = d[k] & 0x7e0u, dm = d[k] & 0xbec00000u;
                    x[k].x = bitsel(d[k], x[k].x, 0x40078000u);
                    x[k].y = prmt(x[k].y, x[k].w, 0x5410);
                    x[k].w = prmt(y[k].y, y[k].w, 0x5410);
                    y[k].x = bitsel(d[k], y[k].x, 0x40000000u);
                    y[k].y = y[k].z;
                    stg_q128(ring_ptr(p, dp4(dm, 0x20000000u, imad(mi, WIN / 32, pa))), x[k].x, x[k].y, x[k].z, x[k].w, todo > 8 * k);
                    stg_q64(ring_ptr(p, dp4(dm, 0x10200000u, imad(mi, WIN / 32, ph))), y[k].x, y[k].y, todo > 8 * k);
                }
                la += 32 * KR;
                todo -= 8 * KR;
                rest -= 8 * KR;
            } while (rest > 0);
#pragma unroll
            for (int g = 0; g < GPW; g++) c[g] = atoms_add(cnt + g * 128, fr[g]) + fr[g];
            credits();
            idle = num <= CFG_TH;
            if (done && !__any_sync(0xffffffffu, left & 0xffffu)) break;
            if (idle) { __nanosleep(CFG_TS); scan(); credits(); }
        } else {
            if (done && !__any_sync(0xffffffffu, left & 0xffffu)) break;
            idle = true;
            __nanosleep(CFG_FSLEEP);
            scan();
            credits();
            if (++guard > GUARD) __trap();
        }
    }
#pragma unroll
    for (int g = 0; g < GPW; g++) st_rlx_if(fin1_of(p, sb, half * H2 + f * GPW + g) + id, qo[g] - (32u << 25) + 1u, (lane & 15) == 0 && f * GPW + g < NI);
    mbar_arrive_if(sb + SM_DONE2, lane == 0);
    TR(18, f == 0 && lane == 0);
    ACC_SAVE
}
__device__ __forceinline__ void role_credit1(const Params& p, uint32_t sb, int id, int lane) {
    const uint32_t* const cred = cred1_of(p, sb, id) + lane * 2;
    for (int guard = 0; !__all_sync(0xffffffffu, mbar_test(sb + SM_DONE2, 0)); guard++) {
        const uint2 v = ldg_q64(cred);
        sts64(sb + SM_CRED + lane * 8, v.x, v.y);
        __nanosleep(CFG_C1SLEEP);
        if (guard > GUARD) __trap();
    }
}

__device__ __forceinline__ float h2f(uint32_t h) {
    float f;
    asm("{.reg .b16 t; cvt.u16.u32 t, %1; cvt.f32.f16 %0, t;}" : "=f"(f) : "r"(h));
    return f;
}
__device__ __forceinline__ void p2_slow(const Params& p, uint32_t sb, const uint32_t* tmp, int row0, uint32_t dst) {
#pragma unroll 1
    for (int j = 0; j < 4; j++)
        if (tmp[8 + j] & 0x40u) slow_add(p.m, sb, row0 + (tmp[j] & 0x7fffu), (tmp[4 + j] & 0x7fffu) * 32 + dst, h2f(tmp[j] >> 16) * 64.0f);
}
__device__ __forceinline__ uint32_t mul_h2_hi(uint32_t a, uint32_t b) {
    uint32_t r;
    asm("{.reg .b16 l, h; .reg .b32 t; mov.b32 {l, h}, %2; mov.b32 t, {h, h}; mul.rn.f16x2 %0, %1, t;}" : "=r"(r) : "r"(a), "r"(b));
    return r;
}
template <bool CHECK>
__device__ __forceinline__ void role_p2(const Params& p, uint32_t sb, int id, int w, int lane) {
    lane = keep32(lane);
    const int part = id / H2, blk = id - part * H2, row0 = blk * p.rows2;
    const int o = lane >> 2, q = lane & 3;
    uint32_t* const cbase = (uint32_t*)(p.ring + (CWIN + lds32(sb + SM_MISC + 16)) * WIN);
    const uint32_t cred = opaque32((uint32_t)(uintptr_t)(cbase + part * 32 + blk));
    const uint32_t pa = opaque32(p.ring_lo + (2 * blk + part) * WIN + q * 16), ph = opaque32(pa - q * 8);
    const uint32_t po = opaque32(p.ring_lo + (q2_off(sb, blk, part * H3) & ~4096u) + q * 16 + (o & 1) * 64);
    const uint32_t sel = __ballot_sync(0xffffffffu, q2_off(sb, blk, part * H3 + (lane & 15)) & 4096u) << 12;
    const uint32_t* const fins = fin1_of(p, sb, id);
    uint32_t st[QPW] = {}, sq[QPW] = {};
    uint4 qa[NBT];
    uint2 qh[NBT];
    auto load = [&](int k) {
        qa[k] = ldg_q128(ring_ptr(p, pa + (bitsel(sq[k], st[k] >> 19, 0x7f800u) & 0x7ffc0u)));
        qh[k] = ldg_q64(ring_ptr(p, ph + (bitsel(sq[k] >> 9, st[k] >> 20, 0x7fc00u) & 0x7ffe0u)));
    };
#pragma unroll
    for (int k = 0; k < QPW; k++) {
        const int src = w * QPW + k;
        st[k] = o << 25 | (src < N1 ? 1u : 5u);
        sq[k] = src < N1 ? q1h_off(sb, src, blk, part) << 9 | q1a_off(sb, src, blk, part) | (uint32_t)(cred1_of(p, sb, src) - cbase) / 8 : 0x7e000u * 513u;
    }
#pragma unroll
    for (int k = 0; k < NBT; k++) load(k);
    ACC_DECL
    int guard = 0;
    uint32_t streak = 0;
    while (true) {
        uint32_t nn[NBT], xx[NBT][4], hh[NBT][2], dd[NBT], any = 0;
        bool last = false;
#pragma unroll
        for (int k = 0; k < NBT; k++) {
            const uint4 a = qa[k];
            const uint2 h = qh[k];
            uint32_t n = 8;
            const uint32_t miss = __ballot_sync(0xffffffffu, (int)imad((a.x ^ st[k]) & (h.x ^ st[k]), 2u, 0u) >= 0);
            if (miss) {
                n = (__ffs(miss) - 1) >> 2;
                if (!__any_sync(0xffffffffu, st[k] & 8u)) { if (streak < CFG_PSTREAK) n &= CFG_PMASK; }
                else if (!__any_sync(0xffffffffu, ((st[k] >> 6) + ((n - o) << 19) ^ st[k]) & 0x1f80000u)) { st[k] |= 4u; last = true; }
            }
            ACC(1, n == 0) ACC(2, n != 0) ACC(3, n)
            st[k] = imad(n, 1u << 25, st[k]);
            st_rlx_if((uint32_t*)ring_ptr(p, imad(sq[k] & 0x7f0u, 32u, cred)), st[k], lane == 0 && n);
            xx[k][0] = bitsel(a.x, 0x00040000u, 0xbff87fffu); xx[k][1] = a.z; xx[k][2] = h.x & 0xbfffffffu; xx[k][3] = h.y;
            hh[k][0] = a.y; hh[k][1] = a.w; dd[k] = a.x >> 13 & 0x3cu; nn[k] = n;
            any |= n;
        }
        if (!any) {
#pragma unroll
            for (int k = 0; k < QPW; k++) {
                const uint32_t fin = ld_rlx(fins + ((sq[k] >> 12 & 62u) | (sq[k] >> 11 & 1u)));
                if (fin & 1u) st[k] |= (fin >> 6 & 0x1f80000u) | ((fin ^ (st[k] - (o << 25))) >> 25 ? 8u : 12u);
            }
            last = true;
            if (++guard > GUARD) __trap();
            streak++;
        } else streak = 0;
        if (last) {
            uint32_t all = 4u;
#pragma unroll
            for (int k = 0; k < QPW; k++) all &= st[k];
            last = __all_sync(0xffffffffu, all);
        }
        {
            uint32_t t[QPW], u[QPW];
#pragma unroll
            for (int k = 0; k < QPW; k++) { t[k] = st[(k + NBT) % QPW]; u[k] = sq[(k + NBT) % QPW]; }
#pragma unroll
            for (int k = 0; k < QPW; k++) { st[k] = t[k]; sq[k] = u[k]; }
        }
#pragma unroll
        for (int k = 0; k < NBT; k++) load(k);
#pragma unroll
      for (int k = 0; k < NBT; k++) {
        if (nn[k]) {
            const uint32_t* const x = xx[k];
            const uint32_t h0 = hh[k][0], h1 = hh[k][1], d4 = dd[k];
            const bool v = o < nn[k];
            uint32_t old = 0, ta[4], tb[4], w0[4], w1[4];
            atoms_add_keep(old, sb + SM_CNT2 + d4, 0x10001u, q == 0 && v);
#pragma unroll
            for (int j = 0; j < 4; j++) {
                ta[j] = lds32nv(dp2(x[j], 4u, 0u) + (sb + B_TA));
                tb[j] = lds16nv(dp2(x[j], 2u, 0u) + (sb + B_TB));
            }
            old = __shfl_sync(0xffffffffu, old, lane & 28);
            const uint32_t tag = old << 8 & 0x40000000u;
#pragma unroll
            for (int j = 0; j < 4; j++) {
                const uint32_t z = prmt(j & 2 ? h1 : h0, 0, j & 1 ? 0x4342 : 0x4140);
                const uint32_t t23 = prmt((ta[j] & 0x60076007u) * 2050u, tb[j], 0x5341) & 0xfffcffffu;
                w0[j] = (imad(z, 128u, j & 1 ? 0u : tag) & 0x78007800u) | mul_h2_hi(ta[j] & 0x9ff89ff8u, x[j]);
                w1[j] = (imad(z, 2048u, 0u) & 0x78007800u) | mul_h2_hi(t23, x[j]);
            }
            if (CHECK && v && ((tb[0] | tb[1] | tb[2] | tb[3]) & 0x40u)) {
                uint32_t tmp[12];
#pragma unroll
                for (int j = 0; j < 4; j++) {
                    tmp[j] = x[j]; tmp[4 + j] = (j & 2 ? h1 : h0) >> (j & 1 ? 16 : 0); tmp[8 + j] = tb[j];
                    if (tb[j] & 0x40u) { w0[j] &= 0x78007800u; w1[j] &= 0x78007800u; }
                }
                p2_slow(p, sb, tmp, row0, part * H3 + d4 / 4);
            }
            const uint32_t off = (bitsel(old >> 9, old >> 7, 0x0f80u) & 0x4f80u) + imad(d4, WIN / 4, (sel >> (d4 / 4) & 4096u) + po);
            bool wait = old & (0x10000u - NQ2);
            if (!__any_sync(0xffffffffu, wait)) {
                stg_q128(ring_ptr(p, off), w0[0], w1[0], w0[1], w1[1], v);
                stg_q128(ring_ptr(p, off ^ 64u), w0[2], w1[2], w0[3], w1[3], v);
            } else {
                bool pend = v;
                ACC(0, 1)
                for (int g2 = 0;; g2++) {
                    stg_q128(ring_ptr(p, off), w0[0], w1[0], w0[1], w1[1], pend && !wait);
                    stg_q128(ring_ptr(p, off ^ 64u), w0[2], w1[2], w0[3], w1[3], pend && !wait);
                    pend = wait;
                    if (!__any_sync(0xffffffffu, pend)) break;
                    __nanosleep(CFG_BSLEEP);
                    const uint32_t c = lds32v(sb + SM_CNT2 + d4);
                    wait = pend && (((old >> 16) - (c >> 16) + c) & 0xffffu) >= NQ2;
                    if (g2 > GUARD) __trap();
                }
            }
        }
      }
        if (last) break;
    }
    TR(17, w == 0 && lane == 0);
    __syncwarp();
    uint32_t rank = 0;
    if (lane == 0) { __threadfence_block(); rank = atoms_add(sb + SM_FIN, 1u); __threadfence_block(); }
    if (__shfl_sync(0xffffffffu, rank, 0) == P2W - 1 && lane < 16)
        st_rlx(fin2_of(p, sb, part * H3 + lane) + blk, FIN | (((lds32v(sb + SM_CNT2 + lane * 4) >> 16) - NQ2) & 0xffffu));
    __syncwarp();
    mbar_arrive_if(sb + SM_DONE, lane == 0);
    ACC_SAVE
}
__device__ __forceinline__ void role_credit(const Params& p, uint32_t sb, int id, int lane) {
    const uint32_t* const cred = cred2_of(p, sb, id) + (lane & 15);
    uint32_t last = 0;
    for (int guard = 0;; guard++) {
        if (__all_sync(0xffffffffu, mbar_test(sb + SM_DONE, 0))) break;
        const uint32_t c = ld_rlx(cred);
        if (lane < 16 && c != last) reds_add(sb + SM_CNT2 + lane * 4, 0u - ((c - last) & 0xffffu));
        last = c;
        __nanosleep(CFG_CSLEEP);
        if (guard > GUARD) __trap();
    }
}

__device__ __forceinline__ void p3_wrap(uint32_t sb, int id, const uint32_t* tmp) {
    const Scale sc = get_scale(sb);
#pragma unroll 1
    for (int j = 0; j < 8; j++) {
        const uint32_t old = tmp[4 + j], v = tmp[12 + j], nw = old + v, t = (old ^ nw) & (v ^ nw);
        if (t & 0x80008000u) {
            const float k = (t & 0x8000u) ? ((v & 0x8000u) ? -1.0f : 1.0f) : 0.0f;
            const float q = (t & 0x80000000u) ? ((int)v < 0 ? -65536.0f : 65536.0f) : 0.0f;
            const uint32_t e0 = (j & 1) ? sc.eb[2] : sc.eb[0], e1 = (j & 1) ? sc.eb[3] : sc.eb[1];
            const float lo = k * 65536.0f * __uint_as_float((e0 - 10) << 23), hi = (q - k) * __uint_as_float((e1 - 10) << 23);
            if (j & 1) sg_add(tmp[j >> 1] * 32 + id, 0.f, 0.f, lo, hi);
            else sg_add(tmp[j >> 1] * 32 + id, lo, hi, 0.f, 0.f);
        }
    }
}
__device__ __forceinline__ uint32_t p3_val(uint32_t w) {
    const uint32_t mk = prmt(w, 0, 0xBB99);
    return ((w & 0x07ff07ffu) ^ mk) - mk;
}
__device__ __forceinline__ void role_p3(const Params& p, uint32_t sb, int id, int w, int lane) {
    lane = keep32(lane);
    uint32_t* const cred = opaque(cred2_of(p, sb, id / H3 * H2 + w) + id % H3);
    const uint32_t pq = opaque32(p.ring_lo + q2_off(sb, w, id) + lane * 16);
    auto off = [&](uint32_t n) { return (n & 1u) << 11 | (n & 2u) << 13; };
    const uint32_t pp = opaque32(pq - lane * 16 + 112);
    const uint32_t* const finp = opaque(fin2_of(p, sb, id) + w);
    auto tag_of = [&](uint32_t n) { return ~n << 28; };
    uint32_t n = 0, fin = 0, pr = 0, pk = 0;
    uint4 v[4] = {};
    bool have = false, last = false;
    ACC_DECL
    int guard = 0;
    while (true) {
        const uint32_t ex = tag_of(n);
        const bool ok = have && !__any_sync(0xffffffffu, ((v[0].x ^ ex) | (v[1].x ^ ex) | (v[2].x ^ ex) | (v[3].x ^ ex)) & 0x40000000u);
        if (ok) n++;
        const bool ready = (ok || !have) && __all_sync(0xffffffffu, !((pr ^ tag_of(n)) & 0x40000000u));
        st_rlx_if(cred, n * 16, lane == 0 && ok);
        if (!ok && !ready && __all_sync(0xffffffffu, fin & FIN)) {
            const uint32_t left = __shfl_sync(0xffffffffu, (fin - n * 16) & 0xffffu, 0);
            if (left - 1u > 0x8000u) break;
            if (left < 16u) {
#pragma unroll
                for (int u = 0; u < 4; u++) {
                    v[u] = make_uint4(ex & 0x40000000u, 0, 0, 0);
                    ldq128_keep(v[u], ring_ptr(p, pq + off(n)) + u * 512, u * 4 + (lane >> 3) < left);
                }
                have = last = !__any_sync(0xffffffffu, ((v[0].x ^ ex) | (v[1].x ^ ex) | (v[2].x ^ ex) | (v[3].x ^ ex)) & 0x40000000u);
                pr = ~tag_of(n + have);
                if (++guard > GUARD) __trap();
                continue;
            }
        }
        uint32_t row[8], val[16];
#pragma unroll
        for (int u = 0; u < 4; u++) {
            const uint4 x = v[u];
            row[2 * u] = prmt(bitsel(x.x << 1, x.y >> 3, 0x7000f000u), 0, 0x4431);
            row[2 * u + 1] = prmt(bitsel(x.z << 1, x.w >> 3, 0x7000f000u), 0, 0x4431);
            val[4 * u] = p3_val(x.x); val[4 * u + 1] = p3_val(x.y);
            val[4 * u + 2] = p3_val(x.z); val[4 * u + 3] = p3_val(x.w);
        }
#pragma unroll
        for (int u = 0; u < 4; u++) ldq128_keep(v[u], ring_ptr(p, pq + off(n)) + u * 512, ready);
        pk = ready ? CFG_PK1 * 128 : ok ? CFG_PK2 * 128 : have ? 15 * 128 : max(pk, CFG_PK3 * 128u);
        pr = ld_rlx((const uint32_t*)ring_ptr(p, pp + off(n + ready) + pk));
        ACC(2, have && !ok)
        have = ready;
        if (!ok) {
            ACC(1, 1)
            fin = ld_rlx(finp);
            if (++guard > GUARD) __trap();
        } else {
#pragma unroll
            for (int u = 0; u < 4; u += 2) {
                uint32_t old[8], chk = 0;
#pragma unroll
                for (int j = 0; j < 4; j++) {
                    old[2 * j] = atoms_add(sb + C_S + row[2 * u + j] * 4, val[4 * u + 2 * j]);
                    old[2 * j + 1] = atoms_add(sb + C_S + ROWS3_MAX * 4 + row[2 * u + j] * 4, val[4 * u + 2 * j + 1]);
                }
#pragma unroll
                for (int j = 0; j < 8; j++) {
                    const uint32_t nw = old[j] + val[4 * u + j];
                    chk |= (old[j] ^ nw) & (val[4 * u + j] ^ nw);
                }
                if (chk & 0x80008000u) {
                    uint32_t tmp[20];
#pragma unroll
                    for (int j = 0; j < 8; j++) { tmp[j >> 1] = row[2 * u + (j >> 1)]; tmp[4 + j] = old[j]; tmp[12 + j] = val[4 * u + j]; }
                    p3_wrap(sb, id, tmp);
                }
            }
            __syncwarp();
            if (last) break;
        }
    }
    ACC_SAVE
}

__device__ __forceinline__ void row_gates(const float* sw, const uint32_t* c2, uint32_t dbits, float4& gs, float4& gr) {
    const uint32_t d2 = dbits * 0x10001u;
    gs = gr = make_float4(0.f, 0.f, 0.f, 0.f);
#pragma unroll
    for (int r2 = 0; r2 < 4; r2++) {
        uint32_t df = sub_bf2(d2, c2[r2]);
        uint32_t ar = mul_bf2(mul_bf2(df, df), 0xC120C120u);
        uint32_t rb = pack_bf2(__expf(bflo(ar)), __expf(bfhi(ar)));
        const float r0 = bflo(rb), r1 = bfhi(rb);
        const float4 s0 = *(const float4*)(sw + r2 * 8), s1 = *(const float4*)(sw + r2 * 8 + 4);
        const float4 q0 = *(const float4*)(sw + 32 + r2 * 8), q1 = *(const float4*)(sw + 32 + r2 * 8 + 4);
        gs.x += r0 * s0.x + r1 * s1.x; gs.y += r0 * s0.y + r1 * s1.y;
        gs.z += r0 * s0.z + r1 * s1.z; gs.w += r0 * s0.w + r1 * s1.w;
        gr.x += r0 * q0.x + r1 * q1.x; gr.y += r0 * q0.y + r1 * q1.y;
        gr.z += r0 * q0.z + r1 * q1.z; gr.w += r0 * q0.w + r1 * q1.w;
    }
}
__device__ __forceinline__ uint2 finish_row(const float* wu, const float4& gs, const float4& gr, const float S[4], uint2 mrow) {
    const float a[4] = {S[0] * gs.x, S[1] * gs.y, S[2] * gs.z, S[3] * gs.w};
    float u[4] = {0, 0, 0, 0};
#pragma unroll
    for (int k = 0; k < 4; k++) {
        u[0] += a[k] * wu[4 * k]; u[1] += a[k] * wu[4 * k + 1]; u[2] += a[k] * wu[4 * k + 2]; u[3] += a[k] * wu[4 * k + 3];
    }
    return make_uint2(pack_bf2(bflo(mrow.x) + u[0] * gr.x, bfhi(mrow.x) + u[1] * gr.y),
                      pack_bf2(bflo(mrow.y) + u[2] * gr.z, bfhi(mrow.y) + u[3] * gr.w));
}
__device__ __forceinline__ void load_tail_weights(const Params& p, float* sw, int tid) {
    if (tid < 32) sw[tid] = __bfloat162float(p.w_sbf[tid]);
    else if (tid < 64) sw[tid] = __bfloat162float(p.w_rbf[tid - 32]);
    else if (tid < 80) sw[tid] = __bfloat162float(p.w_up[tid - 64]);
    else if (tid < 96) sw[tid] = __bfloat162float(p.w_down[tid - 80]);
}
__device__ __forceinline__ float exp_ftz(float x) {
    float r;
    asm("ex2.approx.ftz.f32 %0, %1;" : "=f"(r) : "f"(x * 1.4426950408889634f));
    return r;
}
__device__ __forceinline__ void tail_rows(const Params& p, int tidx, int w, int lane) {
    constexpr uint32_t sb = SB;
    if (w == NW - 1 && lane < 2) {
        fence_gpu();
        red_rlx(rdy_of(p, sb, 320, lane), 1u);
    }
    if (w >= NPC * WPP) return;
    const int pc = w / WPP, r0 = pc * RPC + (tidx * WPP + w - pc * WPP) * 8, e0 = r0 * 32;
    const uint32_t G = sb + T_G + w * TWB, M = G + 4096, D = M + 2048;
    cp16z(D + lane * 16, p.dist + e0 + lane * 8, min(max(p.E - e0 - lane * 8, 0), 8) * 2);
#pragma unroll
    for (int k = 0; k < 4; k++) cp16(M + (k * 32 + lane) * 16, p.m + e0 + (k * 32 + lane) * 2, e0 + (k * 32 + lane) * 2 < p.E);
    cp_commit();
    const Scale sc = get_scale(sb);
    const float lsb[4] = {__uint_as_float((sc.eb[0] - 10) << 23), __uint_as_float((sc.eb[1] - 10) << 23),
                          __uint_as_float((sc.eb[2] - 10) << 23), __uint_as_float((sc.eb[3] - 10) << 23)};
    {
        const int g = lane >> 2, t = lane & 3;
        const uint32_t c2 = ((const uint32_t*)p.centers)[t];
        const unsigned short* wg = (const unsigned short*)(g < 4 ? p.w_sbf : p.w_rbf) + t * 8 + (g & 3);
        const uint32_t b = wg[0] | (uint32_t)wg[4] << 16;
        cp_wait<0>();
        __syncwarp();
        TR(19, w == 0 && lane == 0 && b + c2 != 0x12345);
#pragma unroll 2
        for (int k = 0; k < 16; k++) {
            const uint32_t dv = lds32(D + (k * 8 + g) * 4);
            uint32_t a[2];
#pragma unroll
            for (int h = 0; h < 2; h++) {
                const uint32_t df = sub_bf2(prmt(dv, 0, h ? 0x3232 : 0x1010), c2);
                const uint32_t ar = mul_bf2(mul_bf2(df, df), 0xC120C120u);
                a[h] = pack_bf2(exp_ftz(bflo(ar)), exp_ftz(bfhi(ar)));
            }
            float d[4];
            asm("mma.sync.aligned.m16n8k8.row.col.f32.bf16.bf16.f32 {%0,%1,%2,%3}, {%4,%5}, {%6}, {%7,%7,%7,%7};"
                : "=f"(d[0]), "=f"(d[1]), "=f"(d[2]), "=f"(d[3]) : "r"(a[0]), "r"(a[1]), "r"(b), "f"(0.f));
            const uint32_t at = G + (k * 16 + g * 2) * 16 + t * 4;
            sts32(at, pack_bf2(d[0], d[1]));
            sts32(at + 16, pack_bf2(d[2], d[3]));
        }
    }
    __syncwarp();
    TR(2, w == 0 && lane == 0);
    float wu[16];
#pragma unroll
    for (int k = 0; k < 4; k++) *(uint4*)(wu + 4 * k) = lds128(sb + SM_W + 256 + 16 * k);
    uint32_t dirty = 0;
#pragma unroll 1
    for (int pass = CFG_DRY ? 0 : 1; pass < 2; pass++) {
        if (pass) {
            if (w == pc * WPP && lane < 2) spin_ge(rdy_of(p, sb, lane ? 320 : 160 + 32 * pc, lds32(sb + SM_MISC + 20)), lane ? NTAIL : N3);
            __syncwarp();
            bar_sync(1 + pc, WPP * 32);
            TR(3, w == 0 && lane == 0);
            TR(10, w == NPC * WPP - 1 && lane == 0);
            if (r0 >= (int)p.rows3) return;
        }
        uint4 sv[4] = {};
#pragma unroll
        for (int u = 0; u < 4; u++) ldq128_keep(sv[u], &g_S[0][u * 16 + (lane >> 1)][r0 + (lane & 1) * 4], pass);
        if (pass && lane < 8 && (r0 + lane) * 32 < p.E && (dirty = ld_rlx(g_dirty + r0 + lane))) st_rlx(g_dirty + r0 + lane, 0u);
        dirty = __ballot_sync(0xffffffffu, dirty != 0);
        uint32_t xs[8] = {sv[0].x, sv[0].y, sv[0].z, sv[0].w, sv[1].x, sv[1].y, sv[1].z, sv[1].w};
        uint32_t ys[8] = {sv[2].x, sv[2].y, sv[2].z, sv[2].w, sv[3].x, sv[3].y, sv[3].z, sv[3].w};
        asm volatile("" : "+r"(lane));
        auto finish = [&](int k, uint32_t x, uint32_t y, bool extra) {
            const int i = (lane & 1) * 128 + (lane >> 1) + (k & 3) * 32 + (k >> 2) * 16, e = e0 + i;
            float S[4];
            const uint32_t tx = x + 0x80008000u, ty = y + 0x80008000u;
            S[0] = (__uint_as_float(prmt(tx, 0x4b000000u, 0x7610)) - 8421376.0f) * lsb[0];
            S[1] = (__uint_as_float(prmt(tx, 0x4b000000u, 0x7632)) - 8421376.0f) * lsb[1];
            S[2] = (__uint_as_float(prmt(ty, 0x4b000000u, 0x7610)) - 8421376.0f) * lsb[2];
            S[3] = (__uint_as_float(prmt(ty, 0x4b000000u, 0x7632)) - 8421376.0f) * lsb[3];
            if (extra && e < p.E) {
                const float4 g = __ldcg(g_Sg + e);
                S[0] += g.x; S[1] += g.y; S[2] += g.z; S[3] += g.w;
                __stcg(g_Sg + e, make_float4(0.f, 0.f, 0.f, 0.f));
            }
            const uint4 g = lds128(G + i * 16);
            const uint2 o = finish_row(wu, make_float4(bflo(g.x), bfhi(g.x), bflo(g.y), bfhi(g.y)), make_float4(bflo(g.z), bfhi(g.z), bflo(g.w), bfhi(g.w)), S,
                                       lds64v(M + i * 8));
            asm volatile("{.reg .pred q; setp.ne.u32 q, %3, 0; @q st.global.v2.u32 [%0], {%1,%2};}"
                         ::"l"(p.out + e), "r"(o.x), "r"(o.y), "r"((uint32_t)(pass && e < p.E)));
        };
        if (!dirty) {
#pragma unroll
            for (int k = 0; k < 8; k++) finish(k, xs[k], ys[k], false);
        } else {
#pragma unroll 1
            for (int k = 0; k < 8; k++) {
                finish(k, xs[0], ys[0], dirty >> ((lane & 1) * 4 + (k & 3)) & 1);
#pragma unroll
                for (int j = 0; j < 7; j++) { xs[j] = xs[j + 1]; ys[j] = ys[j + 1]; }
            }
        }
    }
    TR(9, w == 0 && lane == 0);
    TR(11, w == NPC * WPP - 1 && lane == 0);
}

#define CFG_MAP1 1
__global__ void __launch_bounds__(NT, 1) k_main(const __grid_constant__ Params p) {
    extern __shared__ __align__(1024) unsigned char smem[];
    constexpr uint32_t sb = SB;
    if ((uint32_t)__cvta_generic_to_shared(smem) != SB) __trap();
    const int tid = threadIdx.x, w = __shfl_sync(0xffffffffu, tid >> 5, 0), lane = tid & 31;
    if (w < NPROBE) probe(p, sb, w, lane);
    else {
        if (tid == NT - 1) sts32(sb + SM_MISC + 16, ld_rlx(&g_epoch) & 1);
        if (tid >= NT - 32 && lane < 12) sts32(sb + SM_FIN + lane * 4, 0u);
        load_tail_weights(p, (float*)(smem + SM_W), tid - NPROBE * 32);
        const int k = blockIdx.x % (NCTA / 2) * 14 + lane;
        if (w == NW - 2 && lane < 14 && k < NT - 32) asm volatile("prefetch.global.L2 [%0];" ::"l"((const uint4*)p.m + k * (p.E / 2 / (NT - 32))));
    }
    cta_sync();
    if (w) {
        const uint4 in = __ldg((const uint4*)p.m + (tid - 32) * (p.E / 2 / (NT - 32)));
        const Mat4 wd = load_mat4(p.w_down, lane);
        for (int i = SM_DATA / 16 + tid - 32; i < ZEND / 16; i += NT - 32) ((uint4*)smem)[i] = make_uint4(0, 0, 0, 0);
        if (tid - 32 < 256) ((uint4*)(smem + SM_ZERO))[tid - 32] = make_uint4(0, 0, 0, 0);
        if (tid < 48) sts32(sb + SM_CNT2 + (tid - 32) * 4, NQ2 << 16);
        __syncwarp();
        if (CFG_PFD && tid == NT - 1) {
            __nanosleep(CFG_PFD);
            const uint32_t n = (p.E / 2 + NCTA - 1) / NCTA, o = blockIdx.x * n;
            if (o < (uint32_t)p.E / 2) asm volatile("cp.async.bulk.prefetch.L2.global [%0], %1;" ::"l"((const uint4*)p.m + o), "r"(min(n, p.E / 2 - o) * 16) : "memory");
        }
        __syncwarp();
        md_stats(in, wd, lane);
    } else assign_role(p, sb, lane);
    if (tid == 0) {
        mbar_init(sb + SM_DONE, lds32(sb + SM_MISC) >> 8 ? P2W : P1W);
        mbar_init(sb + SM_DONE2, NF);
    }
    cta_sync();
    const uint32_t rid = __shfl_sync(0xffffffffu, lds32(sb + SM_MISC), 0);
    const int role = rid >> 8, id = rid & 255;
    TR(5, tid == 0);
    if (role == 0) {
        const int ww = CFG_MAP1 == 0 ? ((w & 3) == 3 ? NW : (w >> 2) * 3 + (w & 3)) : CFG_MAP1 == 1 ? (w & 2 ? NW : (w >> 2) * 2 + (w & 1)) : w;
        const int sw = CFG_MAP1 == 0 ? ((w & 3) == 3 ? w >> 2 : NW) : CFG_MAP1 == 1 ? (w & 2 ? (w >> 2) * 2 + (w & 1) : NW) : w - P1W;
        static_assert(CFG_MAP1 == 0 ? (P1W <= NW / 4 * 3 && NF + 2 <= NW / 4) : CFG_MAP1 == 1 ? (P1W <= NW / 2 && NF + 2 <= NW / 2) : true, "warp map");
        for (int i = tid; i < NF * GPW * 32; i += NT) sts32(sb + A_CNT + i * 4, 1u << 24);
        if (tid < 64) sts32(sb + SM_CRED + tid * 4, 0u);
        cta_sync();
        TR(1, tid == 0);
        if (ww < P1W) role_p1(p, sb, id, ww, lane);
        else if (sw < NF) role_flush(p, sb, id, sw, lane);
        else if (sw == NF) role_credit1(p, sb, id, lane);
        else if (w == NW - 1) {
            uint4* owin = (uint4*)(p.ring + (CWIN + (lds32(sb + SM_MISC + 16) ^ 1)) * WIN);
            for (int i = id * 32 + lane; i < CPAIRS * 512; i += N1 * 32) __stcg(owin + i, make_uint4(0, 0, 0, 0));
            __syncwarp();
        }
    } else if (role == 1) {
        const int row0 = id % H2 * p.rows2;
        const int nrows = min((int)p.rows2, p.E - row0);
        constexpr int NTB = NT - 32, TBD = CFG_TBD;
        bool flagged = false;
        if (w < NW - 1) {
            const uint4* const src = (const uint4*)(p.m + row0);
            uint4 r2[TBD], nx[TBD];
            auto fetch = [&](int i) {
#pragma unroll
                for (int k = 0; k < TBD; k++)
                    asm volatile("ld.global.nc.v4.u32 {%0,%1,%2,%3}, [%4];" : "=r"(nx[k].x), "=r"(nx[k].y), "=r"(nx[k].z), "=r"(nx[k].w) : "l"(src + min(i + k * NTB, nrows / 2 - 1)));
            };
            fetch(tid);
            const Scale sc = get_scale(sb);
            const Mat4 wd = load_mat4(p.w_down, lane);
            Mat4 ws;
#pragma unroll
            for (int k = 0; k < 4; k++) ws.b[k] = mul_bf2(wd.b[k], ((246u - (lane & 4 ? sc.eb[(k & 2) + 1] : sc.eb[k & 2])) << 7) * 0x10001u);
#pragma unroll 1
            for (int i0 = tid; 2 * (i0 - lane) < nrows; i0 += TBD * NTB) {
#pragma unroll
                for (int k = 0; k < TBD; k++) r2[k] = make_uint4(nx[k].x, nx[k].z, nx[k].y, nx[k].w);
                fetch(i0 + TBD * NTB);
#pragma unroll
                for (int k = 0; k < TBD; k++) {
                    const int i = i0 + k * NTB;
                    float y[8];
                    mul4(make_uint4(r2[k].x, r2[k].z, r2[k].y, r2[k].w), ws, y);
                    uint32_t a[4], h[4], ta[2];
#pragma unroll
                    for (int j = 0; j < 4; j++) { a[j] = pack_h2(y[2 * j], y[2 * j + 1]); h[j] = a[j] + 0x00040004u; }
#pragma unroll
                    for (int j = 0; j < 2; j++) ta[j] = bitsel(h[2 * j], bitsel(h[2 * j + 1] >> 3, h[2 * j + 1] << 7, 0x00070007u), 0x9ff89ff8u);
                    uint32_t tb = prmt(h[1], h[3], 0x7531);
                    const uint32_t b0 = a[0] | a[1] | h[0] | h[1], b1 = a[2] | a[3] | h[2] | h[3];
                    if (__any_sync(0xffffffffu, ((b0 | b1) & 0x60006000u) || sc.allslow)) {
                        if ((b0 & 0x60006000u) || sc.allslow) { ta[0] = 0; tb = (tb & 0xffff0000u) | 0x40u; }
                        if ((b1 & 0x60006000u) || sc.allslow) { ta[1] = 0; tb = (tb & 0xffffu) | 0x400000u; }
                        flagged = true;
                    }
                    sts64_if(sb + B_TA + i * 8, ta[0], ta[1], 2 * i < nrows);
                    sts32_if(sb + B_TB + i * 4, tb, 2 * i < nrows);
                }
            }
            if (tid == 0) {
                sts32(sb + B_TA + p.rows2 * 4, 0u);
                sts16(sb + B_TB + p.rows2 * 2, 0u);
            }
            TR(8, tid == 0);
        } else if (lane == 0) spin_ge(rdy_of(p, sb, id, id / H2), H3);
        __syncwarp();
        flagged = __any_sync(0xffffffffu, __syncthreads_or(flagged));
        TR(1, tid == 0);
        if (w < P2W) {
            if (flagged) role_p2<true>(p, sb, id, w, lane);
            else role_p2<false>(p, sb, id, w, lane);
        } else if (w == P2W) role_credit(p, sb, id, lane);
    } else {
        if (w == 0) clear_queues<false>(p, sb, id, lane);
        if (tid >= 32 && tid < 33 + NPC) mbar_init(sb + SM_CNT2 + (tid - 32) * 8, 1);
        cta_sync();
        TR(1, tid == 0);
        if (w < P3W) role_p3(p, sb, id, w, lane);
        const int pc = w - P3W, n = min(((int)p.rows3 + 7) / 8 * 8 - pc * RPC, RPC);
        uint32_t *f0 = nullptr, *f1 = nullptr;
        if (pc >= 0) { f0 = opaque(rdy_of(p, sb, 160 + 32 * pc, 0)); f1 = opaque(rdy_of(p, sb, 160 + 32 * pc, 1)); }
        cta_sync();
        TR(2, tid == 0);
        if (pc >= 0 && pc < NPC && lane == 0) {
            fence_async_smem();
            if (pc >= CFG_DOUT) mbar_wait(sb + SM_CNT2 + (pc + 1 - CFG_DOUT) * 8, 0);
            if (n > 0) {
                bulk_store(g_S[0][id] + pc * RPC, sb + C_S + pc * RPC * 4, n * 4);
                bulk_store(g_S[1][id] + pc * RPC, sb + C_S + (ROWS3_MAX + pc * RPC) * 4, n * 4);
            }
            asm volatile("cp.async.bulk.commit_group;" ::: "memory");
            asm volatile("cp.async.bulk.wait_group.read 0;" ::: "memory");
            mbar_arrive(sb + SM_CNT2 + pc * 8 + 8);
            asm volatile("cp.async.bulk.wait_group 0;" ::: "memory");
            fence_gpu();
            red_rlx(f0, 1u);
            red_rlx(f1, 1u);
            if (id == 0 && pc == 0) red_rlx(&g_epoch, 1u);
            TR(12 + pc, true);
        }
        return;
    }
    cta_sync();
    TR(18, tid == 0 && role == 1);
    if (role == 0 && w == NW - 2) clear_queues<true>(p, sb, id, lane);
    tail_rows(p, role * N1 + id, w, lane);
}

__global__ void k_direct(const Params p, long long T) {
    float wd[16];
#pragma unroll
    for (int i = 0; i < 16; i++) wd[i] = __bfloat162float(p.w_down[i]);
    const float f = __bfloat162float(p.freq[0]);
    for (long long t = blockIdx.x * (long long)blockDim.x + threadIdx.x; t < T; t += (long long)gridDim.x * blockDim.x) {
        float x = __bfloat162float(__float2bfloat16(f * __bfloat162float(p.angle[t])));
        float c = __bfloat162float(__float2bfloat16(cosf(x)));
        uint2 md = down_row(__ldg(p.m + p.idx_in[t]), wd);
        red_v4(g_Sg + p.idx_out[t], c * bflo(md.x), c * bfhi(md.x), c * bflo(md.y), c * bfhi(md.y));
    }
}
__global__ void k_direct_tail(const Params p) {
    __shared__ __align__(16) float sw[96];
    load_tail_weights(p, sw, threadIdx.x);
    __syncthreads();
    uint32_t c2[4];
#pragma unroll
    for (int i = 0; i < 4; i++) c2[i] = ((const uint32_t*)p.centers)[i];
    for (int e = blockIdx.x * blockDim.x + threadIdx.x; e < p.E; e += gridDim.x * blockDim.x) {
        float4 g = __ldcg(g_Sg + e);
        __stcg(g_Sg + e, make_float4(0.f, 0.f, 0.f, 0.f));
        const float Sv[4] = {g.x, g.y, g.z, g.w};
        float4 gs, gr;
        row_gates(sw, c2, __bfloat16_as_ushort(p.dist[e]), gs, gr);
        p.out[e] = finish_row(sw + 64, gs, gr, Sv, __ldg(p.m + e));
    }
}

static bool pick_rows(int E, int n, int rows_max, int mult, uint32_t* rows, uint32_t* magic) {
    for (uint32_t r = (E + n - 1) / n; r <= (uint32_t)rows_max; r++) {
        if (r < 2 || r % mult) continue;
        uint64_t mg = ((1ull << 32) + r - 1) / r;
        uint64_t err = mg * r - (1ull << 32);
        if (err * (uint64_t)n < mg) { *rows = r; *magic = (uint32_t)mg; return true; }
    }
    return false;
}

}

extern "C" void kernel_launch(void* const* d_in, const int* in_sizes, int n_in, void* d_out, int out_size) {
    using namespace gs;
    (void)n_in; (void)out_size;
    Params p;
    p.m = (const uint2*)d_in[0];
    p.idx_in = (const int*)d_in[1];
    p.idx_out = (const int*)d_in[2];
    p.dist = (const __nv_bfloat16*)d_in[3];
    p.angle = (const __nv_bfloat16*)d_in[4];
    p.centers = (const __nv_bfloat16*)d_in[5];
    p.freq = (const __nv_bfloat16*)d_in[6];
    p.w_rbf = (const __nv_bfloat16*)d_in[7];
    p.w_sbf = (const __nv_bfloat16*)d_in[8];
    p.w_down = (const __nv_bfloat16*)d_in[9];
    p.w_up = (const __nv_bfloat16*)d_in[10];
    p.out = (uint2*)d_out;
    p.E = in_sizes[3];
    const long long T = in_sizes[1];
    p.n4 = (int)(T / 4);
    p.rows2 = p.magic2 = 0;
    p.ring = nullptr;

    static int sms = 0, rsv = 0;
    if (!sms) {
        int dev = 0;
        cudaGetDevice(&dev);
        cudaDeviceGetAttribute(&rsv, cudaDevAttrReservedSharedMemoryPerBlock, dev);
        cudaDeviceGetAttribute(&sms, cudaDevAttrMultiProcessorCount, dev);
        cudaFuncSetAttribute(k_main, cudaFuncAttributeMaxDynamicSharedMemorySize, SMEM_BYTES);
    }
    cudaStream_t st = cudaStreamPerThread;
    bool fast = (T % 4 == 0) && T > 0 && sms >= NCTA && rsv == (int)SB && p.E >= 65536 && p.E <= E_MAX &&
                p.E % 4 == 0 && (((uintptr_t)p.m | (uintptr_t)p.idx_in | (uintptr_t)p.idx_out | (uintptr_t)p.angle) & 15) == 0 &&
                pick_rows(p.E, NI, ROWS2_MAX, 2, &p.rows2, &p.magic2);
    p.nrows2 = 0u - p.rows2;
    p.rows3 = (p.E + 31) / 32;
    fast = fast && (p.rows2 * (NI - 1) + 2 <= (uint32_t)p.E);
    static const void* tkey[3] = {nullptr, nullptr, nullptr};
    static cudaTextureObject_t tex[3] = {0, 0, 0};
    static long long tlen = -1;
    const void* tptr[3] = {p.idx_in, p.idx_out, p.angle};
    for (int k = 0; fast && k < 3; k++) {
        if (tkey[k] == tptr[k] && tlen == T) continue;
        if (tkey[k]) cudaDestroyTextureObject(tex[k]);
        tkey[k] = nullptr;
        cudaResourceDesc rd = {};
        rd.resType = cudaResourceTypeLinear;
        rd.res.linear.devPtr = (void*)tptr[k];
        rd.res.linear.desc = cudaCreateChannelDesc(32, 32, k < 2 ? 32 : 0, k < 2 ? 32 : 0, cudaChannelFormatKindUnsigned);
        rd.res.linear.sizeInBytes = (size_t)T * (k < 2 ? 4 : 2);
        cudaTextureDesc td = {};
        td.readMode = cudaReadModeElementType;
        if (cudaCreateTextureObject(&tex[k], &rd, &td, nullptr) == cudaSuccess) tkey[k] = tptr[k];
        else { (void)cudaGetLastError(); fast = false; }
    }
    if (fast) tlen = T;
    p.t_in = tex[0]; p.t_out = tex[1]; p.t_ang = tex[2];
    if (fast) {
        void* ring = nullptr;
        cudaGetSymbolAddress(&ring, g_ring);
        uintptr_t a = ((uintptr_t)ring + WIN - 1) & ~(uintptr_t)(WIN - 1);
        if (a >> 32 != (a + RING_BYTES - 1) >> 32) a += RING_BYTES;
        p.ring = (unsigned char*)a;
        p.ring_lo = (uint32_t)a;
        p.ring_hi = (uint32_t)(a >> 32);
        k_main<<<NCTA, NT, SMEM_BYTES, st>>>(p);
    } else {
        k_direct<<<sms * 8, 256, 0, st>>>(p, T);
        k_direct_tail<<<sms * 4, 256, 0, st>>>(p);
    }
}
```

```cpp
#include <cuda_runtime.h>
#include <cuda_bf16.h>
#include <stdint.h>

#define CFG_N1 56
#define CFG_NI 22
#define CFG_NW 28
#define CFG_P1W 14
#define CFG_GPW 2
#define CFG_KR 1
#define CFG_QPW 3
#define CFG_TG 2
#define CFG_PMASK 8
#define CFG_PSTREAK 1
#define CFG_NBT 1
#define CFG_KM 5
#define CFG_KN 9
#define CFG_TBD 3
#define CFG_P0 500
#define CFG_PFD 200
#define CFG_C1SLEEP 200
#define CFG_PK1 6
#define CFG_PK2 8
#define CFG_PK3 11
#define CFG_CLN 8
#define CFG_CLS 500
#define CFG_DOUT 2
#define CFG_TH 14
#define CFG_TS 200
#define CFG_POLL 64
#define CFG_HINT 20000
#define CFG_BSLEEP 100
#define CFG_CSLEEP 200
#define CFG_FSLEEP 100
#define CFG_PSLEEP 100
#define CFG_DRY 1
#define CFG_PROBES 4

namespace gs {

constexpr int E_MAX = 640000;
constexpr int N1 = CFG_N1, NI = CFG_NI, N2 = 2 * NI, N3 = 32, NCTA = N1 + N2 + N3;
constexpr int H2 = NI, H3 = N3 / 2;
constexpr int NB = NI * N3;
constexpr int NW = CFG_NW, NT = NW * 32;
constexpr int GPW = CFG_GPW, NF = (NI + GPW - 1) / GPW;
constexpr int QPW = CFG_QPW, NBT = CFG_NBT;
constexpr int P1W = CFG_P1W, P2W = (N1 + QPW - 1) / QPW, P3W = NI;
constexpr int NQ2 = 64;
constexpr int ROWS2_MAX = ((E_MAX + NI - 1) / NI + 31) / 8 * 8;
constexpr int ROWS3_MAX = (E_MAX / 32 + 31) / 32 * 32;
constexpr int NTAIL = N1 + N2;
constexpr int NPC = 5, WPP = 5, RPC = NTAIL * WPP * 8;
constexpr int GUARD = 1 << 26;
static_assert(NCTA % 4 == 0 && NCTA <= 192, "roles come in CTA pairs, per partition");
static_assert((GPW == 2 || GPW == 4) && QPW >= NBT && QPW <= 4 && NI <= 32 && N1 <= 62, "queue ownership");
static_assert(P1W + NF + 2 <= NW && P2W + 2 <= NW && P3W + 5 <= NW && P1W * 256 + 64 < 8192, "warp roles");
static_assert(ROWS2_MAX + 8 <= 32768 && ROWS3_MAX <= 32768, "index bits");

constexpr uint32_t SB = 1024;
constexpr int SM_DONE = 0, SM_DONE2 = 8;
constexpr int SM_MISC = 16;
constexpr int SM_FIN = 48;
constexpr int SM_STAT = 64;
constexpr int SM_CNT2 = 128;
constexpr int SM_W = 256;
constexpr int SM_PUB = SM_W + 384;
constexpr int SM_PROBE = SM_PUB + 768;
constexpr int SM_CRED = 1792;
constexpr int SM_DATA = 2048;
constexpr int cmax(int a, int b) { return a > b ? a : b; }
constexpr int A_CNT = SM_DATA;
constexpr int KR = CFG_KR, LISTB = (GPW * 32 + 8 * KR) * 4;
constexpr int A_LIST = A_CNT + NF * GPW * 128;
constexpr int A_ST = (A_LIST + NF * LISTB + 127) / 128 * 128;
constexpr int A_END = A_ST + NB * 256;
constexpr int B_TB = SM_DATA;
constexpr int B_TA = SM_DATA + (ROWS2_MAX + 8) * 2;
constexpr int B_END = SM_DATA + (ROWS2_MAX + 8) * 6;
constexpr int C_S = SM_DATA;
constexpr int C_END = C_S + ROWS3_MAX * 8;
constexpr int T_G = SM_DATA, TWB = 4096 + 2048 + 512, T_END = T_G + NPC * WPP * TWB;
constexpr int ZEND = cmax(A_END, C_END);
constexpr int SM_ZERO = (cmax(C_END, T_END) + 127) / 128 * 128;
constexpr int SMEM_BYTES = cmax(cmax(A_END, B_END), SM_ZERO + 4096);
static_assert(SMEM_BYTES <= 232448 && SM_PROBE + 128 <= SM_CRED, "shared memory");
static_assert(NPC * RPC >= ROWS3_MAX && NPC * WPP + 2 <= NW, "tail");

constexpr uint32_t FIN = 0x80000000u;

constexpr uint32_t WIN = 524288;
constexpr int CWIN = N2 + N3, NWIN = CWIN + 2, CPAIRS = 31;
constexpr uint32_t PROBE_OFF = (uint32_t)NWIN * WIN;
constexpr int NPROBE = 16;
static_assert(NWIN <= NCTA && NPROBE <= NW, "windows");
constexpr size_t RING_BYTES = (size_t)PROBE_OFF + WIN;
__device__ __align__(128) unsigned char g_ring[2 * RING_BYTES + WIN];
__device__ __align__(128) uint32_t g_S[2][32][ROWS3_MAX];
__device__ __align__(128) float4 g_Sg[E_MAX];
__device__ uint32_t g_dirty[E_MAX / 32];
__device__ uint32_t g_epoch;

#define TR(ev, on)
#define ACC_DECL
#define ACC(i, n)
#define ACC_SAVE

struct Params {
    const uint2* m;
    const int* idx_in;
    const int* idx_out;
    const __nv_bfloat16* dist;
    const __nv_bfloat16* angle;
    const __nv_bfloat16* centers;
    const __nv_bfloat16* freq;
    const __nv_bfloat16* w_rbf;
    const __nv_bfloat16* w_sbf;
    const __nv_bfloat16* w_down;
    const __nv_bfloat16* w_up;
    uint2* out;
    unsigned char* ring;
    cudaTextureObject_t t_in, t_out, t_ang;
    int E, n4;
    uint32_t rows2, nrows2, magic2, rows3;
    uint32_t ring_lo, ring_hi;
};

__device__ __forceinline__ float bflo(uint32_t w) { return __uint_as_float(w << 16); }
__device__ __forceinline__ float bfhi(uint32_t w) { return __uint_as_float(w & 0xffff0000u); }
__device__ __forceinline__ uint32_t pack_bf2(float lo, float hi) {
    uint32_t r;
    asm("cvt.rn.bf16x2.f32 %0, %1, %2;" : "=r"(r) : "f"(hi), "f"(lo));
    return r;
}
__device__ __forceinline__ uint32_t mul_bf2(uint32_t a, uint32_t b) {
    uint32_t r;
    asm("mul.rn.bf16x2 %0, %1, %2;" : "=r"(r) : "r"(a), "r"(b));
    return r;
}
__device__ __forceinline__ uint32_t sub_bf2(uint32_t a, uint32_t b) {
    uint32_t r;
    asm("sub.rn.bf16x2 %0, %1, %2;" : "=r"(r) : "r"(a), "r"(b));
    return r;
}
__device__ __forceinline__ uint32_t maxabs_bf2(uint32_t a, uint32_t b) {
    uint32_t r;
    asm("max.NaN.xorsign.abs.bf16x2 %0, %1, %2;" : "=r"(r) : "r"(a), "r"(b));
    return r;
}
__device__ __forceinline__ void mbar_init(uint32_t a, uint32_t n) {
    asm volatile("mbarrier.init.shared::cta.b64 [%0], %1;" ::"r"(a), "r"(n) : "memory");
}
__device__ __forceinline__ void mbar_arrive(uint32_t a) {
    asm volatile("mbarrier.arrive.shared::cta.b64 _, [%0];" ::"r"(a) : "memory");
}
__device__ __forceinline__ void mbar_arrive_if(uint32_t a, bool on) {
    asm volatile("{.reg .pred q; setp.ne.u32 q, %1, 0; @q mbarrier.arrive.shared::cta.b64 _, [%0];}" ::"r"(a), "r"((uint32_t)on) : "memory");
}
__device__ __forceinline__ void mbar_wait(uint32_t a, uint32_t parity) {
    uint32_t ok;
    int guard = 0;
    do {
        asm volatile("{.reg .pred p; mbarrier.try_wait.parity.shared::cta.b64 p, [%1], %2, %3; selp.u32 %0, 1, 0, p;}"
                     : "=r"(ok) : "r"(a), "r"(parity), "r"(CFG_HINT) : "memory");
        if (!ok) {
            if (++guard > GUARD) __trap();
        }
    } while (!ok);
}
__device__ __forceinline__ void cta_sync() { __syncwarp(); __syncthreads(); }
__device__ __forceinline__ void bar_sync(int id, int n) { asm volatile("bar.sync %0, %1;" ::"r"(id), "r"(n) : "memory"); }
__device__ __forceinline__ bool mbar_test(uint32_t a, uint32_t parity) {
    uint32_t ok;
    asm volatile("{.reg .pred p; mbarrier.test_wait.parity.shared::cta.b64 p, [%1], %2; selp.u32 %0, 1, 0, p;}"
                 : "=r"(ok) : "r"(a), "r"(parity) : "memory");
    return ok;
}
__device__ __forceinline__ uint32_t ld_acq(const uint32_t* p) {
    uint32_t v;
    asm volatile("ld.acquire.gpu.global.u32 %0, [%1];" : "=r"(v) : "l"(p) : "memory");
    return v;
}
__device__ __forceinline__ uint32_t ld_rlx(const uint32_t* p) {
    uint32_t v;
    asm volatile("ld.relaxed.gpu.global.u32 %0, [%1];" : "=r"(v) : "l"(p) : "memory");
    return v;
}
__device__ __forceinline__ void st_rlx(uint32_t* p, uint32_t v) {
    asm volatile("st.relaxed.gpu.global.u32 [%0], %1;" ::"l"(p), "r"(v) : "memory");
}
__device__ __forceinline__ void red_rlx(uint32_t* p, uint32_t v) {
    asm volatile("red.relaxed.gpu.global.add.u32 [%0], %1;" ::"l"(p), "r"(v) : "memory");
}
__device__ __forceinline__ uint32_t spin_ge(const uint32_t* p, uint32_t target) {
    int guard = 0;
    while (ld_rlx(p) < target) {
        __nanosleep(CFG_POLL);
        if (++guard > GUARD) __trap();
    }
    return ld_acq(p);
}
__device__ __forceinline__ void fence_gpu() { asm volatile("fence.acq_rel.gpu;" ::: "memory"); }
__device__ __forceinline__ void fence_async_smem() { asm volatile("fence.proxy.async.shared::cta;" ::: "memory"); }
__device__ __forceinline__ void fence_async_all() { asm volatile("fence.proxy.async;" ::: "memory"); }
__device__ __forceinline__ void bulk_store(void* g, uint32_t s, uint32_t bytes) {
    asm volatile("cp.async.bulk.global.shared::cta.bulk_group [%0], [%1], %2;" ::"l"(g), "r"(s), "r"(bytes) : "memory");
}
__device__ __forceinline__ void cp16(uint32_t s, const void* g, bool on) {
    asm volatile("{.reg .pred q; setp.ne.u32 q, %2, 0; @q cp.async.cg.shared.global [%0], [%1], 16;}" ::"r"(s), "l"(g), "r"((uint32_t)on) : "memory");
}
__device__ __forceinline__ void cp16z(uint32_t s, const void* g, int bytes) {
    asm volatile("cp.async.cg.shared.global [%0], [%1], 16, %2;" ::"r"(s), "l"(g), "r"(bytes) : "memory");
}
__device__ __forceinline__ void cp_commit() { asm volatile("cp.async.commit_group;" ::: "memory"); }
template <int N> __device__ __forceinline__ void cp_wait() { asm volatile("cp.async.wait_group %0;" ::"n"(N) : "memory"); }
__device__ __forceinline__ uint32_t atoms_add(uint32_t a, uint32_t v) {
    uint32_t o;
    asm volatile("atom.shared.add.u32 %0, [%1], %2;" : "=r"(o) : "r"(a), "r"(v) : "memory");
    return o;
}
__device__ __forceinline__ void sts32(uint32_t a, uint32_t v) { asm volatile("st.shared.u32 [%0], %1;" ::"r"(a), "r"(v) : "memory"); }
__device__ __forceinline__ void sts16(uint32_t a, uint32_t v) { asm volatile("st.shared.u16 [%0], %1;" ::"r"(a), "h"((uint16_t)v) : "memory"); }
__device__ __forceinline__ void sts64(uint32_t a, uint32_t x, uint32_t y) { asm volatile("st.shared.v2.u32 [%0], {%1,%2};" ::"r"(a), "r"(x), "r"(y) : "memory"); }
__device__ __forceinline__ uint32_t lds32(uint32_t a) {
    uint32_t v;
    asm volatile("ld.shared.u32 %0, [%1];" : "=r"(v) : "r"(a) : "memory");
    return v;
}
__device__ __forceinline__ uint2 lds64v(uint32_t a) {
    uint2 v;
    asm volatile("ld.volatile.shared.v2.u32 {%0,%1}, [%2];" : "=r"(v.x), "=r"(v.y) : "r"(a) : "memory");
    return v;
}
__device__ __forceinline__ uint32_t lds32v(uint32_t a) {
    uint32_t v;
    asm volatile("ld.volatile.shared.u32 %0, [%1];" : "=r"(v) : "r"(a) : "memory");
    return v;
}
__device__ __forceinline__ uint4 lds128(uint32_t a) {
    uint4 v;
    asm volatile("ld.shared.v4.u32 {%0,%1,%2,%3}, [%4];" : "=r"(v.x), "=r"(v.y), "=r"(v.z), "=r"(v.w) : "r"(a) : "memory");
    return v;
}
__device__ __forceinline__ void sts128(uint32_t a, uint4 v) {
    asm volatile("st.shared.v4.u32 [%0], {%1,%2,%3,%4};" ::"r"(a), "r"(v.x), "r"(v.y), "r"(v.z), "r"(v.w) : "memory");
}
#define LD_Q "ld.relaxed.gpu.global"
__device__ __forceinline__ uint4 ldg_q128(const void* p) {
    uint4 v;
    asm volatile(LD_Q ".v4.u32 {%0,%1,%2,%3}, [%4];"
                 : "=r"(v.x), "=r"(v.y), "=r"(v.z), "=r"(v.w) : "l"(p) : "memory");
    return v;
}
__device__ __forceinline__ uint2 ldg_q64(const void* p) {
    uint2 v;
    asm volatile(LD_Q ".v2.u32 {%0,%1}, [%2];" : "=r"(v.x), "=r"(v.y) : "l"(p) : "memory");
    return v;
}
__device__ __forceinline__ void red_v4(float4* p, float a, float b, float c, float d) {
    asm volatile("red.global.add.v4.f32 [%0], {%1,%2,%3,%4};" ::"l"(p), "f"(a), "f"(b), "f"(c), "f"(d) : "memory");
}
__device__ __forceinline__ uint2 down_row(uint2 r, const float* wd) {
    float x0 = bflo(r.x), x1 = bfhi(r.x), x2 = bflo(r.y), x3 = bfhi(r.y);
    float y[4];
#pragma unroll
    for (int j = 0; j < 4; j++) y[j] = x0 * wd[j] + x1 * wd[4 + j] + x2 * wd[8 + j] + x3 * wd[12 + j];
    return make_uint2(pack_bf2(y[0], y[1]), pack_bf2(y[2], y[3]));
}
__device__ __forceinline__ uint32_t prmt(uint32_t a, uint32_t b, uint32_t s) {
    uint32_t r;
    asm("prmt.b32 %0, %1, %2, %3;" : "=r"(r) : "r"(a), "r"(b), "r"(s));
    return r;
}
__device__ __forceinline__ uint32_t bitsel(uint32_t a, uint32_t b, uint32_t m) {
    uint32_t r;
    asm("lop3.b32 %0, %1, %2, %3, 0xE4;" : "=r"(r) : "r"(a), "r"(b), "r"(m));
    return r;
}
__device__ __forceinline__ uint32_t pack_h2(float lo, float hi) {
    uint32_t r;
    asm("cvt.rn.f16x2.f32 %0, %1, %2;" : "=r"(r) : "f"(hi), "f"(lo));
    return r;
}
__device__ __forceinline__ uint32_t mul_h2(uint32_t a, uint32_t b) {
    uint32_t r;
    asm("mul.rn.f16x2 %0, %1, %2;" : "=r"(r) : "r"(a), "r"(b));
    return r;
}
__device__ __forceinline__ uint32_t lds32nv(uint32_t a) {
    uint32_t v;
    asm volatile("ld.shared.u32 %0, [%1];" : "=r"(v) : "r"(a));
    return v;
}
__device__ __forceinline__ uint32_t lds16nv(uint32_t a) {
    uint32_t v;
    asm volatile("ld.shared.u16 %0, [%1];" : "=r"(v) : "r"(a));
    return v;
}
#define ST_Q "st.relaxed.gpu.global"
__device__ __forceinline__ void stg_q128(void* p, uint32_t a, uint32_t b, uint32_t c, uint32_t d, bool on) {
    asm volatile("{.reg .pred q; setp.ne.u32 q, %5, 0; @q " ST_Q ".v4.u32 [%0], {%1,%2,%3,%4};}"
                 ::"l"(p), "r"(a), "r"(b), "r"(c), "r"(d), "r"((uint32_t)on) : "memory");
}
__device__ __forceinline__ void stg_q64(void* p, uint32_t a, uint32_t b, bool on) {
    asm volatile("{.reg .pred q; setp.ne.u32 q, %3, 0; @q " ST_Q ".v2.u32 [%0], {%1,%2};}"
                 ::"l"(p), "r"(a), "r"(b), "r"((uint32_t)on) : "memory");
}
__device__ __forceinline__ void st_rlx_if(uint32_t* p, uint32_t v, bool on) {
    asm volatile("{.reg .pred q; setp.ne.u32 q, %2, 0; @q st.relaxed.gpu.global.u32 [%0], %1;}" ::"l"(p), "r"(v), "r"((uint32_t)on) : "memory");
}
__device__ __forceinline__ void ldq128_keep(uint4& v, const void* p, bool on) {
    asm volatile("{.reg .pred q; setp.ne.u32 q, %5, 0; @q ld.relaxed.gpu.global.v4.u32 {%0,%1,%2,%3}, [%4];}"
                 : "+r"(v.x), "+r"(v.y), "+r"(v.z), "+r"(v.w) : "l"(p), "r"((uint32_t)on) : "memory");
}
__device__ __forceinline__ void atoms_add_keep(uint32_t& o, uint32_t a, uint32_t v, bool on) {
    asm volatile("{.reg .pred q; setp.ne.u32 q, %3, 0; @q atom.shared.add.u32 %0, [%1], %2;}" : "+r"(o) : "r"(a), "r"(v), "r"((uint32_t)on) : "memory");
}
__device__ __forceinline__ void reds_add(uint32_t a, uint32_t v) { asm volatile("red.shared.add.u32 [%0], %1;" ::"r"(a), "r"(v) : "memory"); }
__device__ __forceinline__ void sts32_if(uint32_t a, uint32_t v, bool on) {
    asm volatile("{.reg .pred q; setp.ne.u32 q, %2, 0; @q st.shared.u32 [%0], %1;}" ::"r"(a), "r"(v), "r"((uint32_t)on) : "memory");
}
__device__ __forceinline__ void sts64_if(uint32_t a, uint32_t x, uint32_t y, bool on) {
    asm volatile("{.reg .pred q; setp.ne.u32 q, %3, 0; @q st.shared.v2.u32 [%0], {%1,%2};}" ::"r"(a), "r"(x), "r"(y), "r"((uint32_t)on) : "memory");
}
__device__ __forceinline__ void lds128_keep(uint4& v, uint32_t a, bool on) {
    asm volatile("{.reg .pred q; setp.ne.u32 q, %5, 0; @q ld.volatile.shared.v4.u32 {%0,%1,%2,%3}, [%4];}"
                 : "+r"(v.x), "+r"(v.y), "+r"(v.z), "+r"(v.w) : "r"(a), "r"((uint32_t)on) : "memory");
}
__device__ __forceinline__ void or3_if(uint32_t& x, uint32_t a, uint32_t b, bool on) {
    asm("{.reg .pred q; setp.ne.u32 q, %3, 0; @q lop3.b32 %0, %0, %1, %2, 0xfe;}" : "+r"(x) : "r"(a), "r"(b), "r"((uint32_t)on));
}
__device__ __forceinline__ uint32_t clk() {
    uint32_t t;
    asm volatile("mov.u32 %0, %%clock;" : "=r"(t) :: "memory");
    return t;
}
__device__ __forceinline__ void sg_add(int row, float a, float b, float c, float d) {
    red_v4(g_Sg + row, a, b, c, d);
    st_rlx(g_dirty + (row >> 5), 1u);
}
__device__ __forceinline__ void slow_add(const uint2* m, uint32_t sb, int in, int out, float c) {
    const uint2 r = __ldg(m + in);
    const float x[4] = {bflo(r.x), bfhi(r.x), bflo(r.y), bfhi(r.y)};
    float y[4] = {0.f, 0.f, 0.f, 0.f};
#pragma unroll
    for (int k = 0; k < 4; k++) {
        const uint4 q = lds128(sb + SM_W + 320 + k * 16);
        y[0] = k ? y[0] + x[k] * __uint_as_float(q.x) : x[k] * __uint_as_float(q.x);
        y[1] = k ? y[1] + x[k] * __uint_as_float(q.y) : x[k] * __uint_as_float(q.y);
        y[2] = k ? y[2] + x[k] * __uint_as_float(q.z) : x[k] * __uint_as_float(q.z);
        y[3] = k ? y[3] + x[k] * __uint_as_float(q.w) : x[k] * __uint_as_float(q.w);
    }
    const uint32_t lo = pack_bf2(y[0], y[1]), hi = pack_bf2(y[2], y[3]);
    sg_add(out, c * bflo(lo), c * bfhi(lo), c * bflo(hi), c * bfhi(hi));
}

struct Mat4 { uint32_t b[4]; };
__device__ __forceinline__ Mat4 load_mat4(const __nv_bfloat16* w, int lane) {
    const unsigned short* u = (const unsigned short*)w + (lane >> 2 & 1);
    const bool on = lane >> 3 == (lane & 3);
    Mat4 m;
#pragma unroll
    for (int k = 0; k < 4; k++) m.b[k] = on ? u[(k & 1) * 8 + (k & 2)] | (uint32_t)u[(k & 1) * 8 + 4 + (k & 2)] << 16 : 0u;
    return m;
}
__device__ __forceinline__ void mul4(const uint4& x, const Mat4& m, float (&y)[8]) {
    asm("mma.sync.aligned.m16n8k16.row.col.f32.bf16.bf16.f32 {%0,%1,%2,%3}, {%8,%9,%10,%11}, {%12,%13}, {%16,%16,%16,%16};\n\t"
        "mma.sync.aligned.m16n8k16.row.col.f32.bf16.bf16.f32 {%4,%5,%6,%7}, {%8,%9,%10,%11}, {%14,%15}, {%16,%16,%16,%16};"
        : "=&f"(y[0]), "=&f"(y[1]), "=&f"(y[4]), "=&f"(y[5]), "=&f"(y[2]), "=&f"(y[3]), "=&f"(y[6]), "=&f"(y[7])
        : "r"(x.x), "r"(x.z), "r"(x.y), "r"(x.w), "r"(m.b[0]), "r"(m.b[1]), "r"(m.b[2]), "r"(m.b[3]), "f"(0.f));
}

struct Scale { uint32_t eb[4]; bool allslow; };
__device__ __forceinline__ void md_stats(const uint4& in, const Mat4& wd, int lane) {
    float y[8];
    mul4(in, wd, y);
    uint32_t mx[4], se[4];
#pragma unroll
    for (int c = 0; c < 4; c++) {
        uint32_t a = __float_as_uint(y[c]) & 0x7fffffffu, b = __float_as_uint(y[4 + c]) & 0x7fffffffu;
        if (a >= 0x7f800000u) a = 0;
        if (b >= 0x7f800000u) b = 0;
        mx[c] = __reduce_max_sync(0xffffffffu, max(a, b));
        se[c] = __reduce_add_sync(0xffffffffu, (a >> 23) + (b >> 23) + (a ? 1u << 20 : 0u) + (b ? 1u << 20 : 0u));
    }
    if (lane < 4) {
        asm volatile("red.shared.max.u32 [%0], %1;" ::"r"(SB + SM_STAT + lane * 4), "r"(lane == 0 ? mx[0] : lane == 1 ? mx[1] : lane == 2 ? mx[2] : mx[3]) : "memory");
        reds_add(SB + SM_STAT + 16 + lane * 4, lane == 0 ? se[0] : lane == 1 ? se[1] : lane == 2 ? se[2] : se[3]);
    }
}
__device__ __forceinline__ Scale get_scale(uint32_t sb) {
    Scale s;
    s.allslow = false;
#pragma unroll
    for (int k = 0; k < 4; k++) {
        const uint32_t mx = lds32(sb + SM_STAT + 4 * k), se = lds32(sb + SM_STAT + 16 + 4 * k);
        const uint32_t mean = (uint32_t)__fdividef((float)(se & 0xfffffu), (float)max(se >> 20, 1u));
        uint32_t eb = min(min((mx + 0x6e0000u) >> 23, mean + 5u), 227u);
        if (eb < 27u) { s.allslow = s.allslow || mx != 0; eb = 27u; }
        if (eb > 170u) s.allslow = true;
        s.eb[k] = eb;
    }
    return s;
}

__device__ __forceinline__ uint32_t probe_rt(uint32_t* p) {
    uint32_t best = 0xffffffffu;
#pragma unroll 1
    for (int r = 0; r < CFG_PROBES; r++) {
        const uint32_t t0 = clock();
        uint32_t v;
        asm volatile("atom.relaxed.gpu.global.add.u32 %0, [%1], 1;" : "=r"(v) : "l"(p) : "memory");
        if (v > 100000u) __trap();
        const uint32_t t1 = clock();
        best = min(best, t1 - t0);
    }
    return best;
}
__device__ __forceinline__ uint32_t* pub_ptr(const Params& p, int blk, uint32_t sel) {
    const int pr = blk / 44;
    return (uint32_t*)(p.ring + PROBE_OFF + (pr ? 4096u << pr : 0u) + (sel << 12) + 2176 + (blk - pr * 44) * 32);
}
__device__ __forceinline__ void probe(const Params& p, uint32_t sb, int w, int lane) {
    const int blk = blockIdx.x, pr = w >> 1;
    uint32_t off = PROBE_OFF + blk * 16 + (pr ? 4096u << pr : 0u);
    if (pr == 7) off = blk < NWIN ? blk * WIN + 4064 : PROBE_OFF + 3584 + blk % 16 * 32;
    off += (w & 1) * 4096;
    if (lane < 8) st_rlx((uint32_t*)(p.ring + (off & ~31u)) + lane, 0u);
    if (lane == 0) sts32(sb + SM_PROBE + w * 4, probe_rt((uint32_t*)(p.ring + off)));
}
__device__ __forceinline__ void assign_role(const Params& p, uint32_t sb, int lane) {
    {
        const bool x = lane < 8 && lds32(sb + SM_PROBE + lane * 8 + 4) < lds32(sb + SM_PROBE + lane * 8);
        const uint32_t near = __ballot_sync(0xffffffffu, x), bits = near & 1 ? ~near | 1u : near;
        const uint32_t tag = (lds32(sb + SM_MISC + 16) + 1) << 30;
        if (lane < 16) st_rlx(pub_ptr(p, blockIdx.x, lane >> 3) + (lane & 7), tag | (bits & 0xffu));
        constexpr int K = (NCTA + 31) / 32;
        __nanosleep(CFG_P0);
        uint32_t v[K], bad;
        int guard = 0;
        do {
            bad = 0;
#pragma unroll
            for (int k = 0; k < K; k++) {
                const int b = min(lane + 32 * k, NCTA - 1);
                v[k] = ld_rlx(pub_ptr(p, b, near >> (b / 44) & 1));
                bad |= v[k] ^ tag;
            }
            bad = __any_sync(0xffffffffu, bad >> 30);
            if (bad) __nanosleep(CFG_PSLEEP);
            if (++guard > GUARD) __trap();
        } while (bad);
#pragma unroll
        for (int k = 0; k < K; k++) sts32(sb + SM_PUB + (lane + 32 * k) * 4, v[k]);
    }
    __syncwarp();
    constexpr int NP = NCTA / 2, NTAB = H2 + H3;
    const int me = blockIdx.x >> 1, odd = blockIdx.x & 1;
    uint32_t pp[3], key[3];
    int n1 = 0;
#pragma unroll
    for (int k = 0; k < 3; k++) {
        const int i = lane + 32 * k;
        pp[k] = lds32(sb + SM_PUB + min(i, NP - 1) * 8) & 1;
        key[k] = (i * CFG_KM % CFG_KN) << 8 | i;
        n1 += 2 * __popc(__ballot_sync(0xffffffffu, i < NP && pp[k]));
    }
    bool fixed = n1 < NTAB || NCTA - n1 < NTAB;
    if (fixed) {
        n1 = NP / 2 * 2;
        pp[0] = pp[1] = pp[2] = lane & 1;
    }
    const uint32_t mine = __shfl_sync(0xffffffffu, (me < 32 ? key[0] : me < 64 ? key[1] : key[2]) * 2 + (me < 32 ? pp[0] : me < 64 ? pp[1] : pp[2]), me & 31);
    const int part = mine & 1;
    int pos = odd;
#pragma unroll
    for (int k = 0; k < 3; k++) pos += 2 * __popc(__ballot_sync(0xffffffffu, lane + 32 * k < NP && pp[k] == (uint32_t)part && key[k] < mine / 2));
    const int role = pos < H2 ? 1 : pos < NTAB ? 2 : 0;
    const int id = pos < H2 ? part * H2 + pos : pos < NTAB ? part * H3 + pos - H2 : (part ? NCTA - n1 - NTAB : 0) + pos - NTAB;
    const uint32_t v = lds32(sb + SM_PUB + lane * 4);
    uint32_t lin = 0;
#pragma unroll
    for (int b = 0; b < 6; b++) lin |= (__popc(__ballot_sync(0xffffffffu, (v >> (b + 1)) & 1)) > 16 ? 1u : 0u) << b;
    if (lane == 0) {
        sts32(sb + SM_MISC, role << 8 | id);
        sts32(sb + SM_MISC + 4, lin);
        sts32(sb + SM_MISC + 8, NCTA - n1 - NTAB);
        sts32(sb + SM_MISC + 20, part);
        sts32(sb + SM_MISC + 12, role == 0 ? id : role == 1 ? N1 + id : N1 + N2 + id);
    }
}
__device__ __forceinline__ uint32_t sel_of(uint32_t sb, int widx, uint32_t k, int part) {
    return (__popc(k & lds32(sb + SM_MISC + 4)) ^ (lds32(sb + SM_PUB + widx * 4) >> 7) ^ part) & 1;
}
__device__ __forceinline__ uint32_t gran_off(uint32_t sb, int widx, int k, int part) { return (2 * k + sel_of(sb, widx, k, part)) << 12; }
__device__ __forceinline__ uint32_t q1a_off(uint32_t sb, int src, int blk, int part) { return gran_off(sb, 2 * blk + part, src >> 1, part) + (src & 1) * 2048; }
__device__ __forceinline__ uint32_t q1h_off(uint32_t sb, int src, int blk, int part) { return gran_off(sb, 2 * blk + part, 32 + (src >> 2), part) + (src & 3) * 1024; }
__device__ __forceinline__ uint32_t* ctl_word(const Params& p, uint32_t sb, int k, int word, int part) {
    const int widx = CWIN + lds32(sb + SM_MISC + 16);
    return (uint32_t*)(p.ring + (widx * WIN + ((2 * k + sel_of(sb, widx, k, part)) << 12))) + word;
}
__device__ __forceinline__ uint32_t* cred1_of(const Params& p, uint32_t sb, int src) { return ctl_word(p, sb, src >> 3, (src & 7) * 128, src >= (int)lds32(sb + SM_MISC + 8)); }
__device__ __forceinline__ uint32_t* fin1_of(const Params& p, uint32_t sb, int dst) { return ctl_word(p, sb, 8 + (dst >> 3), (dst & 7) * 128, dst / H2); }
__device__ __forceinline__ uint32_t* cred2_of(const Params& p, uint32_t sb, int src) { return ctl_word(p, sb, 16 + (src >> 3), (src & 7) * 128, src / H2); }
__device__ __forceinline__ uint32_t* fin2_of(const Params& p, uint32_t sb, int dst) { return ctl_word(p, sb, 24 + (dst >> 3), (dst & 7) * 128, dst / H3); }
__device__ __forceinline__ uint32_t* rdy_of(const Params& p, uint32_t sb, int word, int part) { return ctl_word(p, sb, 28, word, part); }
__device__ __forceinline__ uint32_t q2_off(uint32_t sb, int blk, int dst) {
    return (N2 + dst) * WIN + gran_off(sb, N2 + dst, (blk >> 1) * 4 + (blk & 1), dst / H3);
}
template <bool IS1>
__device__ __forceinline__ void clear_queues(const Params& p, uint32_t sb, int id, int lane) {
    constexpr int NA = (N1 + 1) / 2, NG = NA + (N1 + 3) / 4, N = IS1 ? NG * N2 : NI * 2;
    if (IS1) {
#pragma unroll 1
        for (int k = 0; k < 8; k++) sts128(sb + SM_ZERO + (k * 32 + lane) * 16, make_uint4(0, 0, 0, 0));
        if (lane == 0) spin_ge(rdy_of(p, sb, 320, lds32(sb + SM_MISC + 20)), NTAIL);
    }
    __syncwarp();
    fence_async_smem();
    for (int k = IS1 ? id + (lane < CFG_CLN ? lane : N) * N1 : lane; k < N; k += IS1 ? CFG_CLN * N1 : 32) {
        if (IS1 && k >= CFG_CLN * N1) __nanosleep(CFG_CLS);
        const int wi = k / NG, g = k - wi * NG;
        const uint32_t off = IS1 ? wi * WIN + gran_off(sb, wi, g < NA ? g : 32 + g - NA, wi & 1) : q2_off(sb, k >> 1, id) + (k & 1) * 16384;
        bulk_store(p.ring + off, sb + SM_ZERO, 4096);
    }
    asm volatile("cp.async.bulk.commit_group;" ::: "memory");
    asm volatile("cp.async.bulk.wait_group 0;" ::: "memory");
    TR(21, IS1 && lane == 0);
    if (!IS1) {
        fence_async_all();
        __syncwarp();
        fence_gpu();
        if (lane < NI) red_rlx(rdy_of(p, sb, id / H3 * H2 + lane, id / H3), 1u);
    }
    __syncwarp();
}

struct In8 { uint4 a[2], o[2]; uint2 g[2]; };
__device__ __forceinline__ void p1_load(const Params& p, In8& r, int i4) {
#pragma unroll
    for (int u = 0; u < 2; u++) {
        [[maybe_unused]] uint32_t x, y;
        asm volatile("tex.1d.v4.u32.s32 {%0,%1,%2,%3}, [%4, {%5}];" : "=r"(r.a[u].x), "=r"(r.a[u].y), "=r"(r.a[u].z), "=r"(r.a[u].w) : "l"(p.t_in), "r"(i4 + u * 32));
        asm volatile("tex.1d.v4.u32.s32 {%0,%1,%2,%3}, [%4, {%5}];" : "=r"(r.o[u].x), "=r"(r.o[u].y), "=r"(r.o[u].z), "=r"(r.o[u].w) : "l"(p.t_out), "r"(i4 + u * 32));
        asm volatile("tex.1d.v4.u32.s32 {%0,%1,%2,%3}, [%4, {%5}];" : "=r"(r.g[u].x), "=r"(r.g[u].y), "=r"(x), "=r"(y) : "l"(p.t_ang), "r"(i4 + u * 32));
    }
}
__device__ __forceinline__ uint32_t imad(uint32_t a, uint32_t b, uint32_t c) {
    uint32_t r;
    asm("mad.lo.u32 %0, %1, %2, %3;" : "=r"(r) : "r"(a), "r"(b), "r"(c));
    return r;
}
__device__ __forceinline__ unsigned char* ring_ptr(const Params& p, uint32_t lo) {
    uint64_t r;
    asm("mov.b64 %0, {%1, %2};" : "=l"(r) : "r"(lo), "r"(p.ring_hi));
    return (unsigned char*)r;
}
__device__ __forceinline__ uint32_t keep32(uint32_t x) {
    return __shfl_sync(0xffffffffu, x, threadIdx.x & 31);
}
__device__ __forceinline__ uint32_t opaque32(uint32_t x) {
    asm volatile("" : "+r"(x));
    return x;
}
template <typename T> __device__ __forceinline__ T* opaque(T* p) {
    asm volatile("" : "+l"(p));
    return p;
}
template <int LUT> __device__ __forceinline__ uint32_t lop3(uint32_t a, uint32_t b, uint32_t c) {
    uint32_t r;
    asm("lop3.b32 %0, %1, %2, %3, %4;" : "=r"(r) : "r"(a), "r"(b), "r"(c), "n"(LUT));
    return r;
}
__device__ __forceinline__ uint32_t dp4(uint32_t a, uint32_t b, uint32_t c) {
    uint32_t r;
    asm("dp4a.u32.u32 %0, %1, %2, %3;" : "=r"(r) : "r"(a), "r"(b), "r"(c));
    return r;
}
__device__ __forceinline__ uint32_t dp2(uint32_t a, uint32_t b, uint32_t c) {
    uint32_t r;
    asm("dp2a.lo.u32.u32 %0, %1, %2, %3;" : "=r"(r) : "r"(a), "r"(b), "r"(c));
    return r;
}
__device__ __forceinline__ void p1_put(uint32_t sb, uint32_t wa, uint32_t wb, uint32_t old, bool on) {
    asm volatile("{.reg .pred q; setp.ne.u32 q, %3, 0; @q st.shared.v2.u32 [%0], {%1,%2};}"
                 ::"r"(sb + A_ST + prmt(old, wb, 0xf762)), "r"(wa), "r"(prmt(wb, old, 0x7210)), "r"((uint32_t)on) : "memory");
}
__device__ __forceinline__ void p1_slow_tile(const Params& p, uint32_t sb, int i4) {
    const float f = __bfloat162float(p.freq[0]);
#pragma unroll 1
    for (int u = 0; u < 8; u++) {
        const int k4 = i4 + (u >> 2) * 32;
        if (k4 < p.n4) {
            const size_t t = (size_t)k4 * 4 + (u & 3);
            const float x = __bfloat162float(__float2bfloat16(f * __bfloat162float(p.angle[t])));
            slow_add(p.m, sb, p.idx_in[t], p.idx_out[t], __bfloat162float(__float2bfloat16(cosf(x))));
        }
    }
}
__device__ __forceinline__ void role_p1(const Params& p, uint32_t sb, int id, int w, int lane) {
    lane = keep32(lane);
    const uint32_t f2 = (uint32_t)__bfloat16_as_ushort(p.freq[0]) * 0x10001u;
    constexpr int TG = CFG_TG, NTK = P1W;
    static_assert(NTK <= 16, "tickets");
    const int tc = (w + id) % NTK, first = (N1 * P1W + tc) * (TG * 64);
    uint32_t* const tickets = opaque(ctl_word(p, sb, 29 + tc / 8, tc % 8 * 128 + lane, tc & 1));
    auto draw = [&]() {
        uint32_t t = 0;
        asm volatile("{.reg .pred q; setp.eq.u32 q, %2, 0; @q atom.relaxed.gpu.global.add.u32 %0, [%1], 1;}" : "+r"(t) : "l"(tickets), "r"(lane) : "memory");
        return t;
    };
    int i4 = (id * P1W + w) * (TG * 64);
    In8 r;
    ACC_DECL
    uint32_t tk = draw();
    p1_load(p, r, i4 + lane);
    while (i4 < p.n4) {
        const int cur = i4;
        i4 += 64;
        if (i4 % (TG * 64) == 0) {
            i4 = min(__shfl_sync(0xffffffffu, tk, 0), 0x7fffffffu / (NTK * TG * 64) - N1 * P1W / NTK - 2) * (NTK * TG * 64) + first;
            tk = draw();
        }
        uint32_t wa[8], wb[8], x2[4];
        x2[0] = mul_bf2(r.g[0].x, f2); x2[1] = mul_bf2(r.g[0].y, f2);
        x2[2] = mul_bf2(r.g[1].x, f2); x2[3] = mul_bf2(r.g[1].y, f2);
        const uint32_t mx = maxabs_bf2(maxabs_bf2(x2[0], x2[1]), maxabs_bf2(x2[2], x2[3]));
        const bool fast = __all_sync(0xffffffffu, cur + 64 <= p.n4 && ((mx & 0x7fffu) <= 0x4300u) && ((mx & 0x7fff0000u) <= 0x43000000u));
        {
            const uint32_t in[8] = {r.a[0].x, r.a[0].y, r.a[0].z, r.a[0].w, r.a[1].x, r.a[1].y, r.a[1].z, r.a[1].w};
            const uint32_t ou[8] = {r.o[0].x, r.o[0].y, r.o[0].z, r.o[0].w, r.o[1].x, r.o[1].y, r.o[1].z, r.o[1].w};
#pragma unroll
            for (int j = 0; j < 8; j += 2) {
                const uint32_t ch = mul_h2(pack_h2(__cosf(bflo(x2[j >> 1])), __cosf(bfhi(x2[j >> 1]))), 0x24002400u);
#pragma unroll
                for (int k = j; k < j + 2; k++) {
                    const uint32_t blk = __umulhi(in[k], p.magic2), il = imad(blk, p.nrows2, in[k]);
                    wa[k] = k & 1 ? bitsel(ch, il, 0xffff0000u) : imad(ch, 65536u, il);
                    wb[k] = imad(blk, 1u << 21, imad(ou[k] >> 5, 1u - (1u << 21), ou[k] << 16));
                }
            }
        }
        p1_load(p, r, i4 + lane);
        if (fast) {
            uint32_t old[8], any = 0;
#pragma unroll
            for (int j = 0; j < 8; j++) old[j] = atoms_add(dp2(wb[j], 0x400u, 0u) + (sb + A_CNT), 0x80001u);
#pragma unroll
            for (int j = 0; j < 8; j++) any |= old[j];
            if (!__any_sync(0xffffffffu, any & 0xffe0u)) {
#pragma unroll
                for (int j = 0; j < 8; j++) p1_put(sb, wa[j], wb[j], old[j], true);
            } else {
                uint32_t pend = 0;
#pragma unroll
                for (int j = 0; j < 8; j++) { p1_put(sb, wa[j], wb[j], old[j], !(old[j] & 0xffe0u)); if (old[j] & 0xffe0u) pend |= 1u << j; }
                ACC(0, 1)
                for (int guard = 0; __any_sync(0xffffffffu, pend); guard++) {
                    __nanosleep(CFG_BSLEEP);
                    ACC(1, 1)
#pragma unroll
                    for (int j = 0; j < 8; j++) {
                        if (__any_sync(0xffffffffu, pend >> j & 1)) {
                            const uint32_t c = lds32v(sb + A_CNT + (pend >> j & 1 ? wb[j] >> 16 : 0) * 4);
                            const bool go = (pend >> j & 1) && (((old[j] >> 19) - (c >> 19) + c) & 8191u) < 32u;
                            p1_put(sb, wa[j], wb[j], old[j], go);
                            if (go) pend &= ~(1u << j);
                        }
                    }
                    if (guard > GUARD) __trap();
                }
            }
        } else {
            p1_slow_tile(p, sb, cur + lane);
            __syncwarp();
        }
    }
    __syncwarp();
    mbar_arrive_if(sb + SM_DONE, lane == 0);
    ACC_SAVE
}

__device__ __forceinline__ void role_flush(const Params& p, uint32_t sb, int id, int f, int lane) {
    lane = keep32(lane);
    const int half = lane >> 4, o = lane >> 2, q = lane & 3;
    const uint32_t hm = keep32(half ? 0xffff0000u : 0xffffu), lth = keep32(((1u << lane) - 1) & hm);
    const uint32_t list = sb + A_LIST + f * LISTB, cnt = keep32(sb + A_CNT + (f * GPW * 32 + lane) * 4);
    const uint32_t cred = opaque32(sb + SM_CRED + (half * 32 + f * GPW) * 4);
    const uint32_t pa = opaque32(p.ring_lo + (id >> 1) * 8192 + (id & 1) * 2048 + q * 16);
    const uint32_t ph = opaque32(p.ring_lo + (32 + (id >> 2)) * 8192 + (id & 3) * 1024 + q * 8 - 2048);
    const uint32_t sa = q * 16 + (o & 1) * 64;
    uint32_t qo[GPW], hs[GPW], cr[4] = {0, 0, 0, 0};
#pragma unroll
    for (int g = 0; g < GPW; g++) {
        const int blk = f * GPW + g;
        qo[g] = 32u << 25;
        const uint32_t sa = sel_of(sb, 2 * blk + half, id >> 1, half), sh = sel_of(sb, 2 * blk + half, 32 + (id >> 2), half);
        hs[g] = sa << 31 | (2 * sh + 1 - sa) << 22 | 1u << 24 | (lane & 15) << 15 | (blk * 32 + lane) * 2;
    }
    uint4 x[KR] = {}, y[KR] = {};
    uint32_t c[GPW] = {};
    auto scan = [&]() {
#pragma unroll
        for (int g = 0; g < GPW; g++) c[g] = lds32v(cnt + g * 128);
    };
    auto credits = [&]() {
        if (GPW == 4) { const uint4 v = lds128(cred); cr[0] = v.x; cr[1] = v.y; cr[2] = v.z; cr[3] = v.w; }
        else { const uint2 v = lds64v(cred); cr[0] = v.x; cr[1] = v.y; }
    };
    ACC_DECL
    int guard = 0;
    bool idle = false, done = false;
    while (true) {
        uint32_t fr[GPW], rank[GPW], num = 0, left = 0;
        bool ok[GPW];
        if (idle && !done && __all_sync(0xffffffffu, mbar_test(sb + SM_DONE, 0))) {
            done = true;
            TR(17, f == 0 && lane == 0);
#pragma unroll
            for (int g = 0; g < GPW; g++) {
                const uint32_t u = lds32v(cnt + g * 128) & 31u, hd = hs[g] ^ (u & 16u ? imad(hs[g], 1u << 24, 1u) & 0x01000001u : 0u);
#pragma unroll 2
                for (uint32_t j = 0, k; k = (j + lane) & 15u, j < 16; j++)
                    sts64_if(sb + A_ST + ((hd & 0x7ffu) << 7) + k * 8, p.rows2, (lane * 16 + k) | (hd & 0x1000000u), (u & 15u) && k >= (u & 15u));
                reds_add(cnt + g * 128, ((0u - u) & 15u) * 0x80001u);
            }
            __syncwarp();
            scan();
        }
#pragma unroll
        for (int g = 0; g < GPW; g++) {
            const bool isfull = c[g] & 0xfff0u;
            rank[g] = __popc(__ballot_sync(0xffffffffu, isfull) & lth);
            ok[g] = isfull && (int)(rank[g] << 25) < (int)(cr[g] - qo[g] + (63u << 25));
            ACC(2, __popc(__ballot_sync(0xffffffffu, isfull && !ok[g])))
        }
#pragma unroll
        for (int g = 0; g < GPW; g++) {
            const uint32_t m = __ballot_sync(0xffffffffu, ok[g]), n = __popc(m & hm), all = __popc(m), e = num + rank[g] + (half ? all - n : 0u);
            sts32_if(KR == 2 ? list + (e & 48u) * 4 + (e & 7u) * 8 + (e >> 1 & 4u) : imad(e, 4u, list), bitsel(imad(rank[g], 1u << 25, qo[g]), hs[g], 0x7e000000u), ok[g]);
            if (ok[g]) hs[g] ^= imad(hs[g], 1u << 24, 1u) & 0x01000001u;
            fr[g] = ok[g] ? 0u - 16u : 0u;
            left |= c[g] + fr[g];
            qo[g] = imad(n, 1u << 25, qo[g]);
            num += all;
        }
        __syncwarp();
        ACC(0, 1) ACC(1, num)
        if (num) {
            uint32_t la = list + o * (KR == 2 ? 8 : 4);
            int todo = (int)num - o, rest = num;
            do {
                uint32_t d[KR];
                if (KR == 2) { const uint2 v = lds64v(la); d[0] = v.x; d[KR - 1] = v.y; }
                else {
#pragma unroll
                    for (int k = 0; k < KR; k++) d[k] = lds32v(la + 32 * k);
                }
                while (true) {
                    uint32_t bad = 0;
#pragma unroll
                    for (int k = 0; k < KR; k++) {
                        const uint32_t m = d[k] & 0x7ffu;
                        lds128_keep(x[k], imad(m, 128u, sa) + (sb + A_ST), todo > 8 * k);
                        lds128_keep(y[k], imad(m, 128u, sa ^ 64) + (sb + A_ST), todo > 8 * k);
                    }
#pragma unroll
                    for (int k = 0; k < KR; k++)
                        or3_if(bad, lop3<0x7e>(x[k].y, x[k].w, d[k]), lop3<0x7e>(y[k].y, y[k].w, d[k]), todo > 8 * k);
                    if (!__any_sync(0xffffffffu, (int)imad(bad, 128u, 0u) < 0)) break;
                    if (++guard > GUARD) __trap();
                }
#pragma unroll
                for (int k = 0; k < KR; k++) {
                    const uint32_t mi = d[k] & 0x7e0u, dm = d[k] & 0xbec00000u;
                    x[k].x = bitsel(d[k], x[k].x, 0x40078000u);
                    x[k].y = prmt(x[k].y, x[k].w, 0x5410);
                    x[k].w = prmt(y[k].y, y[k].w, 0x5410);
                    y[k].x = bitsel(d[k], y[k].x, 0x40000000u);
                    y[k].y = y[k].z;
                    stg_q128(ring_ptr(p, dp4(dm, 0x20000000u, imad(mi, WIN / 32, pa))), x[k].x, x[k].y, x[k].z, x[k].w, todo > 8 * k);
                    stg_q64(ring_ptr(p, dp4(dm, 0x10200000u, imad(mi, WIN / 32, ph))), y[k].x, y[k].y, todo > 8 * k);
                }
                la += 32 * KR;
                todo -= 8 * KR;
                rest -= 8 * KR;
            } while (rest > 0);
#pragma unroll
            for (int g = 0; g < GPW; g++) c[g] = atoms_add(cnt + g * 128, fr[g]) + fr[g];
            credits();
            idle = num <= CFG_TH;
            if (done && !__any_sync(0xffffffffu, left & 0xffffu)) break;
            if (idle) { __nanosleep(CFG_TS); scan(); credits(); }
        } else {
            if (done && !__any_sync(0xffffffffu, left & 0xffffu)) break;
            idle = true;
            __nanosleep(CFG_FSLEEP);
            scan();
            credits();
            if (++guard > GUARD) __trap();
        }
    }
#pragma unroll
    for (int g = 0; g < GPW; g++) st_rlx_if(fin1_of(p, sb, half * H2 + f * GPW + g) + id, qo[g] - (32u << 25) + 1u, (lane & 15) == 0 && f * GPW + g < NI);
    mbar_arrive_if(sb + SM_DONE2, lane == 0);
    TR(18, f == 0 && lane == 0);
    ACC_SAVE
}
__device__ __forceinline__ void role_credit1(const Params& p, uint32_t sb, int id, int lane) {
    const uint32_t* const cred = cred1_of(p, sb, id) + lane * 2;
    for (int guard = 0; !__all_sync(0xffffffffu, mbar_test(sb + SM_DONE2, 0)); guard++) {
        const uint2 v = ldg_q64(cred);
        sts64(sb + SM_CRED + lane * 8, v.x, v.y);
        __nanosleep(CFG_C1SLEEP);
        if (guard > GUARD) __trap();
    }
}

__device__ __forceinline__ float h2f(uint32_t h) {
    float f;
    asm("{.reg .b16 t; cvt.u16.u32 t, %1; cvt.f32.f16 %0, t;}" : "=f"(f) : "r"(h));
    return f;
}
__device__ __forceinline__ void p2_slow(const Params& p, uint32_t sb, const uint32_t* tmp, int row0, uint32_t dst) {
#pragma unroll 1
    for (int j = 0; j < 4; j++)
        if (tmp[8 + j] & 0x40u) slow_add(p.m, sb, row0 + (tmp[j] & 0x7fffu), (tmp[4 + j] & 0x7fffu) * 32 + dst, h2f(tmp[j] >> 16) * 64.0f);
}
__device__ __forceinline__ uint32_t mul_h2_hi(uint32_t a, uint32_t b) {
    uint32_t r;
    asm("{.reg .b16 l, h; .reg .b32 t; mov.b32 {l, h}, %2; mov.b32 t, {h, h}; mul.rn.f16x2 %0, %1, t;}" : "=r"(r) : "r"(a), "r"(b));
    return r;
}
template <bool CHECK>
__device__ __forceinline__ void role_p2(const Params& p, uint32_t sb, int id, int w, int lane) {
    lane = keep32(lane);
    const int part = id / H2, blk = id - part * H2, row0 = blk * p.rows2;
    const int o = lane >> 2, q = lane & 3;
    uint32_t* const cbase = (uint32_t*)(p.ring + (CWIN + lds32(sb + SM_MISC + 16)) * WIN);
    const uint32_t cred = opaque32((uint32_t)(uintptr_t)(cbase + part * 32 + blk));
    const uint32_t pa = opaque32(p.ring_lo + (2 * blk + part) * WIN + q * 16), ph = opaque32(pa - q * 8);
    const uint32_t po = opaque32(p.ring_lo + (q2_off(sb, blk, part * H3) & ~4096u) + q * 16 + (o & 1) * 64);
    const uint32_t sel = __ballot_sync(0xffffffffu, q2_off(sb, blk, part * H3 + (lane & 15)) & 4096u) << 12;
    const uint32_t* const fins = fin1_of(p, sb, id);
    uint32_t st[QPW] = {}, sq[QPW] = {};
    uint4 qa[NBT];
    uint2 qh[NBT];
    auto load = [&](int k) {
        qa[k] = ldg_q128(ring_ptr(p, pa + (bitsel(sq[k], st[k] >> 19, 0x7f800u) & 0x7ffc0u)));
        qh[k] = ldg_q64(ring_ptr(p, ph + (bitsel(sq[k] >> 9, st[k] >> 20, 0x7fc00u) & 0x7ffe0u)));
    };
#pragma unroll
    for (int k = 0; k < QPW; k++) {
        const int src = w * QPW + k;
        st[k] = o << 25 | (src < N1 ? 1u : 5u);
        sq[k] = src < N1 ? q1h_off(sb, src, blk, part) << 9 | q1a_off(sb, src, blk, part) | (uint32_t)(cred1_of(p, sb, src) - cbase) / 8 : 0x7e000u * 513u;
    }
#pragma unroll
    for (int k = 0; k < NBT; k++) load(k);
    ACC_DECL
    int guard = 0;
    uint32_t streak = 0;
    while (true) {
        uint32_t nn[NBT], xx[NBT][4], hh[NBT][2], dd[NBT], any = 0;
        bool last = false;
#pragma unroll
        for (int k = 0; k < NBT; k++) {
            const uint4 a = qa[k];
            const uint2 h = qh[k];
            uint32_t n = 8;
            const uint32_t miss = __ballot_sync(0xffffffffu, (int)imad((a.x ^ st[k]) & (h.x ^ st[k]), 2u, 0u) >= 0);
            if (miss) {
                n = (__ffs(miss) - 1) >> 2;
                if (!__any_sync(0xffffffffu, st[k] & 8u)) { if (streak < CFG_PSTREAK) n &= CFG_PMASK; }
                else if (!__any_sync(0xffffffffu, ((st[k] >> 6) + ((n - o) << 19) ^ st[k]) & 0x1f80000u)) { st[k] |= 4u; last = true; }
            }
            ACC(1, n == 0) ACC(2, n != 0) ACC(3, n)
            st[k] = imad(n, 1u << 25, st[k]);
            st_rlx_if((uint32_t*)ring_ptr(p, imad(sq[k] & 0x7f0u, 32u, cred)), st[k], lane == 0 && n);
            xx[k][0] = bitsel(a.x, 0x00040000u, 0xbff87fffu); xx[k][1] = a.z; xx[k][2] = h.x & 0xbfffffffu; xx[k][3] = h.y;
            hh[k][0] = a.y; hh[k][1] = a.w; dd[k] = a.x >> 13 & 0x3cu; nn[k] = n;
            any |= n;
        }
        if (!any) {
#pragma unroll
            for (int k = 0; k < QPW; k++) {
                const uint32_t fin = ld_rlx(fins + ((sq[k] >> 12 & 62u) | (sq[k] >> 11 & 1u)));
                if (fin & 1u) st[k] |= (fin >> 6 & 0x1f80000u) | ((fin ^ (st[k] - (o << 25))) >> 25 ? 8u : 12u);
            }
            last = true;
            if (++guard > GUARD) __trap();
            streak++;
        } else streak = 0;
        if (last) {
            uint32_t all = 4u;
#pragma unroll
            for (int k = 0; k < QPW; k++) all &= st[k];
            last = __all_sync(0xffffffffu, all);
        }
        {
            uint32_t t[QPW], u[QPW];
#pragma unroll
            for (int k = 0; k < QPW; k++) { t[k] = st[(k + NBT) % QPW]; u[k] = sq[(k + NBT) % QPW]; }
#pragma unroll
            for (int k = 0; k < QPW; k++) { st[k] = t[k]; sq[k] = u[k]; }
        }
#pragma unroll
        for (int k = 0; k < NBT; k++) load(k);
#pragma unroll
      for (int k = 0; k < NBT; k++) {
        if (nn[k]) {
            const uint32_t* const x = xx[k];
            const uint32_t h0 = hh[k][0], h1 = hh[k][1], d4 = dd[k];
            const bool v = o < nn[k];
            uint32_t old = 0, ta[4], tb[4], w0[4], w1[4];
            atoms_add_keep(old, sb + SM_CNT2 + d4, 0x10001u, q == 0 && v);
#pragma unroll
            for (int j = 0; j < 4; j++) {
                ta[j] = lds32nv(dp2(x[j], 4u, 0u) + (sb + B_TA));
                tb[j] = lds16nv(dp2(x[j], 2u, 0u) + (sb + B_TB));
            }
            old = __shfl_sync(0xffffffffu, old, lane & 28);
            const uint32_t tag = old << 8 & 0x40000000u;
#pragma unroll
            for (int j = 0; j < 4; j++) {
                const uint32_t z = prmt(j & 2 ? h1 : h0, 0, j & 1 ? 0x4342 : 0x4140);
                const uint32_t t23 = prmt((ta[j] & 0x60076007u) * 2050u, tb[j], 0x5341) & 0xfffcffffu;
                w0[j] = (imad(z, 128u, j & 1 ? 0u : tag) & 0x78007800u) | mul_h2_hi(ta[j] & 0x9ff89ff8u, x[j]);
                w1[j] = (imad(z, 2048u, 0u) & 0x78007800u) | mul_h2_hi(t23, x[j]);
            }
            if (CHECK && v && ((tb[0] | tb[1] | tb[2] | tb[3]) & 0x40u)) {
                uint32_t tmp[12];
#pragma unroll
                for (int j = 0; j < 4; j++) {
                    tmp[j] = x[j]; tmp[4 + j] = (j & 2 ? h1 : h0) >> (j & 1 ? 16 : 0); tmp[8 + j] = tb[j];
                    if (tb[j] & 0x40u) { w0[j] &= 0x78007800u; w1[j] &= 0x78007800u; }
                }
                p2_slow(p, sb, tmp, row0, part * H3 + d4 / 4);
            }
            const uint32_t off = (bitsel(old >> 9, old >> 7, 0x0f80u) & 0x4f80u) + imad(d4, WIN / 4, (sel >> (d4 / 4) & 4096u) + po);
            bool wait = old & (0x10000u - NQ2);
            if (!__any_sync(0xffffffffu, wait)) {
                stg_q128(ring_ptr(p, off), w0[0], w1[0], w0[1], w1[1], v);
                stg_q128(ring_ptr(p, off ^ 64u), w0[2], w1[2], w0[3], w1[3], v);
            } else {
                bool pend = v;
                ACC(0, 1)
                for (int g2 = 0;; g2++) {
                    stg_q128(ring_ptr(p, off), w0[0], w1[0], w0[1], w1[1], pend && !wait);
                    stg_q128(ring_ptr(p, off ^ 64u), w0[2], w1[2], w0[3], w1[3], pend && !wait);
                    pend = wait;
                    if (!__any_sync(0xffffffffu, pend)) break;
                    __nanosleep(CFG_BSLEEP);
                    const uint32_t c = lds32v(sb + SM_CNT2 + d4);
                    wait = pend && (((old >> 16) - (c >> 16) + c) & 0xffffu) >= NQ2;
                    if (g2 > GUARD) __trap();
                }
            }
        }
      }
        if (last) break;
    }
    TR(17, w == 0 && lane == 0);
    __syncwarp();
    uint32_t rank = 0;
    if (lane == 0) { __threadfence_block(); rank = atoms_add(sb + SM_FIN, 1u); __threadfence_block(); }
    if (__shfl_sync(0xffffffffu, rank, 0) == P2W - 1 && lane < 16)
        st_rlx(fin2_of(p, sb, part * H3 + lane) + blk, FIN | (((lds32v(sb + SM_CNT2 + lane * 4) >> 16) - NQ2) & 0xffffu));
    __syncwarp();
    mbar_arrive_if(sb + SM_DONE, lane == 0);
    ACC_SAVE
}
__device__ __forceinline__ void role_credit(const Params& p, uint32_t sb, int id, int lane) {
    const uint32_t* const cred = cred2_of(p, sb, id) + (lane & 15);
    uint32_t last = 0;
    for (int guard = 0;; guard++) {
        if (__all_sync(0xffffffffu, mbar_test(sb + SM_DONE, 0))) break;
        const uint32_t c = ld_rlx(cred);
        if (lane < 16 && c != last) reds_add(sb + SM_CNT2 + lane * 4, 0u - ((c - last) & 0xffffu));
        last = c;
        __nanosleep(CFG_CSLEEP);
        if (guard > GUARD) __trap();
    }
}

__device__ __forceinline__ void p3_wrap(uint32_t sb, int id, const uint32_t* tmp) {
    const Scale sc = get_scale(sb);
#pragma unroll 1
    for (int j = 0; j < 8; j++) {
        const uint32_t old = tmp[4 + j], v = tmp[12 + j], nw = old + v, t = (old ^ nw) & (v ^ nw);
        if (t & 0x80008000u) {
            const float k = (t & 0x8000u) ? ((v & 0x8000u) ? -1.0f : 1.0f) : 0.0f;
            const float q = (t & 0x80000000u) ? ((int)v < 0 ? -65536.0f : 65536.0f) : 0.0f;
            const uint32_t e0 = (j & 1) ? sc.eb[2] : sc.eb[0], e1 = (j & 1) ? sc.eb[3] : sc.eb[1];
            const float lo = k * 65536.0f * __uint_as_float((e0 - 10) << 23), hi = (q - k) * __uint_as_float((e1 - 10) << 23);
            if (j & 1) sg_add(tmp[j >> 1] * 32 + id, 0.f, 0.f, lo, hi);
            else sg_add(tmp[j >> 1] * 32 + id, lo, hi, 0.f, 0.f);
        }
    }
}
__device__ __forceinline__ uint32_t p3_val(uint32_t w) {
    const uint32_t mk = prmt(w, 0, 0xBB99);
    return ((w & 0x07ff07ffu) ^ mk) - mk;
}
__device__ __forceinline__ void role_p3(const Params& p, uint32_t sb, int id, int w, int lane) {
    lane = keep32(lane);
    uint32_t* const cred = opaque(cred2_of(p, sb, id / H3 * H2 + w) + id % H3);
    const uint32_t pq = opaque32(p.ring_lo + q2_off(sb, w, id) + lane * 16);
    auto off = [&](uint32_t n) { return (n & 1u) << 11 | (n & 2u) << 13; };
    const uint32_t pp = opaque32(pq - lane * 16 + 112);
    const uint32_t* const finp = opaque(fin2_of(p, sb, id) + w);
    auto tag_of = [&](uint32_t n) { return ~n << 28; };
    uint32_t n = 0, fin = 0, pr = 0, pk = 0;
    uint4 v[4] = {};
    bool have = false, last = false;
    ACC_DECL
    int guard = 0;
    while (true) {
        const uint32_t ex = tag_of(n);
        const bool ok = have && !__any_sync(0xffffffffu, ((v[0].x ^ ex) | (v[1].x ^ ex) | (v[2].x ^ ex) | (v[3].x ^ ex)) & 0x40000000u);
        if (ok) n++;
        const bool ready = (ok || !have) && __all_sync(0xffffffffu, !((pr ^ tag_of(n)) & 0x40000000u));
        st_rlx_if(cred, n * 16, lane == 0 && ok);
        if (!ok && !ready && __all_sync(0xffffffffu, fin & FIN)) {
            const uint32_t left = __shfl_sync(0xffffffffu, (fin - n * 16) & 0xffffu, 0);
            if (left - 1u > 0x8000u) break;
            if (left < 16u) {
#pragma unroll
                for (int u = 0; u < 4; u++) {
                    v[u] = make_uint4(ex & 0x40000000u, 0, 0, 0);
                    ldq128_keep(v[u], ring_ptr(p, pq + off(n)) + u * 512, u * 4 + (lane >> 3) < left);
                }
                have = last = !__any_sync(0xffffffffu, ((v[0].x ^ ex) | (v[1].x ^ ex) | (v[2].x ^ ex) | (v[3].x ^ ex)) & 0x40000000u);
                pr = ~tag_of(n + have);
                if (++guard > GUARD) __trap();
                continue;
            }
        }
        uint32_t row[8], val[16];
#pragma unroll
        for (int u = 0; u < 4; u++) {
            const uint4 x = v[u];
            row[2 * u] = prmt(bitsel(x.x << 1, x.y >> 3, 0x7000f000u), 0, 0x4431);
            row[2 * u + 1] = prmt(bitsel(x.z << 1, x.w >> 3, 0x7000f000u), 0, 0x4431);
            val[4 * u] = p3_val(x.x); val[4 * u + 1] = p3_val(x.y);
            val[4 * u + 2] = p3_val(x.z); val[4 * u + 3] = p3_val(x.w);
        }
#pragma unroll
        for (int u = 0; u < 4; u++) ldq128_keep(v[u], ring_ptr(p, pq + off(n)) + u * 512, ready);
        pk = ready ? CFG_PK1 * 128 : ok ? CFG_PK2 * 128 : have ? 15 * 128 : max(pk, CFG_PK3 * 128u);
        pr = ld_rlx((const uint32_t*)ring_ptr(p, pp + off(n + ready) + pk));
        ACC(2, have && !ok)
        have = ready;
        if (!ok) {
            ACC(1, 1)
            fin = ld_rlx(finp);
            if (++guard > GUARD) __trap();
        } else {
#pragma unroll
            for (int u = 0; u < 4; u += 2) {
                uint32_t old[8], chk = 0;
#pragma unroll
                for (int j = 0; j < 4; j++) {
                    old[2 * j] = atoms_add(sb + C_S + row[2 * u + j] * 4, val[4 * u + 2 * j]);
                    old[2 * j + 1] = atoms_add(sb + C_S + ROWS3_MAX * 4 + row[2 * u + j] * 4, val[4 * u + 2 * j + 1]);
                }
#pragma unroll
                for (int j = 0; j < 8; j++) {
                    const uint32_t nw = old[j] + val[4 * u + j];
                    chk |= (old[j] ^ nw) & (val[4 * u + j] ^ nw);
                }
                if (chk & 0x80008000u) {
                    uint32_t tmp[20];
#pragma unroll
                    for (int j = 0; j < 8; j++) { tmp[j >> 1] = row[2 * u + (j >> 1)]; tmp[4 + j] = old[j]; tmp[12 + j] = val[4 * u + j]; }
                    p3_wrap(sb, id, tmp);
                }
            }
            __syncwarp();
            if (last) break;
        }
    }
    ACC_SAVE
}

__device__ __forceinline__ void row_gates(const float* sw, const uint32_t* c2, uint32_t dbits, float4& gs, float4& gr) {
    const uint32_t d2 = dbits * 0x10001u;
    gs = gr = make_float4(0.f, 0.f, 0.f, 0.f);
#pragma unroll
    for (int r2 = 0; r2 < 4; r2++) {
        uint32_t df = sub_bf2(d2, c2[r2]);
        uint32_t ar = mul_bf2(mul_bf2(df, df), 0xC120C120u);
        uint32_t rb = pack_bf2(__expf(bflo(ar)), __expf(bfhi(ar)));
        const float r0 = bflo(rb), r1 = bfhi(rb);
        const float4 s0 = *(const float4*)(sw + r2 * 8), s1 = *(const float4*)(sw + r2 * 8 + 4);
        const float4 q0 = *(const float4*)(sw + 32 + r2 * 8), q1 = *(const float4*)(sw + 32 + r2 * 8 + 4);
        gs.x += r0 * s0.x + r1 * s1.x; gs.y += r0 * s0.y + r1 * s1.y;
        gs.z += r0 * s0.z + r1 * s1.z; gs.w += r0 * s0.w + r1 * s1.w;
        gr.x += r0 * q0.x + r1 * q1.x; gr.y += r0 * q0.y + r1 * q1.y;
        gr.z += r0 * q0.z + r1 * q1.z; gr.w += r0 * q0.w + r1 * q1.w;
    }
}
__device__ __forceinline__ uint2 finish_row(const float* wu, const float4& gs, const float4& gr, const float S[4], uint2 mrow) {
    const float a[4] = {S[0] * gs.x, S[1] * gs.y, S[2] * gs.z, S[3] * gs.w};
    float u[4] = {0, 0, 0, 0};
#pragma unroll
    for (int k = 0; k < 4; k++) {
        u[0] += a[k] * wu[4 * k]; u[1] += a[k] * wu[4 * k + 1]; u[2] += a[k] * wu[4 * k + 2]; u[3] += a[k] * wu[4 * k + 3];
    }
    return make_uint2(pack_bf2(bflo(mrow.x) + u[0] * gr.x, bfhi(mrow.x) + u[1] * gr.y),
                      pack_bf2(bflo(mrow.y) + u[2] * gr.z, bfhi(mrow.y) + u[3] * gr.w));
}
__device__ __forceinline__ void load_tail_weights(const Params& p, float* sw, int tid) {
    if (tid < 32) sw[tid] = __bfloat162float(p.w_sbf[tid]);
    else if (tid < 64) sw[tid] = __bfloat162float(p.w_rbf[tid - 32]);
    else if (tid < 80) sw[tid] = __bfloat162float(p.w_up[tid - 64]);
    else if (tid < 96) sw[tid] = __bfloat162float(p.w_down[tid - 80]);
}
__device__ __forceinline__ float exp_ftz(float x) {
    float r;
    asm("ex2.approx.ftz.f32 %0, %1;" : "=f"(r) : "f"(x * 1.4426950408889634f));
    return r;
}
__device__ __forceinline__ void tail_rows(const Params& p, int tidx, int w, int lane) {
    constexpr uint32_t sb = SB;
    if (w == NW - 1 && lane < 2) {
        fence_gpu();
        red_rlx(rdy_of(p, sb, 320, lane), 1u);
    }
    if (w >= NPC * WPP) return;
    const int pc = w / WPP, r0 = pc * RPC + (tidx * WPP + w - pc * WPP) * 8, e0 = r0 * 32;
    const uint32_t G = sb + T_G + w * TWB, M = G + 4096, D = M + 2048;
    cp16z(D + lane * 16, p.dist + e0 + lane * 8, min(max(p.E - e0 - lane * 8, 0), 8) * 2);
#pragma unroll
    for (int k = 0; k < 4; k++) cp16(M + (k * 32 + lane) * 16, p.m + e0 + (k * 32 + lane) * 2, e0 + (k * 32 + lane) * 2 < p.E);
    cp_commit();
    const Scale sc = get_scale(sb);
    const float lsb[4] = {__uint_as_float((sc.eb[0] - 10) << 23), __uint_as_float((sc.eb[1] - 10) << 23),
                          __uint_as_float((sc.eb[2] - 10) << 23), __uint_as_float((sc.eb[3] - 10) << 23)};
    {
        const int g = lane >> 2, t = lane & 3;
        const uint32_t c2 = ((const uint32_t*)p.centers)[t];
        const unsigned short* wg = (const unsigned short*)(g < 4 ? p.w_sbf : p.w_rbf) + t * 8 + (g & 3);
        const uint32_t b = wg[0] | (uint32_t)wg[4] << 16;
        cp_wait<0>();
        __syncwarp();
        TR(19, w == 0 && lane == 0 && b + c2 != 0x12345);
#pragma unroll 2
        for (int k = 0; k < 16; k++) {
            const uint32_t dv = lds32(D + (k * 8 + g) * 4);
            uint32_t a[2];
#pragma unroll
            for (int h = 0; h < 2; h++) {
                const uint32_t df = sub_bf2(prmt(dv, 0, h ? 0x3232 : 0x1010), c2);
                const uint32_t ar = mul_bf2(mul_bf2(df, df), 0xC120C120u);
                a[h] = pack_bf2(exp_ftz(bflo(ar)), exp_ftz(bfhi(ar)));
            }
            float d[4];
            asm("mma.sync.aligned.m16n8k8.row.col.f32.bf16.bf16.f32 {%0,%1,%2,%3}, {%4,%5}, {%6}, {%7,%7,%7,%7};"
                : "=f"(d[0]), "=f"(d[1]), "=f"(d[2]), "=f"(d[3]) : "r"(a[0]), "r"(a[1]), "r"(b), "f"(0.f));
            const uint32_t at = G + (k * 16 + g * 2) * 16 + t * 4;
            sts32(at, pack_bf2(d[0], d[1]));
            sts32(at + 16, pack_bf2(d[2], d[3]));
        }
    }
    __syncwarp();
    TR(2, w == 0 && lane == 0);
    float wu[16];
#pragma unroll
    for (int k = 0; k < 4; k++) *(uint4*)(wu + 4 * k) = lds128(sb + SM_W + 256 + 16 * k);
    uint32_t dirty = 0;
#pragma unroll 1
    for (int pass = CFG_DRY ? 0 : 1; pass < 2; pass++) {
        if (pass) {
            if (w == pc * WPP && lane < 2) spin_ge(rdy_of(p, sb, lane ? 320 : 160 + 32 * pc, lds32(sb + SM_MISC + 20)), lane ? NTAIL : N3);
            __syncwarp();
            bar_sync(1 + pc, WPP * 32);
            TR(3, w == 0 && lane == 0);
            TR(10, w == NPC * WPP - 1 && lane == 0);
            if (r0 >= (int)p.rows3) return;
        }
        uint4 sv[4] = {};
#pragma unroll
        for (int u = 0; u < 4; u++) ldq128_keep(sv[u], &g_S[0][u * 16 + (lane >> 1)][r0 + (lane & 1) * 4], pass);
        if (pass && lane < 8 && (r0 + lane) * 32 < p.E && (dirty = ld_rlx(g_dirty + r0 + lane))) st_rlx(g_dirty + r0 + lane, 0u);
        dirty = __ballot_sync(0xffffffffu, dirty != 0);
        uint32_t xs[8] = {sv[0].x, sv[0].y, sv[0].z, sv[0].w, sv[1].x, sv[1].y, sv[1].z, sv[1].w};
        uint32_t ys[8] = {sv[2].x, sv[2].y, sv[2].z, sv[2].w, sv[3].x, sv[3].y, sv[3].z, sv[3].w};
        asm volatile("" : "+r"(lane));
        auto finish = [&](int k, uint32_t x, uint32_t y, bool extra) {
            const int i = (lane & 1) * 128 + (lane >> 1) + (k & 3) * 32 + (k >> 2) * 16, e = e0 + i;
            float S[4];
            const uint32_t tx = x + 0x80008000u, ty = y + 0x80008000u;
            S[0] = (__uint_as_float(prmt(tx, 0x4b000000u, 0x7610)) - 8421376.0f) * lsb[0];
            S[1] = (__uint_as_float(prmt(tx, 0x4b000000u, 0x7632)) - 8421376.0f) * lsb[1];
            S[2] = (__uint_as_float(prmt(ty, 0x4b000000u, 0x7610)) - 8421376.0f) * lsb[2];
            S[3] = (__uint_as_float(prmt(ty, 0x4b000000u, 0x7632)) - 8421376.0f) * lsb[3];
            if (extra && e < p.E) {
                const float4 g = __ldcg(g_Sg + e);
                S[0] += g.x; S[1] += g.y; S[2] += g.z; S[3] += g.w;
                __stcg(g_Sg + e, make_float4(0.f, 0.f, 0.f, 0.f));
            }
            const uint4 g = lds128(G + i * 16);
            const uint2 o = finish_row(wu, make_float4(bflo(g.x), bfhi(g.x), bflo(g.y), bfhi(g.y)), make_float4(bflo(g.z), bfhi(g.z), bflo(g.w), bfhi(g.w)), S,
                                       lds64v(M + i * 8));
            asm volatile("{.reg .pred q; setp.ne.u32 q, %3, 0; @q st.global.v2.u32 [%0], {%1,%2};}"
                         ::"l"(p.out + e), "r"(o.x), "r"(o.y), "r"((uint32_t)(pass && e < p.E)));
        };
        if (!dirty) {
#pragma unroll
            for (int k = 0; k < 8; k++) finish(k, xs[k], ys[k], false);
        } else {
#pragma unroll 1
            for (int k = 0; k < 8; k++) {
                finish(k, xs[0], ys[0], dirty >> ((lane & 1) * 4 + (k & 3)) & 1);
#pragma unroll
                for (int j = 0; j < 7; j++) { xs[j] = xs[j + 1]; ys[j] = ys[j + 1]; }
            }
        }
    }
    TR(9, w == 0 && lane == 0);
    TR(11, w == NPC * WPP - 1 && lane == 0);
}

#define CFG_MAP1 1
__global__ void __launch_bounds__(NT, 1) k_main(const __grid_constant__ Params p) {
    extern __shared__ __align__(1024) unsigned char smem[];
    constexpr uint32_t sb = SB;
    if ((uint32_t)__cvta_generic_to_shared(smem) != SB) __trap();
    const int tid = threadIdx.x, w = __shfl_sync(0xffffffffu, tid >> 5, 0), lane = tid & 31;
    if (w < NPROBE) probe(p, sb, w, lane);
    else {
        if (tid == NT - 1) sts32(sb + SM_MISC + 16, ld_rlx(&g_epoch) & 1);
        if (tid >= NT - 32 && lane < 12) sts32(sb + SM_FIN + lane * 4, 0u);
        load_tail_weights(p, (float*)(smem + SM_W), tid - NPROBE * 32);
        const int k = blockIdx.x % (NCTA / 2) * 14 + lane;
        if (w == NW - 2 && lane < 14 && k < NT - 32) asm volatile("prefetch.global.L2 [%0];" ::"l"((const uint4*)p.m + k * (p.E / 2 / (NT - 32))));
    }
    cta_sync();
    if (w) {
        const uint4 in = __ldg((const uint4*)p.m + (tid - 32) * (p.E / 2 / (NT - 32)));
        const Mat4 wd = load_mat4(p.w_down, lane);
        for (int i = SM_DATA / 16 + tid - 32; i < ZEND / 16; i += NT - 32) ((uint4*)smem)[i] = make_uint4(0, 0, 0, 0);
        if (tid - 32 < 256) ((uint4*)(smem + SM_ZERO))[tid - 32] = make_uint4(0, 0, 0, 0);
        if (tid < 48) sts32(sb + SM_CNT2 + (tid - 32) * 4, NQ2 << 16);
        __syncwarp();
        if (CFG_PFD && tid == NT - 1) {
            __nanosleep(CFG_PFD);
            const uint32_t n = (p.E / 2 + NCTA - 1) / NCTA, o = blockIdx.x * n;
            if (o < (uint32_t)p.E / 2) asm volatile("cp.async.bulk.prefetch.L2.global [%0], %1;" ::"l"((const uint4*)p.m + o), "r"(min(n, p.E / 2 - o) * 16) : "memory");
        }
        __syncwarp();
        md_stats(in, wd, lane);
    } else assign_role(p, sb, lane);
    if (tid == 0) {
        mbar_init(sb + SM_DONE, lds32(sb + SM_MISC) >> 8 ? P2W : P1W);
        mbar_init(sb + SM_DONE2, NF);
    }
    cta_sync();
    const uint32_t rid = __shfl_sync(0xffffffffu, lds32(sb + SM_MISC), 0);
    const int role = rid >> 8, id = rid & 255;
    TR(5, tid == 0);
    if (role == 0) {
        const int ww = CFG_MAP1 == 0 ? ((w & 3) == 3 ? NW : (w >> 2) * 3 + (w & 3)) : CFG_MAP1 == 1 ? (w & 2 ? NW : (w >> 2) * 2 + (w & 1)) : w;
        const int sw = CFG_MAP1 == 0 ? ((w & 3) == 3 ? w >> 2 : NW) : CFG_MAP1 == 1 ? (w & 2 ? (w >> 2) * 2 + (w & 1) : NW) : w - P1W;
        static_assert(CFG_MAP1 == 0 ? (P1W <= NW / 4 * 3 && NF + 2 <= NW / 4) : CFG_MAP1 == 1 ? (P1W <= NW / 2 && NF + 2 <= NW / 2) : true, "warp map");
        for (int i = tid; i < NF * GPW * 32; i += NT) sts32(sb + A_CNT + i * 4, 1u << 24);
        if (tid < 64) sts32(sb + SM_CRED + tid * 4, 0u);
        cta_sync();
        TR(1, tid == 0);
        if (ww < P1W) role_p1(p, sb, id, ww, lane);
        else if (sw < NF) role_flush(p, sb, id, sw, lane);
        else if (sw == NF) role_credit1(p, sb, id, lane);
        else if (w == NW - 1) {
            uint4* owin = (uint4*)(p.ring + (CWIN + (lds32(sb + SM_MISC + 16) ^ 1)) * WIN);
            for (int i = id * 32 + lane; i < CPAIRS * 512; i += N1 * 32) __stcg(owin + i, make_uint4(0, 0, 0, 0));
            __syncwarp();
        }
    } else if (role == 1) {
        const int row0 = id % H2 * p.rows2;
        const int nrows = min((int)p.rows2, p.E - row0);
        constexpr int NTB = NT - 32, TBD = CFG_TBD;
        bool flagged = false;
        if (w < NW - 1) {
            const uint4* const src = (const uint4*)(p.m + row0);
            uint4 r2[TBD], nx[TBD];
            auto fetch = [&](int i) {
#pragma unroll
                for (int k = 0; k < TBD; k++)
                    asm volatile("ld.global.nc.v4.u32 {%0,%1,%2,%3}, [%4];" : "=r"(nx[k].x), "=r"(nx[k].y), "=r"(nx[k].z), "=r"(nx[k].w) : "l"(src + min(i + k * NTB, nrows / 2 - 1)));
            };
            fetch(tid);
            const Scale sc = get_scale(sb);
            const Mat4 wd = load_mat4(p.w_down, lane);
            const uint32_t slow = sc.allslow ? 0x60006000u : 0u;
            Mat4 ws;
#pragma unroll
            for (int k = 0; k < 4; k++) ws.b[k] = mul_bf2(wd.b[k], ((246u - (lane & 4 ? sc.eb[(k & 2) + 1] : sc.eb[k & 2])) << 7) * 0x10001u);
#pragma unroll 1
            for (int i0 = tid; 2 * (i0 - lane) < nrows; i0 += TBD * NTB) {
#pragma unroll
                for (int k = 0; k < TBD; k++) r2[k] = make_uint4(nx[k].x, nx[k].z, nx[k].y, nx[k].w);
                fetch(i0 + TBD * NTB);
                uint32_t big[2 * TBD], any = slow;
#pragma unroll
                for (int k = 0; k < TBD; k++) {
                    const int i = i0 + k * NTB;
                    float y[8];
                    mul4(make_uint4(r2[k].x, r2[k].z, r2[k].y, r2[k].w), ws, y);
                    uint32_t a[4], h[4], ta[2];
#pragma unroll
                    for (int j = 0; j < 4; j++) { a[j] = pack_h2(y[2 * j], y[2 * j + 1]); h[j] = a[j] + 0x00040004u; }
#pragma unroll
                    for (int j = 0; j < 2; j++) {
                        ta[j] = bitsel(h[2 * j], bitsel(h[2 * j + 1] >> 3, h[2 * j + 1] << 7, 0x00070007u), 0x9ff89ff8u);
                        big[2 * k + j] = a[2 * j] | a[2 * j + 1] | h[2 * j] | h[2 * j + 1];
                    }
                    any |= big[2 * k] | big[2 * k + 1];
                    sts64_if(sb + B_TA + i * 8, ta[0], ta[1], 2 * i < nrows);
                    sts32_if(sb + B_TB + i * 4, prmt(h[1], h[3], 0x7531), 2 * i < nrows);
                }
                if (__any_sync(0xffffffffu, any & 0x60006000u)) {
#pragma unroll
                    for (int k = 0; k < 2 * TBD; k++) {
                        const int r = 2 * (i0 + (k >> 1) * NTB) + (k & 1);
                        if (((big[k] | slow) & 0x60006000u) && r < nrows) { sts32(sb + B_TA + r * 4, 0u); sts16(sb + B_TB + r * 2, 0x40u); }
                    }
                    flagged = true;
                }
            }
            if (tid == 0) {
                sts32(sb + B_TA + p.rows2 * 4, 0u);
                sts16(sb + B_TB + p.rows2 * 2, 0u);
            }
            TR(8, tid == 0);
        } else if (lane == 0) spin_ge(rdy_of(p, sb, id, id / H2), H3);
        __syncwarp();
        flagged = __any_sync(0xffffffffu, __syncthreads_or(flagged));
        TR(1, tid == 0);
        if (w < P2W) {
            if (flagged) role_p2<true>(p, sb, id, w, lane);
            else role_p2<false>(p, sb, id, w, lane);
        } else if (w == P2W) role_credit(p, sb, id, lane);
    } else {
        if (w == 0) clear_queues<false>(p, sb, id, lane);
        if (tid >= 32 && tid < 33 + NPC) mbar_init(sb + SM_CNT2 + (tid - 32) * 8, 1);
        cta_sync();
        TR(1, tid == 0);
        if (w < P3W) role_p3(p, sb, id, w, lane);
        const int pc = w - P3W, n = min(((int)p.rows3 + 7) / 8 * 8 - pc * RPC, RPC);
        uint32_t *f0 = nullptr, *f1 = nullptr;
        if (pc >= 0) { f0 = opaque(rdy_of(p, sb, 160 + 32 * pc, 0)); f1 = opaque(rdy_of(p, sb, 160 + 32 * pc, 1)); }
        cta_sync();
        TR(2, tid == 0);
        if (pc >= 0 && pc < NPC && lane == 0) {
            fence_async_smem();
            if (pc >= CFG_DOUT) mbar_wait(sb + SM_CNT2 + (pc + 1 - CFG_DOUT) * 8, 0);
            if (n > 0) {
                bulk_store(g_S[0][id] + pc * RPC, sb + C_S + pc * RPC * 4, n * 4);
                bulk_store(g_S[1][id] + pc * RPC, sb + C_S + (ROWS3_MAX + pc * RPC) * 4, n * 4);
            }
            asm volatile("cp.async.bulk.commit_group;" ::: "memory");
            asm volatile("cp.async.bulk.wait_group.read 0;" ::: "memory");
            mbar_arrive(sb + SM_CNT2 + pc * 8 + 8);
            asm volatile("cp.async.bulk.wait_group 0;" ::: "memory");
            fence_gpu();
            red_rlx(f0, 1u);
            red_rlx(f1, 1u);
            if (id == 0 && pc == 0) red_rlx(&g_epoch, 1u);
            TR(12 + pc, true);
        }
        return;
    }
    cta_sync();
    TR(18, tid == 0 && role == 1);
    if (role == 0 && w == NW - 2) clear_queues<true>(p, sb, id, lane);
    tail_rows(p, role * N1 + id, w, lane);
}

__global__ void k_direct(const Params p, long long T) {
    float wd[16];
#pragma unroll
    for (int i = 0; i < 16; i++) wd[i] = __bfloat162float(p.w_down[i]);
    const float f = __bfloat162float(p.freq[0]);
    for (long long t = blockIdx.x * (long long)blockDim.x + threadIdx.x; t < T; t += (long long)gridDim.x * blockDim.x) {
        float x = __bfloat162float(__float2bfloat16(f * __bfloat162float(p.angle[t])));
        float c = __bfloat162float(__float2bfloat16(cosf(x)));
        uint2 md = down_row(__ldg(p.m + p.idx_in[t]), wd);
        red_v4(g_Sg + p.idx_out[t], c * bflo(md.x), c * bfhi(md.x), c * bflo(md.y), c * bfhi(md.y));
    }
}
__global__ void k_direct_tail(const Params p) {
    __shared__ __align__(16) float sw[96];
    load_tail_weights(p, sw, threadIdx.x);
    __syncthreads();
    uint32_t c2[4];
#pragma unroll
    for (int i = 0; i < 4; i++) c2[i] = ((const uint32_t*)p.centers)[i];
    for (int e = blockIdx.x * blockDim.x + threadIdx.x; e < p.E; e += gridDim.x * blockDim.x) {
        float4 g = __ldcg(g_Sg + e);
        __stcg(g_Sg + e, make_float4(0.f, 0.f, 0.f, 0.f));
        const float Sv[4] = {g.x, g.y, g.z, g.w};
        float4 gs, gr;
        row_gates(sw, c2, __bfloat16_as_ushort(p.dist[e]), gs, gr);
        p.out[e] = finish_row(sw + 64, gs, gr, Sv, __ldg(p.m + e));
    }
}

static bool pick_rows(int E, int n, int rows_max, int mult, uint32_t* rows, uint32_t* magic) {
    for (uint32_t r = (E + n - 1) / n; r <= (uint32_t)rows_max; r++) {
        if (r < 2 || r % mult) continue;
        uint64_t mg = ((1ull << 32) + r - 1) / r;
        uint64_t err = mg * r - (1ull << 32);
        if (err * (uint64_t)n < mg) { *rows = r; *magic = (uint32_t)mg; return true; }
    }
    return false;
}

}

extern "C" void kernel_launch(void* const* d_in, const int* in_sizes, int n_in, void* d_out, int out_size) {
    using namespace gs;
    (void)n_in; (void)out_size;
    Params p;
    p.m = (const uint2*)d_in[0];
    p.idx_in = (const int*)d_in[1];
    p.idx_out = (const int*)d_in[2];
    p.dist = (const __nv_bfloat16*)d_in[3];
    p.angle = (const __nv_bfloat16*)d_in[4];
    p.centers = (const __nv_bfloat16*)d_in[5];
    p.freq = (const __nv_bfloat16*)d_in[6];
    p.w_rbf = (const __nv_bfloat16*)d_in[7];
    p.w_sbf = (const __nv_bfloat16*)d_in[8];
    p.w_down = (const __nv_bfloat16*)d_in[9];
    p.w_up = (const __nv_bfloat16*)d_in[10];
    p.out = (uint2*)d_out;
    p.E = in_sizes[3];
    const long long T = in_sizes[1];
    p.n4 = (int)(T / 4);
    p.rows2 = p.magic2 = 0;
    p.ring = nullptr;

    static int sms = 0, rsv = 0;
    if (!sms) {
        int dev = 0;
        cudaGetDevice(&dev);
        cudaDeviceGetAttribute(&rsv, cudaDevAttrReservedSharedMemoryPerBlock, dev);
        cudaDeviceGetAttribute(&sms, cudaDevAttrMultiProcessorCount, dev);
        cudaFuncSetAttribute(k_main, cudaFuncAttributeMaxDynamicSharedMemorySize, SMEM_BYTES);
    }
    cudaStream_t st = cudaStreamPerThread;
    bool fast = (T % 4 == 0) && T > 0 && sms >= NCTA && rsv == (int)SB && p.E >= 65536 && p.E <= E_MAX &&
                p.E % 4 == 0 && (((uintptr_t)p.m | (uintptr_t)p.idx_in | (uintptr_t)p.idx_out | (uintptr_t)p.angle) & 15) == 0 &&
                pick_rows(p.E, NI, ROWS2_MAX, 2, &p.rows2, &p.magic2);
    p.nrows2 = 0u - p.rows2;
    p.rows3 = (p.E + 31) / 32;
    fast = fast && (p.rows2 * (NI - 1) + 2 <= (uint32_t)p.E);
    static const void* tkey[3] = {nullptr, nullptr, nullptr};
    static cudaTextureObject_t tex[3] = {0, 0, 0};
    static long long tlen = -1;
    const void* tptr[3] = {p.idx_in, p.idx_out, p.angle};
    for (int k = 0; fast && k < 3; k++) {
        if (tkey[k] == tptr[k] && tlen == T) continue;
        if (tkey[k]) cudaDestroyTextureObject(tex[k]);
        tkey[k] = nullptr;
        cudaResourceDesc rd = {};
        rd.resType = cudaResourceTypeLinear;
        rd.res.linear.devPtr = (void*)tptr[k];
        rd.res.linear.desc = cudaCreateChannelDesc(32, 32, k < 2 ? 32 : 0, k < 2 ? 32 : 0, cudaChannelFormatKindUnsigned);
        rd.res.linear.sizeInBytes = (size_t)T * (k < 2 ? 4 : 2);
        cudaTextureDesc td = {};
        td.readMode = cudaReadModeElementType;
        if (cudaCreateTextureObject(&tex[k], &rd, &td, nullptr) == cudaSuccess) tkey[k] = tptr[k];
        else { (void)cudaGetLastError(); fast = false; }
    }
    if (fast) tlen = T;
    p.t_in = tex[0]; p.t_out = tex[1]; p.t_ang = tex[2];
    if (fast) {
        void* ring = nullptr;
        cudaGetSymbolAddress(&ring, g_ring);
        uintptr_t a = ((uintptr_t)ring + WIN - 1) & ~(uintptr_t)(WIN - 1);
        if (a >> 32 != (a + RING_BYTES - 1) >> 32) a += RING_BYTES;
        p.ring = (unsigned char*)a;
        p.ring_lo = (uint32_t)a;
        p.ring_hi = (uint32_t)(a >> 32);
        k_main<<<NCTA, NT, SMEM_BYTES, st>>>(p);
    } else {
        k_direct<<<sms * 8, 256, 0, st>>>(p, T);
        k_direct_tail<<<sms * 4, 256, 0, st>>>(p);
    }
}
```

```cpp
#include <cuda_runtime.h>
#include <cuda_bf16.h>
#include <stdint.h>

#define CFG_N1 56
#define CFG_NI 22
#define CFG_NW 28
#define CFG_P1W 14
#define CFG_GPW 2
#define CFG_KR 1
#define CFG_QPW 3
#define CFG_TG 2
#define CFG_PMASK 8
#define CFG_PSTREAK 1
#define CFG_NBT 1
#define CFG_KM 5
#define CFG_KN 9
#define CFG_TBD 3
#define CFG_P0 500
#define CFG_PFD 200
#define CFG_C1SLEEP 200
#define CFG_PK1 6
#define CFG_PK2 8
#define CFG_PK3 11
#define CFG_CLN 8
#define CFG_CLS 500
#define CFG_DOUT 2
#define CFG_TH 14
#define CFG_TS 200
#define CFG_POLL 64
#define CFG_HINT 20000
#define CFG_BSLEEP 100
#define CFG_CSLEEP 400
#define CFG_FSLEEP 100
#define CFG_PSLEEP 100
#define CFG_DRY 1
#define CFG_PROBES 4

namespace gs {

constexpr int E_MAX = 640000;
constexpr int N1 = CFG_N1, NI = CFG_NI, N2 = 2 * NI, N3 = 32, NCTA = N1 + N2 + N3;
constexpr int H2 = NI, H3 = N3 / 2;
constexpr int NB = NI * N3;
constexpr int NW = CFG_NW, NT = NW * 32;
constexpr int GPW = CFG_GPW, NF = (NI + GPW - 1) / GPW;
constexpr int QPW = CFG_QPW, NBT = CFG_NBT;
constexpr int P1W = CFG_P1W, P2W = (N1 + QPW - 1) / QPW, P3W = NI;
constexpr int NQ2 = 64;
constexpr int ROWS2_MAX = ((E_MAX + NI - 1) / NI + 31) / 8 * 8;
constexpr int ROWS3_MAX = (E_MAX / 32 + 31) / 32 * 32;
constexpr int NTAIL = N1 + N2;
constexpr int NPC = 5, WPP = 5, RPC = NTAIL * WPP * 8;
constexpr int GUARD = 1 << 26;
static_assert(NCTA % 4 == 0 && NCTA <= 192, "roles come in CTA pairs, per partition");
static_assert((GPW == 2 || GPW == 4) && QPW >= NBT && QPW <= 4 && NI <= 32 && N1 <= 62, "queue ownership");
static_assert(P1W + NF + 2 <= NW && P2W + 2 <= NW && P3W + 5 <= NW && P1W * 256 + 64 < 8192, "warp roles");
static_assert(ROWS2_MAX + 8 <= 32768 && ROWS3_MAX <= 32768, "index bits");

constexpr uint32_t SB = 1024;
constexpr int SM_DONE = 0, SM_DONE2 = 8;
constexpr int SM_MISC = 16;
constexpr int SM_FIN = 48;
constexpr int SM_STAT = 64;
constexpr int SM_DBAR = 128;
constexpr int SM_W = 256;
constexpr int SM_PUB = SM_W + 384;
constexpr int SM_PROBE = SM_PUB + 768;
constexpr int SM_CRED = 1792;
constexpr int SM_CNT2 = SM_CRED;
constexpr int SM_DATA = 2048;
constexpr int cmax(int a, int b) { return a > b ? a : b; }
constexpr int A_CNT = SM_DATA;
constexpr int KR = CFG_KR, LISTB = (GPW * 32 + 8 * KR) * 4;
constexpr int A_LIST = A_CNT + NF * GPW * 128;
constexpr int A_ST = (A_LIST + NF * LISTB + 127) / 128 * 128;
constexpr int A_END = A_ST + NB * 256;
constexpr int B_TB = SM_DATA;
constexpr int B_TA = SM_DATA + (ROWS2_MAX + 8) * 2;
constexpr int B_END = SM_DATA + (ROWS2_MAX + 8) * 6;
constexpr int C_S = SM_DATA;
constexpr int C_END = C_S + ROWS3_MAX * 8;
constexpr int T_G = SM_DATA, TWB = 4096 + 2048 + 512, T_END = T_G + NPC * WPP * TWB;
constexpr int ZEND = cmax(A_END, C_END);
constexpr int SM_ZERO = (cmax(C_END, T_END) + 127) / 128 * 128;
constexpr int SMEM_BYTES = cmax(cmax(A_END, B_END), SM_ZERO + 4096);
static_assert(SMEM_BYTES <= 232448 && SM_PROBE + 128 <= SM_CRED, "shared memory");
static_assert(NPC * RPC >= ROWS3_MAX && NPC * WPP + 2 <= NW, "tail");

constexpr uint32_t FIN = 0x80000000u;

constexpr uint32_t WIN = 524288;
constexpr int CWIN = N2 + N3, NWIN = CWIN + 2, CPAIRS = 31;
constexpr uint32_t PROBE_OFF = (uint32_t)NWIN * WIN;
constexpr int NPROBE = 16;
static_assert(NWIN <= NCTA && NPROBE <= NW, "windows");
constexpr size_t RING_BYTES = (size_t)PROBE_OFF + WIN;
__device__ __align__(128) unsigned char g_ring[2 * RING_BYTES + WIN];
__device__ __align__(128) uint32_t g_S[2][32][ROWS3_MAX];
__device__ __align__(128) float4 g_Sg[E_MAX];
__device__ uint32_t g_dirty[E_MAX / 32];
__device__ uint32_t g_epoch;

#define TR(ev, on)
#define ACC_DECL
#define ACC(i, n)
#define ACC_SAVE

struct Params {
    const uint2* m;
    const int* idx_in;
    const int* idx_out;
    const __nv_bfloat16* dist;
    const __nv_bfloat16* angle;
    const __nv_bfloat16* centers;
    const __nv_bfloat16* freq;
    const __nv_bfloat16* w_rbf;
    const __nv_bfloat16* w_sbf;
    const __nv_bfloat16* w_down;
    const __nv_bfloat16* w_up;
    uint2* out;
    unsigned char* ring;
    cudaTextureObject_t t_in, t_out, t_ang;
    int E, n4;
    uint32_t rows2, nrows2, magic2, rows3;
    uint32_t ring_lo, ring_hi;
};

__device__ __forceinline__ float bflo(uint32_t w) { return __uint_as_float(w << 16); }
__device__ __forceinline__ float bfhi(uint32_t w) { return __uint_as_float(w & 0xffff0000u); }
__device__ __forceinline__ uint32_t pack_bf2(float lo, float hi) {
    uint32_t r;
    asm("cvt.rn.bf16x2.f32 %0, %1, %2;" : "=r"(r) : "f"(hi), "f"(lo));
    return r;
}
__device__ __forceinline__ uint32_t mul_bf2(uint32_t a, uint32_t b) {
    uint32_t r;
    asm("mul.rn.bf16x2 %0, %1, %2;" : "=r"(r) : "r"(a), "r"(b));
    return r;
}
__device__ __forceinline__ uint32_t sub_bf2(uint32_t a, uint32_t b) {
    uint32_t r;
    asm("sub.rn.bf16x2 %0, %1, %2;" : "=r"(r) : "r"(a), "r"(b));
    return r;
}
__device__ __forceinline__ uint32_t maxabs_bf2(uint32_t a, uint32_t b) {
    uint32_t r;
    asm("max.NaN.xorsign.abs.bf16x2 %0, %1, %2;" : "=r"(r) : "r"(a), "r"(b));
    return r;
}
__device__ __forceinline__ void mbar_init(uint32_t a, uint32_t n) {
    asm volatile("mbarrier.init.shared::cta.b64 [%0], %1;" ::"r"(a), "r"(n) : "memory");
}
__device__ __forceinline__ void mbar_arrive(uint32_t a) {
    asm volatile("mbarrier.arrive.shared::cta.b64 _, [%0];" ::"r"(a) : "memory");
}
__device__ __forceinline__ void mbar_arrive_if(uint32_t a, bool on) {
    asm volatile("{.reg .pred q; setp.ne.u32 q, %1, 0; @q mbarrier.arrive.shared::cta.b64 _, [%0];}" ::"r"(a), "r"((uint32_t)on) : "memory");
}
__device__ __forceinline__ void mbar_wait(uint32_t a, uint32_t parity) {
    uint32_t ok;
    int guard = 0;
    do {
        asm volatile("{.reg .pred p; mbarrier.try_wait.parity.shared::cta.b64 p, [%1], %2, %3; selp.u32 %0, 1, 0, p;}"
                     : "=r"(ok) : "r"(a), "r"(parity), "r"(CFG_HINT) : "memory");
        if (!ok) {
            if (++guard > GUARD) __trap();
        }
    } while (!ok);
}
__device__ __forceinline__ void cta_sync() { __syncwarp(); __syncthreads(); }
__device__ __forceinline__ void bar_sync(int id, int n) { asm volatile("bar.sync %0, %1;" ::"r"(id), "r"(n) : "memory"); }
__device__ __forceinline__ bool mbar_test(uint32_t a, uint32_t parity) {
    uint32_t ok;
    asm volatile("{.reg .pred p; mbarrier.test_wait.parity.shared::cta.b64 p, [%1], %2; selp.u32 %0, 1, 0, p;}"
                 : "=r"(ok) : "r"(a), "r"(parity) : "memory");
    return ok;
}
__device__ __forceinline__ uint32_t ld_acq(const uint32_t* p) {
    uint32_t v;
    asm volatile("ld.acquire.gpu.global.u32 %0, [%1];" : "=r"(v) : "l"(p) : "memory");
    return v;
}
__device__ __forceinline__ uint32_t ld_rlx(const uint32_t* p) {
    uint32_t v;
    asm volatile("ld.relaxed.gpu.global.u32 %0, [%1];" : "=r"(v) : "l"(p) : "memory");
    return v;
}
__device__ __forceinline__ void st_rlx(uint32_t* p, uint32_t v) {
    asm volatile("st.relaxed.gpu.global.u32 [%0], %1;" ::"l"(p), "r"(v) : "memory");
}
__device__ __forceinline__ void red_rlx(uint32_t* p, uint32_t v) {
    asm volatile("red.relaxed.gpu.global.add.u32 [%0], %1;" ::"l"(p), "r"(v) : "memory");
}
__device__ __forceinline__ uint32_t spin_ge(const uint32_t* p, uint32_t target) {
    int guard = 0;
    while (ld_rlx(p) < target) {
        __nanosleep(CFG_POLL);
        if (++guard > GUARD) __trap();
    }
    return ld_acq(p);
}
__device__ __forceinline__ void fence_gpu() { asm volatile("fence.acq_rel.gpu;" ::: "memory"); }
__device__ __forceinline__ void fence_async_smem() { asm volatile("fence.proxy.async.shared::cta;" ::: "memory"); }
__device__ __forceinline__ void fence_async_all() { asm volatile("fence.proxy.async;" ::: "memory"); }
__device__ __forceinline__ void bulk_store(void* g, uint32_t s, uint32_t bytes) {
    asm volatile("cp.async.bulk.global.shared::cta.bulk_group [%0], [%1], %2;" ::"l"(g), "r"(s), "r"(bytes) : "memory");
}
__device__ __forceinline__ void cp16(uint32_t s, const void* g, bool on) {
    asm volatile("{.reg .pred q; setp.ne.u32 q, %2, 0; @q cp.async.cg.shared.global [%0], [%1], 16;}" ::"r"(s), "l"(g), "r"((uint32_t)on) : "memory");
}
__device__ __forceinline__ void cp16z(uint32_t s, const void* g, int bytes) {
    asm volatile("cp.async.cg.shared.global [%0], [%1], 16, %2;" ::"r"(s), "l"(g), "r"(bytes) : "memory");
}
__device__ __forceinline__ void cp_commit() { asm volatile("cp.async.commit_group;" ::: "memory"); }
template <int N> __device__ __forceinline__ void cp_wait() { asm volatile("cp.async.wait_group %0;" ::"n"(N) : "memory"); }
__device__ __forceinline__ uint32_t atoms_add(uint32_t a, uint32_t v) {
    uint32_t o;
    asm volatile("atom.shared.add.u32 %0, [%1], %2;" : "=r"(o) : "r"(a), "r"(v) : "memory");
    return o;
}
__device__ __forceinline__ void sts32(uint32_t a, uint32_t v) { asm volatile("st.shared.u32 [%0], %1;" ::"r"(a), "r"(v) : "memory"); }
__device__ __forceinline__ void sts16(uint32_t a, uint32_t v) { asm volatile("st.shared.u16 [%0], %1;" ::"r"(a), "h"((uint16_t)v) : "memory"); }
__device__ __forceinline__ void sts64(uint32_t a, uint32_t x, uint32_t y) { asm volatile("st.shared.v2.u32 [%0], {%1,%2};" ::"r"(a), "r"(x), "r"(y) : "memory"); }
__device__ __forceinline__ uint32_t lds32(uint32_t a) {
    uint32_t v;
    asm volatile("ld.shared.u32 %0, [%1];" : "=r"(v) : "r"(a) : "memory");
    return v;
}
__device__ __forceinline__ uint2 lds64v(uint32_t a) {
    uint2 v;
    asm volatile("ld.volatile.shared.v2.u32 {%0,%1}, [%2];" : "=r"(v.x), "=r"(v.y) : "r"(a) : "memory");
    return v;
}
__device__ __forceinline__ uint32_t lds32v(uint32_t a) {
    uint32_t v;
    asm volatile("ld.volatile.shared.u32 %0, [%1];" : "=r"(v) : "r"(a) : "memory");
    return v;
}
__device__ __forceinline__ uint4 lds128(uint32_t a) {
    uint4 v;
    asm volatile("ld.shared.v4.u32 {%0,%1,%2,%3}, [%4];" : "=r"(v.x), "=r"(v.y), "=r"(v.z), "=r"(v.w) : "r"(a) : "memory");
    return v;
}
__device__ __forceinline__ void sts128(uint32_t a, uint4 v) {
    asm volatile("st.shared.v4.u32 [%0], {%1,%2,%3,%4};" ::"r"(a), "r"(v.x), "r"(v.y), "r"(v.z), "r"(v.w) : "memory");
}
#define LD_Q "ld.relaxed.gpu.global"
__device__ __forceinline__ uint4 ldg_q128(const void* p) {
    uint4 v;
    asm volatile(LD_Q ".v4.u32 {%0,%1,%2,%3}, [%4];"
                 : "=r"(v.x), "=r"(v.y), "=r"(v.z), "=r"(v.w) : "l"(p) : "memory");
    return v;
}
__device__ __forceinline__ uint2 ldg_q64(const void* p) {
    uint2 v;
    asm volatile(LD_Q ".v2.u32 {%0,%1}, [%2];" : "=r"(v.x), "=r"(v.y) : "l"(p) : "memory");
    return v;
}
__device__ __forceinline__ void red_v4(float4* p, float a, float b, float c, float d) {
    asm volatile("red.global.add.v4.f32 [%0], {%1,%2,%3,%4};" ::"l"(p), "f"(a), "f"(b), "f"(c), "f"(d) : "memory");
}
__device__ __forceinline__ uint2 down_row(uint2 r, const float* wd) {
    float x0 = bflo(r.x), x1 = bfhi(r.x), x2 = bflo(r.y), x3 = bfhi(r.y);
    float y[4];
#pragma unroll
    for (int j = 0; j < 4; j++) y[j] = x0 * wd[j] + x1 * wd[4 + j] + x2 * wd[8 + j] + x3 * wd[12 + j];
    return make_uint2(pack_bf2(y[0], y[1]), pack_bf2(y[2], y[3]));
}
__device__ __forceinline__ uint32_t prmt(uint32_t a, uint32_t b, uint32_t s) {
    uint32_t r;
    asm("prmt.b32 %0, %1, %2, %3;" : "=r"(r) : "r"(a), "r"(b), "r"(s));
    return r;
}
__device__ __forceinline__ uint32_t bitsel(uint32_t a, uint32_t b, uint32_t m) {
    uint32_t r;
    asm("lop3.b32 %0, %1, %2, %3, 0xE4;" : "=r"(r) : "r"(a), "r"(b), "r"(m));
    return r;
}
__device__ __forceinline__ uint32_t pack_h2(float lo, float hi) {
    uint32_t r;
    asm("cvt.rn.f16x2.f32 %0, %1, %2;" : "=r"(r) : "f"(hi), "f"(lo));
    return r;
}
__device__ __forceinline__ uint32_t mul_h2(uint32_t a, uint32_t b) {
    uint32_t r;
    asm("mul.rn.f16x2 %0, %1, %2;" : "=r"(r) : "r"(a), "r"(b));
    return r;
}
__device__ __forceinline__ uint32_t lds32nv(uint32_t a) {
    uint32_t v;
    asm volatile("ld.shared.u32 %0, [%1];" : "=r"(v) : "r"(a));
    return v;
}
__device__ __forceinline__ uint32_t lds16nv(uint32_t a) {
    uint32_t v;
    asm volatile("ld.shared.u16 %0, [%1];" : "=r"(v) : "r"(a));
    return v;
}
#define ST_Q "st.relaxed.gpu.global"
__device__ __forceinline__ void stg_q128(void* p, uint32_t a, uint32_t b, uint32_t c, uint32_t d, bool on) {
    asm volatile("{.reg .pred q; setp.ne.u32 q, %5, 0; @q " ST_Q ".v4.u32 [%0], {%1,%2,%3,%4};}"
                 ::"l"(p), "r"(a), "r"(b), "r"(c), "r"(d), "r"((uint32_t)on) : "memory");
}
__device__ __forceinline__ void stg_q64(void* p, uint32_t a, uint32_t b, bool on) {
    asm volatile("{.reg .pred q; setp.ne.u32 q, %3, 0; @q " ST_Q ".v2.u32 [%0], {%1,%2};}"
                 ::"l"(p), "r"(a), "r"(b), "r"((uint32_t)on) : "memory");
}
__device__ __forceinline__ void st_rlx_if(uint32_t* p, uint32_t v, bool on) {
    asm volatile("{.reg .pred q; setp.ne.u32 q, %2, 0; @q st.relaxed.gpu.global.u32 [%0], %1;}" ::"l"(p), "r"(v), "r"((uint32_t)on) : "memory");
}
__device__ __forceinline__ void ldq128_keep(uint4& v, const void* p, bool on) {
    asm volatile("{.reg .pred q; setp.ne.u32 q, %5, 0; @q ld.relaxed.gpu.global.v4.u32 {%0,%1,%2,%3}, [%4];}"
                 : "+r"(v.x), "+r"(v.y), "+r"(v.z), "+r"(v.w) : "l"(p), "r"((uint32_t)on) : "memory");
}
__device__ __forceinline__ void reds_add(uint32_t a, uint32_t v) { asm volatile("red.shared.add.u32 [%0], %1;" ::"r"(a), "r"(v) : "memory"); }
__device__ __forceinline__ void sts32_if(uint32_t a, uint32_t v, bool on) {
    asm volatile("{.reg .pred q; setp.ne.u32 q, %2, 0; @q st.shared.u32 [%0], %1;}" ::"r"(a), "r"(v), "r"((uint32_t)on) : "memory");
}
__device__ __forceinline__ void sts64_if(uint32_t a, uint32_t x, uint32_t y, bool on) {
    asm volatile("{.reg .pred q; setp.ne.u32 q, %3, 0; @q st.shared.v2.u32 [%0], {%1,%2};}" ::"r"(a), "r"(x), "r"(y), "r"((uint32_t)on) : "memory");
}
__device__ __forceinline__ void lds128_keep(uint4& v, uint32_t a, bool on) {
    asm volatile("{.reg .pred q; setp.ne.u32 q, %5, 0; @q ld.volatile.shared.v4.u32 {%0,%1,%2,%3}, [%4];}"
                 : "+r"(v.x), "+r"(v.y), "+r"(v.z), "+r"(v.w) : "r"(a), "r"((uint32_t)on) : "memory");
}
__device__ __forceinline__ void or3_if(uint32_t& x, uint32_t a, uint32_t b, bool on) {
    asm("{.reg .pred q; setp.ne.u32 q, %3, 0; @q lop3.b32 %0, %0, %1, %2, 0xfe;}" : "+r"(x) : "r"(a), "r"(b), "r"((uint32_t)on));
}
__device__ __forceinline__ uint32_t clk() {
    uint32_t t;
    asm volatile("mov.u32 %0, %%clock;" : "=r"(t) :: "memory");
    return t;
}
__device__ __forceinline__ void sg_add(int row, float a, float b, float c, float d) {
    red_v4(g_Sg + row, a, b, c, d);
    st_rlx(g_dirty + (row >> 5), 1u);
}
__device__ __forceinline__ void slow_add(const uint2* m, uint32_t sb, int in, int out, float c) {
    const uint2 r = __ldg(m + in);
    const float x[4] = {bflo(r.x), bfhi(r.x), bflo(r.y), bfhi(r.y)};
    float y[4] = {0.f, 0.f, 0.f, 0.f};
#pragma unroll
    for (int k = 0; k < 4; k++) {
        const uint4 q = lds128(sb + SM_W + 320 + k * 16);
        y[0] = k ? y[0] + x[k] * __uint_as_float(q.x) : x[k] * __uint_as_float(q.x);
        y[1] = k ? y[1] + x[k] * __uint_as_float(q.y) : x[k] * __uint_as_float(q.y);
        y[2] = k ? y[2] + x[k] * __uint_as_float(q.z) : x[k] * __uint_as_float(q.z);
        y[3] = k ? y[3] + x[k] * __uint_as_float(q.w) : x[k] * __uint_as_float(q.w);
    }
    const uint32_t lo = pack_bf2(y[0], y[1]), hi = pack_bf2(y[2], y[3]);
    sg_add(out, c * bflo(lo), c * bfhi(lo), c * bflo(hi), c * bfhi(hi));
}

struct Mat4 { uint32_t b[4]; };
__device__ __forceinline__ Mat4 load_mat4(const __nv_bfloat16* w, int lane) {
    const unsigned short* u = (const unsigned short*)w + (lane >> 2 & 1);
    const bool on = lane >> 3 == (lane & 3);
    Mat4 m;
#pragma unroll
    for (int k = 0; k < 4; k++) m.b[k] = on ? u[(k & 1) * 8 + (k & 2)] | (uint32_t)u[(k & 1) * 8 + 4 + (k & 2)] << 16 : 0u;
    return m;
}
__device__ __forceinline__ void mul4(const uint4& x, const Mat4& m, float (&y)[8]) {
    asm("mma.sync.aligned.m16n8k16.row.col.f32.bf16.bf16.f32 {%0,%1,%2,%3}, {%8,%9,%10,%11}, {%12,%13}, {%16,%16,%16,%16};\n\t"
        "mma.sync.aligned.m16n8k16.row.col.f32.bf16.bf16.f32 {%4,%5,%6,%7}, {%8,%9,%10,%11}, {%14,%15}, {%16,%16,%16,%16};"
        : "=&f"(y[0]), "=&f"(y[1]), "=&f"(y[4]), "=&f"(y[5]), "=&f"(y[2]), "=&f"(y[3]), "=&f"(y[6]), "=&f"(y[7])
        : "r"(x.x), "r"(x.z), "r"(x.y), "r"(x.w), "r"(m.b[0]), "r"(m.b[1]), "r"(m.b[2]), "r"(m.b[3]), "f"(0.f));
}

struct Scale { uint32_t eb[4]; bool allslow; };
__device__ __forceinline__ void md_stats(const uint4& in, const Mat4& wd, int lane) {
    float y[8];
    mul4(in, wd, y);
    uint32_t mx[4], se[4];
#pragma unroll
    for (int c = 0; c < 4; c++) {
        uint32_t a = __float_as_uint(y[c]) & 0x7fffffffu, b = __float_as_uint(y[4 + c]) & 0x7fffffffu;
        if (a >= 0x7f800000u) a = 0;
        if (b >= 0x7f800000u) b = 0;
        mx[c] = __reduce_max_sync(0xffffffffu, max(a, b));
        se[c] = __reduce_add_sync(0xffffffffu, (a >> 23) + (b >> 23) + (a ? 1u << 20 : 0u) + (b ? 1u << 20 : 0u));
    }
    if (lane < 4) {
        asm volatile("red.shared.max.u32 [%0], %1;" ::"r"(SB + SM_STAT + lane * 4), "r"(lane == 0 ? mx[0] : lane == 1 ? mx[1] : lane == 2 ? mx[2] : mx[3]) : "memory");
        reds_add(SB + SM_STAT + 16 + lane * 4, lane == 0 ? se[0] : lane == 1 ? se[1] : lane == 2 ? se[2] : se[3]);
    }
}
__device__ __forceinline__ Scale get_scale(uint32_t sb) {
    Scale s;
    s.allslow = false;
#pragma unroll
    for (int k = 0; k < 4; k++) {
        const uint32_t mx = lds32(sb + SM_STAT + 4 * k), se = lds32(sb + SM_STAT + 16 + 4 * k);
        const uint32_t mean = (uint32_t)__fdividef((float)(se & 0xfffffu), (float)max(se >> 20, 1u));
        uint32_t eb = min(min((mx + 0x6e0000u) >> 23, mean + 5u), 227u);
        if (eb < 27u) { s.allslow = s.allslow || mx != 0; eb = 27u; }
        if (eb > 170u) s.allslow = true;
        s.eb[k] = eb;
    }
    return s;
}

__device__ __forceinline__ uint32_t probe_rt(uint32_t* p) {
    uint32_t best = 0xffffffffu;
#pragma unroll 1
    for (int r = 0; r < CFG_PROBES; r++) {
        const uint32_t t0 = clock();
        uint32_t v;
        asm volatile("atom.relaxed.gpu.global.add.u32 %0, [%1], 1;" : "=r"(v) : "l"(p) : "memory");
        if (v > 100000u) __trap();
        const uint32_t t1 = clock();
        best = min(best, t1 - t0);
    }
    return best;
}
__device__ __forceinline__ uint32_t* pub_ptr(const Params& p, int blk, uint32_t sel) {
    const int pr = blk / 44;
    return (uint32_t*)(p.ring + PROBE_OFF + (pr ? 4096u << pr : 0u) + (sel << 12) + 2176 + (blk - pr * 44) * 32);
}
__device__ __forceinline__ void probe(const Params& p, uint32_t sb, int w, int lane) {
    const int blk = blockIdx.x, pr = w >> 1;
    uint32_t off = PROBE_OFF + blk * 16 + (pr ? 4096u << pr : 0u);
    if (pr == 7) off = blk < NWIN ? blk * WIN + 4064 : PROBE_OFF + 3584 + blk % 16 * 32;
    off += (w & 1) * 4096;
    if (lane < 8) st_rlx((uint32_t*)(p.ring + (off & ~31u)) + lane, 0u);
    if (lane == 0) sts32(sb + SM_PROBE + w * 4, probe_rt((uint32_t*)(p.ring + off)));
}
__device__ __forceinline__ void assign_role(const Params& p, uint32_t sb, int lane) {
    {
        const bool x = lane < 8 && lds32(sb + SM_PROBE + lane * 8 + 4) < lds32(sb + SM_PROBE + lane * 8);
        const uint32_t near = __ballot_sync(0xffffffffu, x), bits = near & 1 ? ~near | 1u : near;
        const uint32_t tag = (lds32(sb + SM_MISC + 16) + 1) << 30;
        if (lane < 16) st_rlx(pub_ptr(p, blockIdx.x, lane >> 3) + (lane & 7), tag | (bits & 0xffu));
        constexpr int K = (NCTA + 31) / 32;
        __nanosleep(CFG_P0);
        uint32_t v[K], bad;
        int guard = 0;
        do {
            bad = 0;
#pragma unroll
            for (int k = 0; k < K; k++) {
                const int b = min(lane + 32 * k, NCTA - 1);
                v[k] = ld_rlx(pub_ptr(p, b, near >> (b / 44) & 1));
                bad |= v[k] ^ tag;
            }
            bad = __any_sync(0xffffffffu, bad >> 30);
            if (bad) __nanosleep(CFG_PSLEEP);
            if (++guard > GUARD) __trap();
        } while (bad);
#pragma unroll
        for (int k = 0; k < K; k++) sts32(sb + SM_PUB + (lane + 32 * k) * 4, v[k]);
    }
    __syncwarp();
    constexpr int NP = NCTA / 2, NTAB = H2 + H3;
    const int me = blockIdx.x >> 1, odd = blockIdx.x & 1;
    uint32_t pp[3], key[3];
    int n1 = 0;
#pragma unroll
    for (int k = 0; k < 3; k++) {
        const int i = lane + 32 * k;
        pp[k] = lds32(sb + SM_PUB + min(i, NP - 1) * 8) & 1;
        key[k] = (i * CFG_KM % CFG_KN) << 8 | i;
        n1 += 2 * __popc(__ballot_sync(0xffffffffu, i < NP && pp[k]));
    }
    bool fixed = n1 < NTAB || NCTA - n1 < NTAB;
    if (fixed) {
        n1 = NP / 2 * 2;
        pp[0] = pp[1] = pp[2] = lane & 1;
    }
    const uint32_t mine = __shfl_sync(0xffffffffu, (me < 32 ? key[0] : me < 64 ? key[1] : key[2]) * 2 + (me < 32 ? pp[0] : me < 64 ? pp[1] : pp[2]), me & 31);
    const int part = mine & 1;
    int pos = odd;
#pragma unroll
    for (int k = 0; k < 3; k++) pos += 2 * __popc(__ballot_sync(0xffffffffu, lane + 32 * k < NP && pp[k] == (uint32_t)part && key[k] < mine / 2));
    const int role = pos < H2 ? 1 : pos < NTAB ? 2 : 0;
    const int id = pos < H2 ? part * H2 + pos : pos < NTAB ? part * H3 + pos - H2 : (part ? NCTA - n1 - NTAB : 0) + pos - NTAB;
    const uint32_t v = lds32(sb + SM_PUB + lane * 4);
    uint32_t lin = 0;
#pragma unroll
    for (int b = 0; b < 6; b++) lin |= (__popc(__ballot_sync(0xffffffffu, (v >> (b + 1)) & 1)) > 16 ? 1u : 0u) << b;
    if (lane == 0) {
        sts32(sb + SM_MISC, role << 8 | id);
        sts32(sb + SM_MISC + 4, lin);
        sts32(sb + SM_MISC + 8, NCTA - n1 - NTAB);
        sts32(sb + SM_MISC + 20, part);
        sts32(sb + SM_MISC + 12, role == 0 ? id : role == 1 ? N1 + id : N1 + N2 + id);
    }
}
__device__ __forceinline__ uint32_t sel_of(uint32_t sb, int widx, uint32_t k, int part) {
    return (__popc(k & lds32(sb + SM_MISC + 4)) ^ (lds32(sb + SM_PUB + widx * 4) >> 7) ^ part) & 1;
}
__device__ __forceinline__ uint32_t gran_off(uint32_t sb, int widx, int k, int part) { return (2 * k + sel_of(sb, widx, k, part)) << 12; }
__device__ __forceinline__ uint32_t q1a_off(uint32_t sb, int src, int blk, int part) { return gran_off(sb, 2 * blk + part, src >> 1, part) + (src & 1) * 2048; }
__device__ __forceinline__ uint32_t q1h_off(uint32_t sb, int src, int blk, int part) { return gran_off(sb, 2 * blk + part, 32 + (src >> 2), part) + (src & 3) * 1024; }
__device__ __forceinline__ uint32_t* ctl_word(const Params& p, uint32_t sb, int k, int word, int part) {
    const int widx = CWIN + lds32(sb + SM_MISC + 16);
    return (uint32_t*)(p.ring + (widx * WIN + ((2 * k + sel_of(sb, widx, k, part)) << 12))) + word;
}
__device__ __forceinline__ uint32_t* cred1_of(const Params& p, uint32_t sb, int src) { return ctl_word(p, sb, src >> 3, (src & 7) * 128, src >= (int)lds32(sb + SM_MISC + 8)); }
__device__ __forceinline__ uint32_t* fin1_of(const Params& p, uint32_t sb, int dst) { return ctl_word(p, sb, 8 + (dst >> 3), (dst & 7) * 128, dst / H2); }
__device__ __forceinline__ uint32_t* cred2_of(const Params& p, uint32_t sb, int src) { return ctl_word(p, sb, 16 + (src >> 3), (src & 7) * 128, src / H2); }
__device__ __forceinline__ uint32_t* fin2_of(const Params& p, uint32_t sb, int dst) { return ctl_word(p, sb, 24 + (dst >> 3), (dst & 7) * 128, dst / H3); }
__device__ __forceinline__ uint32_t* rdy_of(const Params& p, uint32_t sb, int word, int part) { return ctl_word(p, sb, 28, word, part); }
__device__ __forceinline__ uint32_t q2_off(uint32_t sb, int blk, int dst) {
    return (N2 + dst) * WIN + gran_off(sb, N2 + dst, (blk >> 1) * 4 + (blk & 1), dst / H3);
}
template <bool IS1>
__device__ __forceinline__ void clear_queues(const Params& p, uint32_t sb, int id, int lane) {
    constexpr int NA = (N1 + 1) / 2, NG = NA + (N1 + 3) / 4, N = IS1 ? NG * N2 : NI * 2;
    if (IS1) {
#pragma unroll 1
        for (int k = 0; k < 8; k++) sts128(sb + SM_ZERO + (k * 32 + lane) * 16, make_uint4(0, 0, 0, 0));
        if (lane == 0) spin_ge(rdy_of(p, sb, 320, lds32(sb + SM_MISC + 20)), NTAIL);
    }
    __syncwarp();
    fence_async_smem();
    for (int k = IS1 ? id + (lane < CFG_CLN ? lane : N) * N1 : lane; k < N; k += IS1 ? CFG_CLN * N1 : 32) {
        if (IS1 && k >= CFG_CLN * N1) __nanosleep(CFG_CLS);
        const int wi = k / NG, g = k - wi * NG;
        const uint32_t off = IS1 ? wi * WIN + gran_off(sb, wi, g < NA ? g : 32 + g - NA, wi & 1) : q2_off(sb, k >> 1, id) + (k & 1) * 16384;
        bulk_store(p.ring + off, sb + SM_ZERO, 4096);
    }
    asm volatile("cp.async.bulk.commit_group;" ::: "memory");
    asm volatile("cp.async.bulk.wait_group 0;" ::: "memory");
    TR(21, IS1 && lane == 0);
    if (!IS1) {
        fence_async_all();
        __syncwarp();
        fence_gpu();
        if (lane < NI) red_rlx(rdy_of(p, sb, id / H3 * H2 + lane, id / H3), 1u);
    }
    __syncwarp();
}

struct In8 { uint4 a[2], o[2]; uint2 g[2]; };
__device__ __forceinline__ void p1_load(const Params& p, In8& r, int i4) {
#pragma unroll
    for (int u = 0; u < 2; u++) {
        [[maybe_unused]] uint32_t x, y;
        asm volatile("tex.1d.v4.u32.s32 {%0,%1,%2,%3}, [%4, {%5}];" : "=r"(r.a[u].x), "=r"(r.a[u].y), "=r"(r.a[u].z), "=r"(r.a[u].w) : "l"(p.t_in), "r"(i4 + u * 32));
        asm volatile("tex.1d.v4.u32.s32 {%0,%1,%2,%3}, [%4, {%5}];" : "=r"(r.o[u].x), "=r"(r.o[u].y), "=r"(r.o[u].z), "=r"(r.o[u].w) : "l"(p.t_out), "r"(i4 + u * 32));
        asm volatile("tex.1d.v4.u32.s32 {%0,%1,%2,%3}, [%4, {%5}];" : "=r"(r.g[u].x), "=r"(r.g[u].y), "=r"(x), "=r"(y) : "l"(p.t_ang), "r"(i4 + u * 32));
    }
}
__device__ __forceinline__ uint32_t imad(uint32_t a, uint32_t b, uint32_t c) {
    uint32_t r;
    asm("mad.lo.u32 %0, %1, %2, %3;" : "=r"(r) : "r"(a), "r"(b), "r"(c));
    return r;
}
__device__ __forceinline__ unsigned char* ring_ptr(const Params& p, uint32_t lo) {
    uint64_t r;
    asm("mov.b64 %0, {%1, %2};" : "=l"(r) : "r"(lo), "r"(p.ring_hi));
    return (unsigned char*)r;
}
__device__ __forceinline__ uint32_t keep32(uint32_t x) {
    return __shfl_sync(0xffffffffu, x, threadIdx.x & 31);
}
__device__ __forceinline__ uint32_t opaque32(uint32_t x) {
    asm volatile("" : "+r"(x));
    return x;
}
template <typename T> __device__ __forceinline__ T* opaque(T* p) {
    asm volatile("" : "+l"(p));
    return p;
}
template <int LUT> __device__ __forceinline__ uint32_t lop3(uint32_t a, uint32_t b, uint32_t c) {
    uint32_t r;
    asm("lop3.b32 %0, %1, %2, %3, %4;" : "=r"(r) : "r"(a), "r"(b), "r"(c), "n"(LUT));
    return r;
}
__device__ __forceinline__ uint32_t dp4(uint32_t a, uint32_t b, uint32_t c) {
    uint32_t r;
    asm("dp4a.u32.u32 %0, %1, %2, %3;" : "=r"(r) : "r"(a), "r"(b), "r"(c));
    return r;
}
__device__ __forceinline__ uint32_t dp2(uint32_t a, uint32_t b, uint32_t c) {
    uint32_t r;
    asm("dp2a.lo.u32.u32 %0, %1, %2, %3;" : "=r"(r) : "r"(a), "r"(b), "r"(c));
    return r;
}
__device__ __forceinline__ void p1_put(uint32_t sb, uint32_t wa, uint32_t wb, uint32_t old, bool on) {
    asm volatile("{.reg .pred q; setp.ne.u32 q, %3, 0; @q st.shared.v2.u32 [%0], {%1,%2};}"
                 ::"r"(sb + A_ST + prmt(old, wb, 0xf762)), "r"(wa), "r"(prmt(wb, old, 0x7210)), "r"((uint32_t)on) : "memory");
}
__device__ __forceinline__ void p1_slow_tile(const Params& p, uint32_t sb, int i4) {
    const float f = __bfloat162float(p.freq[0]);
#pragma unroll 1
    for (int u = 0; u < 8; u++) {
        const int k4 = i4 + (u >> 2) * 32;
        if (k4 < p.n4) {
            const size_t t = (size_t)k4 * 4 + (u & 3);
            const float x = __bfloat162float(__float2bfloat16(f * __bfloat162float(p.angle[t])));
            slow_add(p.m, sb, p.idx_in[t], p.idx_out[t], __bfloat162float(__float2bfloat16(cosf(x))));
        }
    }
}
__device__ __forceinline__ void role_p1(const Params& p, uint32_t sb, int id, int w, int lane) {
    lane = keep32(lane);
    const uint32_t f2 = (uint32_t)__bfloat16_as_ushort(p.freq[0]) * 0x10001u;
    constexpr int TG = CFG_TG, NTK = P1W;
    static_assert(NTK <= 16, "tickets");
    const int tc = (w + id) % NTK, first = (N1 * P1W + tc) * (TG * 64);
    uint32_t* const tickets = opaque(ctl_word(p, sb, 29 + tc / 8, tc % 8 * 128 + lane, tc & 1));
    auto draw = [&]() {
        uint32_t t = 0;
        asm volatile("{.reg .pred q; setp.eq.u32 q, %2, 0; @q atom.relaxed.gpu.global.add.u32 %0, [%1], 1;}" : "+r"(t) : "l"(tickets), "r"(lane) : "memory");
        return t;
    };
    int i4 = (id * P1W + w) * (TG * 64);
    In8 r;
    ACC_DECL
    uint32_t tk = draw();
    p1_load(p, r, i4 + lane);
    while (i4 < p.n4) {
        const int cur = i4;
        i4 += 64;
        if (i4 % (TG * 64) == 0) {
            i4 = min(__shfl_sync(0xffffffffu, tk, 0), 0x7fffffffu / (NTK * TG * 64) - N1 * P1W / NTK - 2) * (NTK * TG * 64) + first;
            tk = draw();
        }
        uint32_t wa[8], wb[8], x2[4];
        x2[0] = mul_bf2(r.g[0].x, f2); x2[1] = mul_bf2(r.g[0].y, f2);
        x2[2] = mul_bf2(r.g[1].x, f2); x2[3] = mul_bf2(r.g[1].y, f2);
        const uint32_t mx = maxabs_bf2(maxabs_bf2(x2[0], x2[1]), maxabs_bf2(x2[2], x2[3]));
        const bool fast = __all_sync(0xffffffffu, cur + 64 <= p.n4 && ((mx & 0x7fffu) <= 0x4300u) && ((mx & 0x7fff0000u) <= 0x43000000u));
        {
            const uint32_t in[8] = {r.a[0].x, r.a[0].y, r.a[0].z, r.a[0].w, r.a[1].x, r.a[1].y, r.a[1].z, r.a[1].w};
            const uint32_t ou[8] = {r.o[0].x, r.o[0].y, r.o[0].z, r.o[0].w, r.o[1].x, r.o[1].y, r.o[1].z, r.o[1].w};
#pragma unroll
            for (int j = 0; j < 8; j += 2) {
                const uint32_t ch = mul_h2(pack_h2(__cosf(bflo(x2[j >> 1])), __cosf(bfhi(x2[j >> 1]))), 0x24002400u);
#pragma unroll
                for (int k = j; k < j + 2; k++) {
                    const uint32_t blk = __umulhi(in[k], p.magic2), il = imad(blk, p.nrows2, in[k]);
                    wa[k] = k & 1 ? bitsel(ch, il, 0xffff0000u) : imad(ch, 65536u, il);
                    wb[k] = imad(blk, 1u << 21, imad(ou[k] >> 5, 1u - (1u << 21), ou[k] << 16));
                }
            }
        }
        p1_load(p, r, i4 + lane);
        if (fast) {
            uint32_t old[8], any = 0;
#pragma unroll
            for (int j = 0; j < 8; j++) old[j] = atoms_add(dp2(wb[j], 0x400u, 0u) + (sb + A_CNT), 0x80001u);
#pragma unroll
            for (int j = 0; j < 8; j++) any |= old[j];
            if (!__any_sync(0xffffffffu, any & 0xffe0u)) {
#pragma unroll
                for (int j = 0; j < 8; j++) p1_put(sb, wa[j], wb[j], old[j], true);
            } else {
                uint32_t pend = 0;
#pragma unroll
                for (int j = 0; j < 8; j++) { p1_put(sb, wa[j], wb[j], old[j], !(old[j] & 0xffe0u)); if (old[j] & 0xffe0u) pend |= 1u << j; }
                ACC(0, 1)
                for (int guard = 0; __any_sync(0xffffffffu, pend); guard++) {
                    __nanosleep(CFG_BSLEEP);
                    ACC(1, 1)
#pragma unroll
                    for (int j = 0; j < 8; j++) {
                        if (__any_sync(0xffffffffu, pend >> j & 1)) {
                            const uint32_t c = lds32v(sb + A_CNT + (pend >> j & 1 ? wb[j] >> 16 : 0) * 4);
                            const bool go = (pend >> j & 1) && (((old[j] >> 19) - (c >> 19) + c) & 8191u) < 32u;
                            p1_put(sb, wa[j], wb[j], old[j], go);
                            if (go) pend &= ~(1u << j);
                        }
                    }
                    if (guard > GUARD) __trap();
                }
            }
        } else {
            p1_slow_tile(p, sb, cur + lane);
            __syncwarp();
        }
    }
    __syncwarp();
    mbar_arrive_if(sb + SM_DONE, lane == 0);
    ACC_SAVE
}

__device__ __forceinline__ void role_flush(const Params& p, uint32_t sb, int id, int f, int lane) {
    lane = keep32(lane);
    const int half = lane >> 4, o = lane >> 2, q = lane & 3;
    const uint32_t hm = keep32(half ? 0xffff0000u : 0xffffu), lth = keep32(((1u << lane) - 1) & hm);
    const uint32_t list = sb + A_LIST + f * LISTB, cnt = keep32(sb + A_CNT + (f * GPW * 32 + lane) * 4);
    const uint32_t cred = opaque32(sb + SM_CRED + (half * 32 + f * GPW) * 4);
    const uint32_t pa = opaque32(p.ring_lo + (id >> 1) * 8192 + (id & 1) * 2048 + q * 16);
    const uint32_t ph = opaque32(p.ring_lo + (32 + (id >> 2)) * 8192 + (id & 3) * 1024 + q * 8 - 2048);
    const uint32_t sa = q * 16 + (o & 1) * 64;
    uint32_t qo[GPW], hs[GPW], cr[4] = {0, 0, 0, 0};
#pragma unroll
    for (int g = 0; g < GPW; g++) {
        const int blk = f * GPW + g;
        qo[g] = 32u << 25;
        const uint32_t sa = sel_of(sb, 2 * blk + half, id >> 1, half), sh = sel_of(sb, 2 * blk + half, 32 + (id >> 2), half);
        hs[g] = sa << 31 | (2 * sh + 1 - sa) << 22 | 1u << 24 | (lane & 15) << 15 | (blk * 32 + lane) * 2;
    }
    uint4 x[KR] = {}, y[KR] = {};
    uint32_t c[GPW] = {};
    auto scan = [&]() {
#pragma unroll
        for (int g = 0; g < GPW; g++) c[g] = lds32v(cnt + g * 128);
    };
    auto credits = [&]() {
        if (GPW == 4) { const uint4 v = lds128(cred); cr[0] = v.x; cr[1] = v.y; cr[2] = v.z; cr[3] = v.w; }
        else { const uint2 v = lds64v(cred); cr[0] = v.x; cr[1] = v.y; }
    };
    ACC_DECL
    int guard = 0;
    bool idle = false, done = false;
    while (true) {
        uint32_t fr[GPW], rank[GPW], num = 0, left = 0;
        bool ok[GPW];
        if (idle && !done && __all_sync(0xffffffffu, mbar_test(sb + SM_DONE, 0))) {
            done = true;
            TR(17, f == 0 && lane == 0);
#pragma unroll
            for (int g = 0; g < GPW; g++) {
                const uint32_t u = lds32v(cnt + g * 128) & 31u, hd = hs[g] ^ (u & 16u ? imad(hs[g], 1u << 24, 1u) & 0x01000001u : 0u);
#pragma unroll 2
                for (uint32_t j = 0, k; k = (j + lane) & 15u, j < 16; j++)
                    sts64_if(sb + A_ST + ((hd & 0x7ffu) << 7) + k * 8, p.rows2, (lane * 16 + k) | (hd & 0x1000000u), (u & 15u) && k >= (u & 15u));
                reds_add(cnt + g * 128, ((0u - u) & 15u) * 0x80001u);
            }
            __syncwarp();
            scan();
        }
#pragma unroll
        for (int g = 0; g < GPW; g++) {
            const bool isfull = c[g] & 0xfff0u;
            rank[g] = __popc(__ballot_sync(0xffffffffu, isfull) & lth);
            ok[g] = isfull && (int)(rank[g] << 25) < (int)(cr[g] - qo[g] + (63u << 25));
            ACC(2, __popc(__ballot_sync(0xffffffffu, isfull && !ok[g])))
        }
#pragma unroll
        for (int g = 0; g < GPW; g++) {
            const uint32_t m = __ballot_sync(0xffffffffu, ok[g]), n = __popc(m & hm), all = __popc(m), e = num + rank[g] + (half ? all - n : 0u);
            sts32_if(KR == 2 ? list + (e & 48u) * 4 + (e & 7u) * 8 + (e >> 1 & 4u) : imad(e, 4u, list), bitsel(imad(rank[g], 1u << 25, qo[g]), hs[g], 0x7e000000u), ok[g]);
            if (ok[g]) hs[g] ^= imad(hs[g], 1u << 24, 1u) & 0x01000001u;
            fr[g] = ok[g] ? 0u - 16u : 0u;
            left |= c[g] + fr[g];
            qo[g] = imad(n, 1u << 25, qo[g]);
            num += all;
        }
        __syncwarp();
        ACC(0, 1) ACC(1, num)
        if (num) {
            uint32_t la = list + o * (KR == 2 ? 8 : 4);
            int todo = (int)num - o, rest = num;
            do {
                uint32_t d[KR];
                if (KR == 2) { const uint2 v = lds64v(la); d[0] = v.x; d[KR - 1] = v.y; }
                else {
#pragma unroll
                    for (int k = 0; k < KR; k++) d[k] = lds32v(la + 32 * k);
                }
                while (true) {
                    uint32_t bad = 0;
#pragma unroll
                    for (int k = 0; k < KR; k++) {
                        const uint32_t m = d[k] & 0x7ffu;
                        lds128_keep(x[k], imad(m, 128u, sa) + (sb + A_ST), todo > 8 * k);
                        lds128_keep(y[k], imad(m, 128u, sa ^ 64) + (sb + A_ST), todo > 8 * k);
                    }
#pragma unroll
                    for (int k = 0; k < KR; k++)
                        or3_if(bad, lop3<0x7e>(x[k].y, x[k].w, d[k]), lop3<0x7e>(y[k].y, y[k].w, d[k]), todo > 8 * k);
                    if (!__any_sync(0xffffffffu, (int)imad(bad, 128u, 0u) < 0)) break;
                    if (++guard > GUARD) __trap();
                }
#pragma unroll
                for (int k = 0; k < KR; k++) {
                    const uint32_t mi = d[k] & 0x7e0u, dm = d[k] & 0xbec00000u;
                    x[k].x = bitsel(d[k], x[k].x, 0x40078000u);
                    x[k].y = prmt(x[k].y, x[k].w, 0x5410);
                    x[k].w = prmt(y[k].y, y[k].w, 0x5410);
                    y[k].x = bitsel(d[k], y[k].x, 0x40000000u);
                    y[k].y = y[k].z;
                    stg_q128(ring_ptr(p, dp4(dm, 0x20000000u, imad(mi, WIN / 32, pa))), x[k].x, x[k].y, x[k].z, x[k].w, todo > 8 * k);
                    stg_q64(ring_ptr(p, dp4(dm, 0x10200000u, imad(mi, WIN / 32, ph))), y[k].x, y[k].y, todo > 8 * k);
                }
                la += 32 * KR;
                todo -= 8 * KR;
                rest -= 8 * KR;
            } while (rest > 0);
#pragma unroll
            for (int g = 0; g < GPW; g++) c[g] = atoms_add(cnt + g * 128, fr[g]) + fr[g];
            credits();
            idle = num <= CFG_TH;
            if (done && !__any_sync(0xffffffffu, left & 0xffffu)) break;
            if (idle) { __nanosleep(CFG_TS); scan(); credits(); }
        } else {
            if (done && !__any_sync(0xffffffffu, left & 0xffffu)) break;
            idle = true;
            __nanosleep(CFG_FSLEEP);
            scan();
            credits();
            if (++guard > GUARD) __trap();
        }
    }
#pragma unroll
    for (int g = 0; g < GPW; g++) st_rlx_if(fin1_of(p, sb, half * H2 + f * GPW + g) + id, qo[g] - (32u << 25) + 1u, (lane & 15) == 0 && f * GPW + g < NI);
    mbar_arrive_if(sb + SM_DONE2, lane == 0);
    TR(18, f == 0 && lane == 0);
    ACC_SAVE
}
__device__ __forceinline__ void role_credit1(const Params& p, uint32_t sb, int id, int lane) {
    const uint32_t* const cred = cred1_of(p, sb, id) + lane * 2;
    for (int guard = 0; !__all_sync(0xffffffffu, mbar_test(sb + SM_DONE2, 0)); guard++) {
        const uint2 v = ldg_q64(cred);
        sts64(sb + SM_CRED + lane * 8, v.x, v.y);
        __nanosleep(CFG_C1SLEEP);
        if (guard > GUARD) __trap();
    }
}

__device__ __forceinline__ float h2f(uint32_t h) {
    float f;
    asm("{.reg .b16 t; cvt.u16.u32 t, %1; cvt.f32.f16 %0, t;}" : "=f"(f) : "r"(h));
    return f;
}
__device__ __forceinline__ void p2_slow(const Params& p, uint32_t sb, const uint32_t* tmp, int row0, uint32_t dst) {
#pragma unroll 1
    for (int j = 0; j < 4; j++)
        if (tmp[8 + j] & 0x40u) slow_add(p.m, sb, row0 + (tmp[j] & 0x7fffu), (tmp[4 + j] & 0x7fffu) * 32 + dst, h2f(tmp[j] >> 16) * 64.0f);
}
__device__ __forceinline__ uint32_t mul_h2_hi(uint32_t a, uint32_t b) {
    uint32_t r;
    asm("{.reg .b16 l, h; .reg .b32 t; mov.b32 {l, h}, %2; mov.b32 t, {h, h}; mul.rn.f16x2 %0, %1, t;}" : "=r"(r) : "r"(a), "r"(b));
    return r;
}
template <bool CHECK>
__device__ __forceinline__ void role_p2(const Params& p, uint32_t sb, int id, int w, int lane) {
    lane = keep32(lane);
    const int part = id / H2, blk = id - part * H2, row0 = blk * p.rows2;
    const int o = lane >> 2, q = lane & 3;
    uint32_t* const cbase = (uint32_t*)(p.ring + (CWIN + lds32(sb + SM_MISC + 16)) * WIN);
    const uint32_t cred = opaque32((uint32_t)(uintptr_t)(cbase + part * 32 + blk));
    const uint32_t pa = opaque32(p.ring_lo + (2 * blk + part) * WIN + q * 16), ph = opaque32(pa - q * 8);
    const uint32_t po = opaque32(p.ring_lo + (q2_off(sb, blk, part * H3) & ~4096u) + q * 16 + (o & 1) * 64);
    const uint32_t sel = __ballot_sync(0xffffffffu, q2_off(sb, blk, part * H3 + (lane & 15)) & 4096u) << 12;
    const uint32_t* const fins = fin1_of(p, sb, id);
    uint32_t st[QPW] = {}, sq[QPW] = {};
    uint4 qa[NBT];
    uint2 qh[NBT];
    auto load = [&](int k) {
        qa[k] = ldg_q128(ring_ptr(p, pa + (bitsel(sq[k], st[k] >> 19, 0x7f800u) & 0x7ffc0u)));
        qh[k] = ldg_q64(ring_ptr(p, ph + (bitsel(sq[k] >> 9, st[k] >> 20, 0x7fc00u) & 0x7ffe0u)));
    };
#pragma unroll
    for (int k = 0; k < QPW; k++) {
        const int src = w * QPW + k;
        st[k] = o << 25 | (src < N1 ? 1u : 5u);
        sq[k] = src < N1 ? q1h_off(sb, src, blk, part) << 9 | q1a_off(sb, src, blk, part) | (uint32_t)(cred1_of(p, sb, src) - cbase) / 8 : 0x7e000u * 513u;
    }
#pragma unroll
    for (int k = 0; k < NBT; k++) load(k);
    ACC_DECL
    int guard = 0;
    uint32_t streak = 0;
    while (true) {
        uint32_t nn[NBT], xx[NBT][4], hh[NBT][2], dd[NBT], any = 0;
        bool last = false;
#pragma unroll
        for (int k = 0; k < NBT; k++) {
            const uint4 a = qa[k];
            const uint2 h = qh[k];
            uint32_t n = 8;
            const uint32_t miss = __ballot_sync(0xffffffffu, (int)imad((a.x ^ st[k]) & (h.x ^ st[k]), 2u, 0u) >= 0);
            if (miss) {
                n = (__ffs(miss) - 1) >> 2;
                if (!__any_sync(0xffffffffu, st[k] & 8u)) { if (streak < CFG_PSTREAK) n &= CFG_PMASK; }
                else if (!__any_sync(0xffffffffu, ((st[k] >> 6) + ((n - o) << 19) ^ st[k]) & 0x1f80000u)) { st[k] |= 4u; last = true; }
            }
            ACC(1, n == 0) ACC(2, n != 0) ACC(3, n)
            st[k] = imad(n, 1u << 25, st[k]);
            st_rlx_if((uint32_t*)ring_ptr(p, imad(sq[k] & 0x7f0u, 32u, cred)), st[k], lane == 0 && n);
            xx[k][0] = bitsel(a.x, 0x00040000u, 0xbff87fffu); xx[k][1] = a.z; xx[k][2] = h.x & 0xbfffffffu; xx[k][3] = h.y;
            hh[k][0] = a.y; hh[k][1] = a.w; dd[k] = a.x >> 13 & 0x3cu; nn[k] = n;
            any |= n;
        }
        if (!any) {
#pragma unroll
            for (int k = 0; k < QPW; k++) {
                const uint32_t fin = ld_rlx(fins + ((sq[k] >> 12 & 62u) | (sq[k] >> 11 & 1u)));
                if (fin & 1u) st[k] |= (fin >> 6 & 0x1f80000u) | ((fin ^ (st[k] - (o << 25))) >> 25 ? 8u : 12u);
            }
            last = true;
            if (++guard > GUARD) __trap();
            streak++;
        } else streak = 0;
        if (last) {
            uint32_t all = 4u;
#pragma unroll
            for (int k = 0; k < QPW; k++) all &= st[k];
            last = __all_sync(0xffffffffu, all);
        }
        {
            uint32_t t[QPW], u[QPW];
#pragma unroll
            for (int k = 0; k < QPW; k++) { t[k] = st[(k + NBT) % QPW]; u[k] = sq[(k + NBT) % QPW]; }
#pragma unroll
            for (int k = 0; k < QPW; k++) { st[k] = t[k]; sq[k] = u[k]; }
        }
#pragma unroll
        for (int k = 0; k < NBT; k++) load(k);
#pragma unroll
      for (int k = 0; k < NBT; k++) {
        if (nn[k]) {
            const uint32_t* const x = xx[k];
            const uint32_t h0 = hh[k][0], h1 = hh[k][1], d4 = dd[k];
            const bool v = o < nn[k];
            uint32_t ta[4], tb[4], w0[4], w1[4];
            const uint32_t ca = imad(d4, 4u, sb + SM_CNT2 + q * 4), old = atoms_add(ca, v ? 0x10001u : 0u);
#pragma unroll
            for (int j = 0; j < 4; j++) {
                ta[j] = lds32nv(dp2(x[j], 4u, 0u) + (sb + B_TA));
                tb[j] = lds16nv(dp2(x[j], 2u, 0u) + (sb + B_TB));
            }
            const uint32_t tag = old << 8 & 0x40000000u;
#pragma unroll
            for (int j = 0; j < 4; j++) {
                const uint32_t z = prmt(j & 2 ? h1 : h0, 0, j & 1 ? 0x4342 : 0x4140);
                const uint32_t t23 = prmt((ta[j] & 0x60076007u) * 2050u, tb[j], 0x5341) & 0xfffcffffu;
                w0[j] = (imad(z, 128u, j & 1 ? 0u : tag) & 0x78007800u) | mul_h2_hi(ta[j] & 0x9ff89ff8u, x[j]);
                w1[j] = (imad(z, 2048u, 0u) & 0x78007800u) | mul_h2_hi(t23, x[j]);
            }
            if (CHECK && v && ((tb[0] | tb[1] | tb[2] | tb[3]) & 0x40u)) {
                uint32_t tmp[12];
#pragma unroll
                for (int j = 0; j < 4; j++) {
                    tmp[j] = x[j]; tmp[4 + j] = (j & 2 ? h1 : h0) >> (j & 1 ? 16 : 0); tmp[8 + j] = tb[j];
                    if (tb[j] & 0x40u) { w0[j] &= 0x78007800u; w1[j] &= 0x78007800u; }
                }
                p2_slow(p, sb, tmp, row0, part * H3 + d4 / 4);
            }
            const uint32_t off = (bitsel(old >> 9, old >> 7, 0x0f80u) & 0x4f80u) + imad(d4, WIN / 4, (sel >> (d4 / 4) & 4096u) + po);
            bool wait = v && (old & (0x10000u - NQ2));
            if (!__any_sync(0xffffffffu, wait)) {
                stg_q128(ring_ptr(p, off), w0[0], w1[0], w0[1], w1[1], v);
                stg_q128(ring_ptr(p, off ^ 64u), w0[2], w1[2], w0[3], w1[3], v);
            } else {
                bool pend = v;
                ACC(0, 1)
                for (int g2 = 0;; g2++) {
                    stg_q128(ring_ptr(p, off), w0[0], w1[0], w0[1], w1[1], pend && !wait);
                    stg_q128(ring_ptr(p, off ^ 64u), w0[2], w1[2], w0[3], w1[3], pend && !wait);
                    pend = wait;
                    if (!__any_sync(0xffffffffu, pend)) break;
                    __nanosleep(CFG_BSLEEP);
                    const uint32_t c = lds32v(ca);
                    wait = pend && (((old >> 16) - (c >> 16) + c) & 0xffffu) >= NQ2;
                    if (g2 > GUARD) __trap();
                }
            }
        }
      }
        if (last) break;
    }
    TR(17, w == 0 && lane == 0);
    __syncwarp();
    uint32_t rank = 0;
    if (lane == 0) { __threadfence_block(); rank = atoms_add(sb + SM_FIN, 1u); __threadfence_block(); }
    if (__shfl_sync(0xffffffffu, rank, 0) == P2W - 1 && lane < 16)
        st_rlx(fin2_of(p, sb, part * H3 + lane) + blk, FIN | (((lds32v(sb + SM_CNT2 + lane * 16) >> 16) - NQ2) & 0xffffu));
    __syncwarp();
    mbar_arrive_if(sb + SM_DONE, lane == 0);
    ACC_SAVE
}
__device__ __forceinline__ void role_credit(const Params& p, uint32_t sb, int id, int lane) {
    const uint32_t* const cred = cred2_of(p, sb, id) + (lane >> 2);
    uint32_t last = 0, last2 = 0;
    for (int guard = 0;; guard++) {
        if (__all_sync(0xffffffffu, mbar_test(sb + SM_DONE, 0))) break;
        const uint32_t c = ld_rlx(cred), c2 = ld_rlx(cred + 8);
        reds_add(sb + SM_CNT2 + lane * 4, 0u - ((c - last) & 0xffffu));
        reds_add(sb + SM_CNT2 + 128 + lane * 4, 0u - ((c2 - last2) & 0xffffu));
        last = c;
        last2 = c2;
        __nanosleep(CFG_CSLEEP);
        if (guard > GUARD) __trap();
    }
}

__device__ __forceinline__ void p3_wrap(uint32_t sb, int id, const uint32_t* tmp) {
    const Scale sc = get_scale(sb);
#pragma unroll 1
    for (int j = 0; j < 8; j++) {
        const uint32_t old = tmp[4 + j], v = tmp[12 + j], nw = old + v, t = (old ^ nw) & (v ^ nw);
        if (t & 0x80008000u) {
            const float k = (t & 0x8000u) ? ((v & 0x8000u) ? -1.0f : 1.0f) : 0.0f;
            const float q = (t & 0x80000000u) ? ((int)v < 0 ? -65536.0f : 65536.0f) : 0.0f;
            const uint32_t e0 = (j & 1) ? sc.eb[2] : sc.eb[0], e1 = (j & 1) ? sc.eb[3] : sc.eb[1];
            const float lo = k * 65536.0f * __uint_as_float((e0 - 10) << 23), hi = (q - k) * __uint_as_float((e1 - 10) << 23);
            if (j & 1) sg_add(tmp[j >> 1] * 32 + id, 0.f, 0.f, lo, hi);
            else sg_add(tmp[j >> 1] * 32 + id, lo, hi, 0.f, 0.f);
        }
    }
}
__device__ __forceinline__ uint32_t p3_val(uint32_t w) {
    const uint32_t mk = prmt(w, 0, 0xBB99);
    return ((w & 0x07ff07ffu) ^ mk) - mk;
}
__device__ __forceinline__ void role_p3(const Params& p, uint32_t sb, int id, int w, int lane) {
    lane = keep32(lane);
    uint32_t* const cred = opaque(cred2_of(p, sb, id / H3 * H2 + w) + id % H3);
    const uint32_t pq = opaque32(p.ring_lo + q2_off(sb, w, id) + lane * 16);
    auto off = [&](uint32_t n) { return (n & 1u) << 11 | (n & 2u) << 13; };
    const uint32_t pp = opaque32(pq - lane * 16 + 112);
    const uint32_t* const finp = opaque(fin2_of(p, sb, id) + w);
    auto tag_of = [&](uint32_t n) { return ~n << 28; };
    uint32_t n = 0, fin = 0, pr = 0, pk = 0;
    uint4 v[4] = {};
    bool have = false, last = false;
    ACC_DECL
    int guard = 0;
    while (true) {
        const uint32_t ex = tag_of(n);
        const bool ok = have && !__any_sync(0xffffffffu, ((v[0].x ^ ex) | (v[1].x ^ ex) | (v[2].x ^ ex) | (v[3].x ^ ex)) & 0x40000000u);
        if (ok) n++;
        const bool ready = (ok || !have) && __all_sync(0xffffffffu, !((pr ^ tag_of(n)) & 0x40000000u));
        st_rlx_if(cred, n * 16, lane == 0 && ok);
        if (!ok && !ready && __all_sync(0xffffffffu, fin & FIN)) {
            const uint32_t left = __shfl_sync(0xffffffffu, (fin - n * 16) & 0xffffu, 0);
            if (left - 1u > 0x8000u) break;
            if (left < 16u) {
#pragma unroll
                for (int u = 0; u < 4; u++) {
                    v[u] = make_uint4((ex & 0x40000000u) | (lane & 16) << 7, (lane & 15) << 11, (lane & 16) << 7, (lane & 15) << 11);
                    ldq128_keep(v[u], ring_ptr(p, pq + off(n)) + u * 512, u * 4 + (lane >> 3) < left);
                }
                have = last = !__any_sync(0xffffffffu, ((v[0].x ^ ex) | (v[1].x ^ ex) | (v[2].x ^ ex) | (v[3].x ^ ex)) & 0x40000000u);
                pr = ~tag_of(n + have);
                if (++guard > GUARD) __trap();
                continue;
            }
        }
        uint32_t row[8], val[16];
#pragma unroll
        for (int u = 0; u < 4; u++) {
            const uint4 x = v[u];
            row[2 * u] = prmt(bitsel(x.x << 1, x.y >> 3, 0x7000f000u), 0, 0x4431);
            row[2 * u + 1] = prmt(bitsel(x.z << 1, x.w >> 3, 0x7000f000u), 0, 0x4431);
            val[4 * u] = p3_val(x.x); val[4 * u + 1] = p3_val(x.y);
            val[4 * u + 2] = p3_val(x.z); val[4 * u + 3] = p3_val(x.w);
        }
#pragma unroll
        for (int u = 0; u < 4; u++) ldq128_keep(v[u], ring_ptr(p, pq + off(n)) + u * 512, ready);
        pk = ready ? CFG_PK1 * 128 : ok ? CFG_PK2 * 128 : have ? 15 * 128 : max(pk, CFG_PK3 * 128u);
        pr = ld_rlx((const uint32_t*)ring_ptr(p, pp + off(n + ready) + pk));
        ACC(2, have && !ok)
        have = ready;
        if (!ok) {
            ACC(1, 1)
            fin = ld_rlx(finp);
            if (++guard > GUARD) __trap();
        } else {
#pragma unroll
            for (int u = 0; u < 4; u += 2) {
                uint32_t old[8], chk = 0;
#pragma unroll
                for (int j = 0; j < 4; j++) {
                    old[2 * j] = atoms_add(sb + C_S + row[2 * u + j] * 4, val[4 * u + 2 * j]);
                    old[2 * j + 1] = atoms_add(sb + C_S + ROWS3_MAX * 4 + row[2 * u + j] * 4, val[4 * u + 2 * j + 1]);
                }
#pragma unroll
                for (int j = 0; j < 8; j++) {
                    const uint32_t nw = old[j] + val[4 * u + j];
                    chk |= (old[j] ^ nw) & (val[4 * u + j] ^ nw);
                }
                if (chk & 0x80008000u) {
                    uint32_t tmp[20];
#pragma unroll
                    for (int j = 0; j < 8; j++) { tmp[j >> 1] = row[2 * u + (j >> 1)]; tmp[4 + j] = old[j]; tmp[12 + j] = val[4 * u + j]; }
                    p3_wrap(sb, id, tmp);
                }
            }
            __syncwarp();
            if (last) break;
        }
    }
    ACC_SAVE
}

__device__ __forceinline__ void row_gates(const float* sw, const uint32_t* c2, uint32_t dbits, float4& gs, float4& gr) {
    const uint32_t d2 = dbits * 0x10001u;
    gs = gr = make_float4(0.f, 0.f, 0.f, 0.f);
#pragma unroll
    for (int r2 = 0; r2 < 4; r2++) {
        uint32_t df = sub_bf2(d2, c2[r2]);
        uint32_t ar = mul_bf2(mul_bf2(df, df), 0xC120C120u);
        uint32_t rb = pack_bf2(__expf(bflo(ar)), __expf(bfhi(ar)));
        const float r0 = bflo(rb), r1 = bfhi(rb);
        const float4 s0 = *(const float4*)(sw + r2 * 8), s1 = *(const float4*)(sw + r2 * 8 + 4);
        const float4 q0 = *(const float4*)(sw + 32 + r2 * 8), q1 = *(const float4*)(sw + 32 + r2 * 8 + 4);
        gs.x += r0 * s0.x + r1 * s1.x; gs.y += r0 * s0.y + r1 * s1.y;
        gs.z += r0 * s0.z + r1 * s1.z; gs.w += r0 * s0.w + r1 * s1.w;
        gr.x += r0 * q0.x + r1 * q1.x; gr.y += r0 * q0.y + r1 * q1.y;
        gr.z += r0 * q0.z + r1 * q1.z; gr.w += r0 * q0.w + r1 * q1.w;
    }
}
__device__ __forceinline__ uint2 finish_row(const float* wu, const float4& gs, const float4& gr, const float S[4], uint2 mrow) {
    const float a[4] = {S[0] * gs.x, S[1] * gs.y, S[2] * gs.z, S[3] * gs.w};
    float u[4] = {0, 0, 0, 0};
#pragma unroll
    for (int k = 0; k < 4; k++) {
        u[0] += a[k] * wu[4 * k]; u[1] += a[k] * wu[4 * k + 1]; u[2] += a[k] * wu[4 * k + 2]; u[3] += a[k] * wu[4 * k + 3];
    }
    return make_uint2(pack_bf2(bflo(mrow.x) + u[0] * gr.x, bfhi(mrow.x) + u[1] * gr.y),
                      pack_bf2(bflo(mrow.y) + u[2] * gr.z, bfhi(mrow.y) + u[3] * gr.w));
}
__device__ __forceinline__ void load_tail_weights(const Params& p, float* sw, int tid) {
    if (tid < 32) sw[tid] = __bfloat162float(p.w_sbf[tid]);
    else if (tid < 64) sw[tid] = __bfloat162float(p.w_rbf[tid - 32]);
    else if (tid < 80) sw[tid] = __bfloat162float(p.w_up[tid - 64]);
    else if (tid < 96) sw[tid] = __bfloat162float(p.w_down[tid - 80]);
}
__device__ __forceinline__ float exp_ftz(float x) {
    float r;
    asm("ex2.approx.ftz.f32 %0, %1;" : "=f"(r) : "f"(x * 1.4426950408889634f));
    return r;
}
__device__ __forceinline__ void tail_rows(const Params& p, int tidx, int w, int lane) {
    constexpr uint32_t sb = SB;
    if (w == NW - 1 && lane < 2) {
        fence_gpu();
        red_rlx(rdy_of(p, sb, 320, lane), 1u);
    }
    if (w >= NPC * WPP) return;
    const int pc = w / WPP, r0 = pc * RPC + (tidx * WPP + w - pc * WPP) * 8, e0 = r0 * 32;
    const uint32_t G = sb + T_G + w * TWB, M = G + 4096, D = M + 2048;
    cp16z(D + lane * 16, p.dist + e0 + lane * 8, min(max(p.E - e0 - lane * 8, 0), 8) * 2);
#pragma unroll
    for (int k = 0; k < 4; k++) cp16(M + (k * 32 + lane) * 16, p.m + e0 + (k * 32 + lane) * 2, e0 + (k * 32 + lane) * 2 < p.E);
    cp_commit();
    const Scale sc = get_scale(sb);
    const float lsb[4] = {__uint_as_float((sc.eb[0] - 10) << 23), __uint_as_float((sc.eb[1] - 10) << 23),
                          __uint_as_float((sc.eb[2] - 10) << 23), __uint_as_float((sc.eb[3] - 10) << 23)};
    {
        const int g = lane >> 2, t = lane & 3;
        const uint32_t c2 = ((const uint32_t*)p.centers)[t];
        const unsigned short* wg = (const unsigned short*)(g < 4 ? p.w_sbf : p.w_rbf) + t * 8 + (g & 3);
        const uint32_t b = wg[0] | (uint32_t)wg[4] << 16;
        cp_wait<0>();
        __syncwarp();
        TR(19, w == 0 && lane == 0 && b + c2 != 0x12345);
#pragma unroll 2
        for (int k = 0; k < 16; k++) {
            const uint32_t dv = lds32(D + (k * 8 + g) * 4);
            uint32_t a[2];
#pragma unroll
            for (int h = 0; h < 2; h++) {
                const uint32_t df = sub_bf2(prmt(dv, 0, h ? 0x3232 : 0x1010), c2);
                const uint32_t ar = mul_bf2(mul_bf2(df, df), 0xC120C120u);
                a[h] = pack_bf2(exp_ftz(bflo(ar)), exp_ftz(bfhi(ar)));
            }
            float d[4];
            asm("mma.sync.aligned.m16n8k8.row.col.f32.bf16.bf16.f32 {%0,%1,%2,%3}, {%4,%5}, {%6}, {%7,%7,%7,%7};"
                : "=f"(d[0]), "=f"(d[1]), "=f"(d[2]), "=f"(d[3]) : "r"(a[0]), "r"(a[1]), "r"(b), "f"(0.f));
            const uint32_t at = G + (k * 16 + g * 2) * 16 + t * 4;
            sts32(at, pack_bf2(d[0], d[1]));
            sts32(at + 16, pack_bf2(d[2], d[3]));
        }
    }
    __syncwarp();
    TR(2, w == 0 && lane == 0);
    float wu[16];
#pragma unroll
    for (int k = 0; k < 4; k++) *(uint4*)(wu + 4 * k) = lds128(sb + SM_W + 256 + 16 * k);
    uint32_t dirty = 0;
#pragma unroll 1
    for (int pass = CFG_DRY ? 0 : 1; pass < 2; pass++) {
        if (pass) {
            if (w == pc * WPP && lane < 2) spin_ge(rdy_of(p, sb, lane ? 320 : 160 + 32 * pc, lds32(sb + SM_MISC + 20)), lane ? NTAIL : N3);
            __syncwarp();
            bar_sync(1 + pc, WPP * 32);
            TR(3, w == 0 && lane == 0);
            TR(10, w == NPC * WPP - 1 && lane == 0);
            if (r0 >= (int)p.rows3) return;
        }
        uint4 sv[4] = {};
#pragma unroll
        for (int u = 0; u < 4; u++) ldq128_keep(sv[u], &g_S[0][u * 16 + (lane >> 1)][r0 + (lane & 1) * 4], pass);
        if (pass && lane < 8 && (r0 + lane) * 32 < p.E && (dirty = ld_rlx(g_dirty + r0 + lane))) st_rlx(g_dirty + r0 + lane, 0u);
        dirty = __ballot_sync(0xffffffffu, dirty != 0);
        uint32_t xs[8] = {sv[0].x, sv[0].y, sv[0].z, sv[0].w, sv[1].x, sv[1].y, sv[1].z, sv[1].w};
        uint32_t ys[8] = {sv[2].x, sv[2].y, sv[2].z, sv[2].w, sv[3].x, sv[3].y, sv[3].z, sv[3].w};
        asm volatile("" : "+r"(lane));
        auto finish = [&](int k, uint32_t x, uint32_t y, bool extra) {
            const int i = (lane & 1) * 128 + (lane >> 1) + (k & 3) * 32 + (k >> 2) * 16, e = e0 + i;
            float S[4];
            const uint32_t tx = x + 0x80008000u, ty = y + 0x80008000u;
            S[0] = (__uint_as_float(prmt(tx, 0x4b000000u, 0x7610)) - 8421376.0f) * lsb[0];
            S[1] = (__uint_as_float(prmt(tx, 0x4b000000u, 0x7632)) - 8421376.0f) * lsb[1];
            S[2] = (__uint_as_float(prmt(ty, 0x4b000000u, 0x7610)) - 8421376.0f) * lsb[2];
            S[3] = (__uint_as_float(prmt(ty, 0x4b000000u, 0x7632)) - 8421376.0f) * lsb[3];
            if (extra && e < p.E) {
                const float4 g = __ldcg(g_Sg + e);
                S[0] += g.x; S[1] += g.y; S[2] += g.z; S[3] += g.w;
                __stcg(g_Sg + e, make_float4(0.f, 0.f, 0.f, 0.f));
            }
            const uint4 g = lds128(G + i * 16);
            const uint2 o = finish_row(wu, make_float4(bflo(g.x), bfhi(g.x), bflo(g.y), bfhi(g.y)), make_float4(bflo(g.z), bfhi(g.z), bflo(g.w), bfhi(g.w)), S,
                                       lds64v(M + i * 8));
            asm volatile("{.reg .pred q; setp.ne.u32 q, %3, 0; @q st.global.v2.u32 [%0], {%1,%2};}"
                         ::"l"(p.out + e), "r"(o.x), "r"(o.y), "r"((uint32_t)(pass && e < p.E)));
        };
        if (!dirty) {
#pragma unroll
            for (int k = 0; k < 8; k++) finish(k, xs[k], ys[k], false);
        } else {
#pragma unroll 1
            for (int k = 0; k < 8; k++) {
                finish(k, xs[0], ys[0], dirty >> ((lane & 1) * 4 + (k & 3)) & 1);
#pragma unroll
                for (int j = 0; j < 7; j++) { xs[j] = xs[j + 1]; ys[j] = ys[j + 1]; }
            }
        }
    }
    TR(9, w == 0 && lane == 0);
    TR(11, w == NPC * WPP - 1 && lane == 0);
}

#define CFG_MAP1 1
__global__ void __launch_bounds__(NT, 1) k_main(const __grid_constant__ Params p) {
    extern __shared__ __align__(1024) unsigned char smem[];
    constexpr uint32_t sb = SB;
    if ((uint32_t)__cvta_generic_to_shared(smem) != SB) __trap();
    const int tid = threadIdx.x, w = __shfl_sync(0xffffffffu, tid >> 5, 0), lane = tid & 31;
    if (w < NPROBE) probe(p, sb, w, lane);
    else {
        if (tid == NT - 1) sts32(sb + SM_MISC + 16, ld_rlx(&g_epoch) & 1);
        if (tid >= NT - 32 && lane < 12) sts32(sb + SM_FIN + lane * 4, 0u);
        load_tail_weights(p, (float*)(smem + SM_W), tid - NPROBE * 32);
        const int k = blockIdx.x % (NCTA / 2) * 14 + lane;
        if (w == NW - 2 && lane < 14 && k < NT - 32) asm volatile("prefetch.global.L2 [%0];" ::"l"((const uint4*)p.m + k * (p.E / 2 / (NT - 32))));
    }
    cta_sync();
    if (w) {
        const uint4 in = __ldg((const uint4*)p.m + (tid - 32) * (p.E / 2 / (NT - 32)));
        const Mat4 wd = load_mat4(p.w_down, lane);
        for (int i = SM_DATA / 16 + tid - 32; i < ZEND / 16; i += NT - 32) ((uint4*)smem)[i] = make_uint4(0, 0, 0, 0);
        if (tid - 32 < 256) ((uint4*)(smem + SM_ZERO))[tid - 32] = make_uint4(0, 0, 0, 0);
        if (tid < 96) sts32(sb + SM_CNT2 + (tid - 32) * 4, NQ2 << 16);
        __syncwarp();
        if (CFG_PFD && tid == NT - 1) {
            __nanosleep(CFG_PFD);
            const uint32_t n = (p.E / 2 + NCTA - 1) / NCTA, o = blockIdx.x * n;
            if (o < (uint32_t)p.E / 2) asm volatile("cp.async.bulk.prefetch.L2.global [%0], %1;" ::"l"((const uint4*)p.m + o), "r"(min(n, p.E / 2 - o) * 16) : "memory");
        }
        __syncwarp();
        md_stats(in, wd, lane);
    } else assign_role(p, sb, lane);
    if (tid == 0) {
        mbar_init(sb + SM_DONE, lds32(sb + SM_MISC) >> 8 ? P2W : P1W);
        mbar_init(sb + SM_DONE2, NF);
    }
    cta_sync();
    const uint32_t rid = __shfl_sync(0xffffffffu, lds32(sb + SM_MISC), 0);
    const int role = rid >> 8, id = rid & 255;
    TR(5, tid == 0);
    if (role == 0) {
        const int ww = CFG_MAP1 == 0 ? ((w & 3) == 3 ? NW : (w >> 2) * 3 + (w & 3)) : CFG_MAP1 == 1 ? (w & 2 ? NW : (w >> 2) * 2 + (w & 1)) : w;
        const int sw = CFG_MAP1 == 0 ? ((w & 3) == 3 ? w >> 2 : NW) : CFG_MAP1 == 1 ? (w & 2 ? (w >> 2) * 2 + (w & 1) : NW) : w - P1W;
        static_assert(CFG_MAP1 == 0 ? (P1W <= NW / 4 * 3 && NF + 2 <= NW / 4) : CFG_MAP1 == 1 ? (P1W <= NW / 2 && NF + 2 <= NW / 2) : true, "warp map");
        for (int i = tid; i < NF * GPW * 32; i += NT) sts32(sb + A_CNT + i * 4, 1u << 24);
        if (tid < 64) sts32(sb + SM_CRED + tid * 4, 0u);
        cta_sync();
        TR(1, tid == 0);
        if (ww < P1W) role_p1(p, sb, id, ww, lane);
        else if (sw < NF) role_flush(p, sb, id, sw, lane);
        else if (sw == NF) role_credit1(p, sb, id, lane);
        else if (w == NW - 1) {
            uint4* owin = (uint4*)(p.ring + (CWIN + (lds32(sb + SM_MISC + 16) ^ 1)) * WIN);
            for (int i = id * 32 + lane; i < CPAIRS * 512; i += N1 * 32) __stcg(owin + i, make_uint4(0, 0, 0, 0));
            __syncwarp();
        }
    } else if (role == 1) {
        const int row0 = id % H2 * p.rows2;
        const int nrows = min((int)p.rows2, p.E - row0);
        constexpr int NTB = NT - 32, TBD = CFG_TBD;
        bool flagged = false;
        if (w < NW - 1) {
            const uint4* const src = (const uint4*)(p.m + row0);
            uint4 r2[TBD], nx[TBD];
            auto fetch = [&](int i) {
#pragma unroll
                for (int k = 0; k < TBD; k++)
                    asm volatile("ld.global.nc.v4.u32 {%0,%1,%2,%3}, [%4];" : "=r"(nx[k].x), "=r"(nx[k].y), "=r"(nx[k].z), "=r"(nx[k].w) : "l"(src + min(i + k * NTB, nrows / 2 - 1)));
            };
            fetch(tid);
            const Scale sc = get_scale(sb);
            const Mat4 wd = load_mat4(p.w_down, lane);
            const uint32_t slow = sc.allslow ? 0x60006000u : 0u;
            Mat4 ws;
#pragma unroll
            for (int k = 0; k < 4; k++) ws.b[k] = mul_bf2(wd.b[k], ((246u - (lane & 4 ? sc.eb[(k & 2) + 1] : sc.eb[k & 2])) << 7) * 0x10001u);
#pragma unroll 1
            for (int i0 = tid; 2 * (i0 - lane) < nrows; i0 += TBD * NTB) {
#pragma unroll
                for (int k = 0; k < TBD; k++) r2[k] = make_uint4(nx[k].x, nx[k].z, nx[k].y, nx[k].w);
                fetch(i0 + TBD * NTB);
                uint32_t big[2 * TBD], any = slow;
#pragma unroll
                for (int k = 0; k < TBD; k++) {
                    const int i = i0 + k * NTB;
                    float y[8];
                    mul4(make_uint4(r2[k].x, r2[k].z, r2[k].y, r2[k].w), ws, y);
                    uint32_t a[4], h[4], ta[2];
#pragma unroll
                    for (int j = 0; j < 4; j++) { a[j] = pack_h2(y[2 * j], y[2 * j + 1]); h[j] = a[j] + 0x00040004u; }
#pragma unroll
                    for (int j = 0; j < 2; j++) {
                        ta[j] = bitsel(h[2 * j], bitsel(h[2 * j + 1] >> 3, h[2 * j + 1] << 7, 0x00070007u), 0x9ff89ff8u);
                        big[2 * k + j] = a[2 * j] | a[2 * j + 1] | h[2 * j] | h[2 * j + 1];
                    }
                    any |= big[2 * k] | big[2 * k + 1];
                    sts64_if(sb + B_TA + i * 8, ta[0], ta[1], 2 * i < nrows);
                    sts32_if(sb + B_TB + i * 4, prmt(h[1], h[3], 0x7531), 2 * i < nrows);
                }
                if (__any_sync(0xffffffffu, any & 0x60006000u)) {
#pragma unroll
                    for (int k = 0; k < 2 * TBD; k++) {
                        const int r = 2 * (i0 + (k >> 1) * NTB) + (k & 1);
                        if (((big[k] | slow) & 0x60006000u) && r < nrows) { sts32(sb + B_TA + r * 4, 0u); sts16(sb + B_TB + r * 2, 0x40u); }
                    }
                    flagged = true;
                }
            }
            if (tid == 0) {
                sts32(sb + B_TA + p.rows2 * 4, 0u);
                sts16(sb + B_TB + p.rows2 * 2, 0u);
            }
            TR(8, tid == 0);
        } else if (lane == 0) spin_ge(rdy_of(p, sb, id, id / H2), H3);
        __syncwarp();
        flagged = __any_sync(0xffffffffu, __syncthreads_or(flagged));
        TR(1, tid == 0);
        if (w < P2W) {
            if (flagged) role_p2<true>(p, sb, id, w, lane);
            else role_p2<false>(p, sb, id, w, lane);
        } else if (w == P2W) role_credit(p, sb, id, lane);
    } else {
        if (w == 0) clear_queues<false>(p, sb, id, lane);
        if (tid >= 32 && tid < 33 + NPC) mbar_init(sb + SM_DBAR + (tid - 32) * 8, 1);
        cta_sync();
        TR(1, tid == 0);
        if (w < P3W) role_p3(p, sb, id, w, lane);
        const int pc = w - P3W, n = min(((int)p.rows3 + 7) / 8 * 8 - pc * RPC, RPC);
        uint32_t *f0 = nullptr, *f1 = nullptr;
        if (pc >= 0) { f0 = opaque(rdy_of(p, sb, 160 + 32 * pc, 0)); f1 = opaque(rdy_of(p, sb, 160 + 32 * pc, 1)); }
        cta_sync();
        TR(2, tid == 0);
        if (pc >= 0 && pc < NPC && lane == 0) {
            fence_async_smem();
            if (pc >= CFG_DOUT) mbar_wait(sb + SM_DBAR + (pc + 1 - CFG_DOUT) * 8, 0);
            if (n > 0) {
                bulk_store(g_S[0][id] + pc * RPC, sb + C_S + pc * RPC * 4, n * 4);
                bulk_store(g_S[1][id] + pc * RPC, sb + C_S + (ROWS3_MAX + pc * RPC) * 4, n * 4);
            }
            asm volatile("cp.async.bulk.commit_group;" ::: "memory");
            asm volatile("cp.async.bulk.wait_group.read 0;" ::: "memory");
            mbar_arrive(sb + SM_DBAR + pc * 8 + 8);
            asm volatile("cp.async.bulk.wait_group 0;" ::: "memory");
            fence_gpu();
            red_rlx(f0, 1u);
            red_rlx(f1, 1u);
            if (id == 0 && pc == 0) red_rlx(&g_epoch, 1u);
            TR(12 + pc, true);
        }
        return;
    }
    cta_sync();
    TR(18, tid == 0 && role == 1);
    if (role == 0 && w == NW - 2) clear_queues<true>(p, sb, id, lane);
    tail_rows(p, role * N1 + id, w, lane);
}

__global__ void k_direct(const Params p, long long T) {
    float wd[16];
#pragma unroll
    for (int i = 0; i < 16; i++) wd[i] = __bfloat162float(p.w_down[i]);
    const float f = __bfloat162float(p.freq[0]);
    for (long long t = blockIdx.x * (long long)blockDim.x + threadIdx.x; t < T; t += (long long)gridDim.x * blockDim.x) {
        float x = __bfloat162float(__float2bfloat16(f * __bfloat162float(p.angle[t])));
        float c = __bfloat162float(__float2bfloat16(cosf(x)));
        uint2 md = down_row(__ldg(p.m + p.idx_in[t]), wd);
        red_v4(g_Sg + p.idx_out[t], c * bflo(md.x), c * bfhi(md.x), c * bflo(md.y), c * bfhi(md.y));
    }
}
__global__ void k_direct_tail(const Params p) {
    __shared__ __align__(16) float sw[96];
    load_tail_weights(p, sw, threadIdx.x);
    __syncthreads();
    uint32_t c2[4];
#pragma unroll
    for (int i = 0; i < 4; i++) c2[i] = ((const uint32_t*)p.centers)[i];
    for (int e = blockIdx.x * blockDim.x + threadIdx.x; e < p.E; e += gridDim.x * blockDim.x) {
        float4 g = __ldcg(g_Sg + e);
        __stcg(g_Sg + e, make_float4(0.f, 0.f, 0.f, 0.f));
        const float Sv[4] = {g.x, g.y, g.z, g.w};
        float4 gs, gr;
        row_gates(sw, c2, __bfloat16_as_ushort(p.dist[e]), gs, gr);
        p.out[e] = finish_row(sw + 64, gs, gr, Sv, __ldg(p.m + e));
    }
}

static bool pick_rows(int E, int n, int rows_max, int mult, uint32_t* rows, uint32_t* magic) {
    for (uint32_t r = (E + n - 1) / n; r <= (uint32_t)rows_max; r++) {
        if (r < 2 || r % mult) continue;
        uint64_t mg = ((1ull << 32) + r - 1) / r;
        uint64_t err = mg * r - (1ull << 32);
        if (err * (uint64_t)n < mg) { *rows = r; *magic = (uint32_t)mg; return true; }
    }
    return false;
}

}

extern "C" void kernel_launch(void* const* d_in, const int* in_sizes, int n_in, void* d_out, int out_size) {
    using namespace gs;
    (void)n_in; (void)out_size;
    Params p;
    p.m = (const uint2*)d_in[0];
    p.idx_in = (const int*)d_in[1];
    p.idx_out = (const int*)d_in[2];
    p.dist = (const __nv_bfloat16*)d_in[3];
    p.angle = (const __nv_bfloat16*)d_in[4];
    p.centers = (const __nv_bfloat16*)d_in[5];
    p.freq = (const __nv_bfloat16*)d_in[6];
    p.w_rbf = (const __nv_bfloat16*)d_in[7];
    p.w_sbf = (const __nv_bfloat16*)d_in[8];
    p.w_down = (const __nv_bfloat16*)d_in[9];
    p.w_up = (const __nv_bfloat16*)d_in[10];
    p.out = (uint2*)d_out;
    p.E = in_sizes[3];
    const long long T = in_sizes[1];
    p.n4 = (int)(T / 4);
    p.rows2 = p.magic2 = 0;
    p.ring = nullptr;

    static int sms = 0, rsv = 0;
    if (!sms) {
        int dev = 0;
        cudaGetDevice(&dev);
        cudaDeviceGetAttribute(&rsv, cudaDevAttrReservedSharedMemoryPerBlock, dev);
        cudaDeviceGetAttribute(&sms, cudaDevAttrMultiProcessorCount, dev);
        cudaFuncSetAttribute(k_main, cudaFuncAttributeMaxDynamicSharedMemorySize, SMEM_BYTES);
    }
    cudaStream_t st = cudaStreamPerThread;
    bool fast = (T % 4 == 0) && T > 0 && sms >= NCTA && rsv == (int)SB && p.E >= 65536 && p.E <= E_MAX &&
                p.E % 4 == 0 && (((uintptr_t)p.m | (uintptr_t)p.idx_in | (uintptr_t)p.idx_out | (uintptr_t)p.angle) & 15) == 0 &&
                pick_rows(p.E, NI, ROWS2_MAX, 2, &p.rows2, &p.magic2);
    p.nrows2 = 0u - p.rows2;
    p.rows3 = (p.E + 31) / 32;
    fast = fast && (p.rows2 * (NI - 1) + 2 <= (uint32_t)p.E);
    static const void* tkey[3] = {nullptr, nullptr, nullptr};
    static cudaTextureObject_t tex[3] = {0, 0, 0};
    static long long tlen = -1;
    const void* tptr[3] = {p.idx_in, p.idx_out, p.angle};
    for (int k = 0; fast && k < 3; k++) {
        if (tkey[k] == tptr[k] && tlen == T) continue;
        if (tkey[k]) cudaDestroyTextureObject(tex[k]);
        tkey[k] = nullptr;
        cudaResourceDesc rd = {};
        rd.resType = cudaResourceTypeLinear;
        rd.res.linear.devPtr = (void*)tptr[k];
        rd.res.linear.desc = cudaCreateChannelDesc(32, 32, k < 2 ? 32 : 0, k < 2 ? 32 : 0, cudaChannelFormatKindUnsigned);
        rd.res.linear.sizeInBytes = (size_t)T * (k < 2 ? 4 : 2);
        cudaTextureDesc td = {};
        td.readMode = cudaReadModeElementType;
        if (cudaCreateTextureObject(&tex[k], &rd, &td, nullptr) == cudaSuccess) tkey[k] = tptr[k];
        else { (void)cudaGetLastError(); fast = false; }
    }
    if (fast) tlen = T;
    p.t_in = tex[0]; p.t_out = tex[1]; p.t_ang = tex[2];
    if (fast) {
        void* ring = nullptr;
        cudaGetSymbolAddress(&ring, g_ring);
        uintptr_t a = ((uintptr_t)ring + WIN - 1) & ~(uintptr_t)(WIN - 1);
        if (a >> 32 != (a + RING_BYTES - 1) >> 32) a += RING_BYTES;
        p.ring = (unsigned char*)a;
        p.ring_lo = (uint32_t)a;
        p.ring_hi = (uint32_t)(a >> 32);
        k_main<<<NCTA, NT, SMEM_BYTES, st>>>(p);
    } else {
        k_direct<<<sms * 8, 256, 0, st>>>(p, T);
        k_direct_tail<<<sms * 4, 256, 0, st>>>(p);
    }
}
```

```cpp
#include <cuda_runtime.h>
#include <cuda_bf16.h>
#include <stdint.h>

#define CFG_N1 56
#define CFG_NI 22
#define CFG_NW 28
#define CFG_P1W 14
#define CFG_GPW 2
#define CFG_KR 1
#define CFG_QPW 3
#define CFG_TG 2
#define CFG_PMASK 8
#define CFG_PSTREAK 1
#define CFG_NBT 1
#define CFG_KM 5
#define CFG_KN 9
#define CFG_TBD 3
#define CFG_P0 500
#define CFG_PFD 200
#define CFG_C1SLEEP 200
#define CFG_PK1 6
#define CFG_PK2 8
#define CFG_PK3 11
#define CFG_DOUT 2
#define CFG_TH 14
#define CFG_TS 200
#define CFG_POLL 64
#define CFG_HINT 20000
#define CFG_BSLEEP 100
#define CFG_CSLEEP 400
#define CFG_FSLEEP 100
#define CFG_PSLEEP 100
#define CFG_PROBES 4

namespace gs {

constexpr int E_MAX = 640000;
constexpr int N1 = CFG_N1, NI = CFG_NI, N2 = 2 * NI, N3 = 32, NCTA = N1 + N2 + N3;
constexpr int H2 = NI, H3 = N3 / 2;
constexpr int NB = NI * N3;
constexpr int NW = CFG_NW, NT = NW * 32;
constexpr int GPW = CFG_GPW, NF = (NI + GPW - 1) / GPW;
constexpr int QPW = CFG_QPW, NBT = CFG_NBT;
constexpr int P1W = CFG_P1W, P2W = (N1 + QPW - 1) / QPW, P3W = NI;
constexpr int NQ2 = 64;
constexpr int ROWS2_MAX = ((E_MAX + NI - 1) / NI + 31) / 8 * 8;
constexpr int ROWS3_MAX = (E_MAX / 32 + 31) / 32 * 32;
constexpr int NTAIL = N1 + N2;
constexpr int NPC = 5, WPP = 5, RPC = NTAIL * WPP * 8;
constexpr int GUARD = 1 << 26;
static_assert(NCTA % 4 == 0 && NCTA <= 192, "roles come in CTA pairs, per partition");
static_assert((GPW == 2 || GPW == 4) && QPW >= NBT && QPW <= 4 && NI <= 32 && N1 <= 62, "queue ownership");
static_assert(P1W + NF + 2 <= NW && P2W + 2 <= NW && P3W + 5 <= NW && P1W * 256 + 64 < 8192, "warp roles");
static_assert(ROWS2_MAX + 8 <= 32768 && ROWS3_MAX <= 32768, "index bits");

constexpr uint32_t SB = 1024;
constexpr int SM_DONE = 0, SM_DONE2 = 8;
constexpr int SM_MISC = 16;
constexpr int SM_FIN = 48;
constexpr int SM_STAT = 64;
constexpr int SM_CEN = 112;
constexpr int SM_DBAR = 128;
constexpr int SM_W = 256;
constexpr int SM_PUB = SM_W + 384;
constexpr int SM_PROBE = SM_PUB + 768;
constexpr int SM_CRED = 1792;
constexpr int SM_CNT2 = SM_CRED;
constexpr int SM_DATA = 2048;
constexpr int cmax(int a, int b) { return a > b ? a : b; }
constexpr int A_CNT = SM_DATA;
constexpr int KR = CFG_KR, LISTB = (GPW * 32 + 8 * KR) * 4;
constexpr int A_LIST = A_CNT + NF * GPW * 128;
constexpr int A_ST = (A_LIST + NF * LISTB + 127) / 128 * 128;
constexpr int A_END = A_ST + NB * 256;
constexpr int B_TB = SM_DATA;
constexpr int B_TA = SM_DATA + (ROWS2_MAX + 8) * 2;
constexpr int B_END = SM_DATA + (ROWS2_MAX + 8) * 6;
constexpr int C_S = SM_DATA;
constexpr int C_END = C_S + ROWS3_MAX * 8;
constexpr int T_G = SM_DATA, TWB = 4096 + 2048 + 512, T_END = T_G + NPC * WPP * TWB;
constexpr int ZEND = cmax(A_END, C_END);
constexpr int SM_ZERO = (cmax(C_END, T_END) + 127) / 128 * 128;
constexpr int SMEM_BYTES = cmax(cmax(A_END, B_END), SM_ZERO + 4096);
static_assert(SMEM_BYTES <= 232448 && SM_PROBE + 128 <= SM_CRED, "shared memory");
static_assert(NPC * RPC >= ROWS3_MAX && NPC * WPP + 3 <= NW, "tail");

constexpr uint32_t FIN = 0x80000000u;

constexpr uint32_t WIN = 524288;
constexpr int CWIN = N2 + N3, NWIN = CWIN + 2, CPAIRS = 31;
constexpr uint32_t PROBE_OFF = (uint32_t)NWIN * WIN;
constexpr int NPROBE = 16;
static_assert(NWIN <= NCTA && NPROBE <= NW, "windows");
constexpr size_t RING_BYTES = (size_t)PROBE_OFF + WIN;
__device__ __align__(128) unsigned char g_ring[2 * RING_BYTES + WIN];
__device__ __align__(128) uint32_t g_S[2][32][ROWS3_MAX];
__device__ __align__(128) float4 g_Sg[E_MAX];
__device__ uint32_t g_dirty[E_MAX / 32];
__device__ uint32_t g_epoch;

#define TR(ev, on)
#define ACC_DECL
#define ACC(i, n)
#define ACC_SAVE

struct Params {
    const uint2* m;
    const int* idx_in;
    const int* idx_out;
    const __nv_bfloat16* dist;
    const __nv_bfloat16* angle;
    const __nv_bfloat16* centers;
    const __nv_bfloat16* freq;
    const __nv_bfloat16* w_rbf;
    const __nv_bfloat16* w_sbf;
    const __nv_bfloat16* w_down;
    const __nv_bfloat16* w_up;
    uint2* out;
    unsigned char* ring;
    cudaTextureObject_t t_in, t_out, t_ang;
    int E, n4;
    uint32_t rows2, nrows2, magic2, rows3;
    uint32_t ring_lo, ring_hi;
};

__device__ __forceinline__ float bflo(uint32_t w) { return __uint_as_float(w << 16); }
__device__ __forceinline__ float bfhi(uint32_t w) { return __uint_as_float(w & 0xffff0000u); }
__device__ __forceinline__ uint32_t pack_bf2(float lo, float hi) {
    uint32_t r;
    asm("cvt.rn.bf16x2.f32 %0, %1, %2;" : "=r"(r) : "f"(hi), "f"(lo));
    return r;
}
__device__ __forceinline__ uint32_t mul_bf2(uint32_t a, uint32_t b) {
    uint32_t r;
    asm("mul.rn.bf16x2 %0, %1, %2;" : "=r"(r) : "r"(a), "r"(b));
    return r;
}
__device__ __forceinline__ uint32_t sub_bf2(uint32_t a, uint32_t b) {
    uint32_t r;
    asm("sub.rn.bf16x2 %0, %1, %2;" : "=r"(r) : "r"(a), "r"(b));
    return r;
}
__device__ __forceinline__ uint32_t maxabs_bf2(uint32_t a, uint32_t b) {
    uint32_t r;
    asm("max.NaN.xorsign.abs.bf16x2 %0, %1, %2;" : "=r"(r) : "r"(a), "r"(b));
    return r;
}
__device__ __forceinline__ void mbar_init(uint32_t a, uint32_t n) {
    asm volatile("mbarrier.init.shared::cta.b64 [%0], %1;" ::"r"(a), "r"(n) : "memory");
}
__device__ __forceinline__ void mbar_arrive(uint32_t a) {
    asm volatile("mbarrier.arrive.shared::cta.b64 _, [%0];" ::"r"(a) : "memory");
}
__device__ __forceinline__ void mbar_arrive_if(uint32_t a, bool on) {
    asm volatile("{.reg .pred q; setp.ne.u32 q, %1, 0; @q mbarrier.arrive.shared::cta.b64 _, [%0];}" ::"r"(a), "r"((uint32_t)on) : "memory");
}
__device__ __forceinline__ void mbar_wait(uint32_t a, uint32_t parity) {
    uint32_t ok;
    int guard = 0;
    do {
        asm volatile("{.reg .pred p; mbarrier.try_wait.parity.shared::cta.b64 p, [%1], %2, %3; selp.u32 %0, 1, 0, p;}"
                     : "=r"(ok) : "r"(a), "r"(parity), "r"(CFG_HINT) : "memory");
        if (!ok) {
            if (++guard > GUARD) __trap();
        }
    } while (!ok);
}
__device__ __forceinline__ void cta_sync() { __syncwarp(); __syncthreads(); }
__device__ __forceinline__ void bar_sync(int id, int n) { asm volatile("bar.sync %0, %1;" ::"r"(id), "r"(n) : "memory"); }
__device__ __forceinline__ bool mbar_test(uint32_t a, uint32_t parity) {
    uint32_t ok;
    asm volatile("{.reg .pred p; mbarrier.test_wait.parity.shared::cta.b64 p, [%1], %2; selp.u32 %0, 1, 0, p;}"
                 : "=r"(ok) : "r"(a), "r"(parity) : "memory");
    return ok;
}
__device__ __forceinline__ uint32_t ld_acq(const uint32_t* p) {
    uint32_t v;
    asm volatile("ld.acquire.gpu.global.u32 %0, [%1];" : "=r"(v) : "l"(p) : "memory");
    return v;
}
__device__ __forceinline__ uint32_t ld_rlx(const uint32_t* p) {
    uint32_t v;
    asm volatile("ld.relaxed.gpu.global.u32 %0, [%1];" : "=r"(v) : "l"(p) : "memory");
    return v;
}
__device__ __forceinline__ void st_rlx(uint32_t* p, uint32_t v) {
    asm volatile("st.relaxed.gpu.global.u32 [%0], %1;" ::"l"(p), "r"(v) : "memory");
}
__device__ __forceinline__ void red_rlx(uint32_t* p, uint32_t v) {
    asm volatile("red.relaxed.gpu.global.add.u32 [%0], %1;" ::"l"(p), "r"(v) : "memory");
}
__device__ __forceinline__ uint32_t spin_ge(const uint32_t* p, uint32_t target) {
    int guard = 0;
    while (ld_rlx(p) < target) {
        __nanosleep(CFG_POLL);
        if (++guard > GUARD) __trap();
    }
    return ld_acq(p);
}
__device__ __forceinline__ void fence_gpu() { asm volatile("fence.acq_rel.gpu;" ::: "memory"); }
__device__ __forceinline__ void fence_async_smem() { asm volatile("fence.proxy.async.shared::cta;" ::: "memory"); }
__device__ __forceinline__ void fence_async_all() { asm volatile("fence.proxy.async;" ::: "memory"); }
__device__ __forceinline__ void bulk_store(void* g, uint32_t s, uint32_t bytes) {
    asm volatile("cp.async.bulk.global.shared::cta.bulk_group [%0], [%1], %2;" ::"l"(g), "r"(s), "r"(bytes) : "memory");
}
__device__ __forceinline__ void cp16(uint32_t s, const void* g, bool on) {
    asm volatile("{.reg .pred q; setp.ne.u32 q, %2, 0; @q cp.async.cg.shared.global [%0], [%1], 16;}" ::"r"(s), "l"(g), "r"((uint32_t)on) : "memory");
}
__device__ __forceinline__ void cp16z(uint32_t s, const void* g, int bytes) {
    asm volatile("cp.async.cg.shared.global [%0], [%1], 16, %2;" ::"r"(s), "l"(g), "r"(bytes) : "memory");
}
__device__ __forceinline__ void cp_commit() { asm volatile("cp.async.commit_group;" ::: "memory"); }
template <int N> __device__ __forceinline__ void cp_wait() { asm volatile("cp.async.wait_group %0;" ::"n"(N) : "memory"); }
__device__ __forceinline__ uint32_t atoms_add(uint32_t a, uint32_t v) {
    uint32_t o;
    asm volatile("atom.shared.add.u32 %0, [%1], %2;" : "=r"(o) : "r"(a), "r"(v) : "memory");
    return o;
}
__device__ __forceinline__ void sts32(uint32_t a, uint32_t v) { asm volatile("st.shared.u32 [%0], %1;" ::"r"(a), "r"(v) : "memory"); }
__device__ __forceinline__ void sts16(uint32_t a, uint32_t v) { asm volatile("st.shared.u16 [%0], %1;" ::"r"(a), "h"((uint16_t)v) : "memory"); }
__device__ __forceinline__ void sts64(uint32_t a, uint32_t x, uint32_t y) { asm volatile("st.shared.v2.u32 [%0], {%1,%2};" ::"r"(a), "r"(x), "r"(y) : "memory"); }
__device__ __forceinline__ uint32_t lds32(uint32_t a) {
    uint32_t v;
    asm volatile("ld.shared.u32 %0, [%1];" : "=r"(v) : "r"(a) : "memory");
    return v;
}
__device__ __forceinline__ uint2 lds64v(uint32_t a) {
    uint2 v;
    asm volatile("ld.volatile.shared.v2.u32 {%0,%1}, [%2];" : "=r"(v.x), "=r"(v.y) : "r"(a) : "memory");
    return v;
}
__device__ __forceinline__ uint32_t lds32v(uint32_t a) {
    uint32_t v;
    asm volatile("ld.volatile.shared.u32 %0, [%1];" : "=r"(v) : "r"(a) : "memory");
    return v;
}
__device__ __forceinline__ uint4 lds128(uint32_t a) {
    uint4 v;
    asm volatile("ld.shared.v4.u32 {%0,%1,%2,%3}, [%4];" : "=r"(v.x), "=r"(v.y), "=r"(v.z), "=r"(v.w) : "r"(a) : "memory");
    return v;
}
__device__ __forceinline__ void sts128(uint32_t a, uint4 v) {
    asm volatile("st.shared.v4.u32 [%0], {%1,%2,%3,%4};" ::"r"(a), "r"(v.x), "r"(v.y), "r"(v.z), "r"(v.w) : "memory");
}
#define LD_Q "ld.relaxed.gpu.global"
__device__ __forceinline__ uint4 ldg_q128(const void* p) {
    uint4 v;
    asm volatile(LD_Q ".v4.u32 {%0,%1,%2,%3}, [%4];"
                 : "=r"(v.x), "=r"(v.y), "=r"(v.z), "=r"(v.w) : "l"(p) : "memory");
    return v;
}
__device__ __forceinline__ uint2 ldg_q64(const void* p) {
    uint2 v;
    asm volatile(LD_Q ".v2.u32 {%0,%1}, [%2];" : "=r"(v.x), "=r"(v.y) : "l"(p) : "memory");
    return v;
}
__device__ __forceinline__ void red_v4(float4* p, float a, float b, float c, float d) {
    asm volatile("red.global.add.v4.f32 [%0], {%1,%2,%3,%4};" ::"l"(p), "f"(a), "f"(b), "f"(c), "f"(d) : "memory");
}
__device__ __forceinline__ uint2 down_row(uint2 r, const float* wd) {
    float x0 = bflo(r.x), x1 = bfhi(r.x), x2 = bflo(r.y), x3 = bfhi(r.y);
    float y[4];
#pragma unroll
    for (int j = 0; j < 4; j++) y[j] = x0 * wd[j] + x1 * wd[4 + j] + x2 * wd[8 + j] + x3 * wd[12 + j];
    return make_uint2(pack_bf2(y[0], y[1]), pack_bf2(y[2], y[3]));
}
__device__ __forceinline__ uint32_t prmt(uint32_t a, uint32_t b, uint32_t s) {
    uint32_t r;
    asm("prmt.b32 %0, %1, %2, %3;" : "=r"(r) : "r"(a), "r"(b), "r"(s));
    return r;
}
__device__ __forceinline__ uint32_t bitsel(uint32_t a, uint32_t b, uint32_t m) {
    uint32_t r;
    asm("lop3.b32 %0, %1, %2, %3, 0xE4;" : "=r"(r) : "r"(a), "r"(b), "r"(m));
    return r;
}
__device__ __forceinline__ uint32_t pack_h2(float lo, float hi) {
    uint32_t r;
    asm("cvt.rn.f16x2.f32 %0, %1, %2;" : "=r"(r) : "f"(hi), "f"(lo));
    return r;
}
__device__ __forceinline__ uint32_t mul_h2(uint32_t a, uint32_t b) {
    uint32_t r;
    asm("mul.rn.f16x2 %0, %1, %2;" : "=r"(r) : "r"(a), "r"(b));
    return r;
}
__device__ __forceinline__ uint32_t lds32nv(uint32_t a) {
    uint32_t v;
    asm volatile("ld.shared.u32 %0, [%1];" : "=r"(v) : "r"(a));
    return v;
}
__device__ __forceinline__ uint32_t lds16nv(uint32_t a) {
    uint32_t v;
    asm volatile("ld.shared.u16 %0, [%1];" : "=r"(v) : "r"(a));
    return v;
}
#define ST_Q "st.relaxed.gpu.global"
__device__ __forceinline__ void stg_q128(void* p, uint32_t a, uint32_t b, uint32_t c, uint32_t d, bool on) {
    asm volatile("{.reg .pred q; setp.ne.u32 q, %5, 0; @q " ST_Q ".v4.u32 [%0], {%1,%2,%3,%4};}"
                 ::"l"(p), "r"(a), "r"(b), "r"(c), "r"(d), "r"((uint32_t)on) : "memory");
}
__device__ __forceinline__ void stg_q64(void* p, uint32_t a, uint32_t b, bool on) {
    asm volatile("{.reg .pred q; setp.ne.u32 q, %3, 0; @q " ST_Q ".v2.u32 [%0], {%1,%2};}"
                 ::"l"(p), "r"(a), "r"(b), "r"((uint32_t)on) : "memory");
}
__device__ __forceinline__ void st_rlx_if(uint32_t* p, uint32_t v, bool on) {
    asm volatile("{.reg .pred q; setp.ne.u32 q, %2, 0; @q st.relaxed.gpu.global.u32 [%0], %1;}" ::"l"(p), "r"(v), "r"((uint32_t)on) : "memory");
}
__device__ __forceinline__ void ldq128_keep(uint4& v, const void* p, bool on) {
    asm volatile("{.reg .pred q; setp.ne.u32 q, %5, 0; @q ld.relaxed.gpu.global.v4.u32 {%0,%1,%2,%3}, [%4];}"
                 : "+r"(v.x), "+r"(v.y), "+r"(v.z), "+r"(v.w) : "l"(p), "r"((uint32_t)on) : "memory");
}
__device__ __forceinline__ void reds_add(uint32_t a, uint32_t v) { asm volatile("red.shared.add.u32 [%0], %1;" ::"r"(a), "r"(v) : "memory"); }
__device__ __forceinline__ void sts32_if(uint32_t a, uint32_t v, bool on) {
    asm volatile("{.reg .pred q; setp.ne.u32 q, %2, 0; @q st.shared.u32 [%0], %1;}" ::"r"(a), "r"(v), "r"((uint32_t)on) : "memory");
}
__device__ __forceinline__ void sts64_if(uint32_t a, uint32_t x, uint32_t y, bool on) {
    asm volatile("{.reg .pred q; setp.ne.u32 q, %3, 0; @q st.shared.v2.u32 [%0], {%1,%2};}" ::"r"(a), "r"(x), "r"(y), "r"((uint32_t)on) : "memory");
}
__device__ __forceinline__ void lds128_keep(uint4& v, uint32_t a, bool on) {
    asm volatile("{.reg .pred q; setp.ne.u32 q, %5, 0; @q ld.volatile.shared.v4.u32 {%0,%1,%2,%3}, [%4];}"
                 : "+r"(v.x), "+r"(v.y), "+r"(v.z), "+r"(v.w) : "r"(a), "r"((uint32_t)on) : "memory");
}
__device__ __forceinline__ void or3_if(uint32_t& x, uint32_t a, uint32_t b, bool on) {
    asm("{.reg .pred q; setp.ne.u32 q, %3, 0; @q lop3.b32 %0, %0, %1, %2, 0xfe;}" : "+r"(x) : "r"(a), "r"(b), "r"((uint32_t)on));
}
__device__ __forceinline__ uint32_t clk() {
    uint32_t t;
    asm volatile("mov.u32 %0, %%clock;" : "=r"(t) :: "memory");
    return t;
}
__device__ __forceinline__ void sg_add(int row, float a, float b, float c, float d) {
    red_v4(g_Sg + row, a, b, c, d);
    st_rlx(g_dirty + (row >> 5), 1u);
}
__device__ __forceinline__ void slow_add(const uint2* m, uint32_t sb, int in, int out, float c) {
    const uint2 r = __ldg(m + in);
    const float x[4] = {bflo(r.x), bfhi(r.x), bflo(r.y), bfhi(r.y)};
    float y[4] = {0.f, 0.f, 0.f, 0.f};
#pragma unroll
    for (int k = 0; k < 4; k++) {
        const uint4 q = lds128(sb + SM_W + 320 + k * 16);
        y[0] = k ? y[0] + x[k] * __uint_as_float(q.x) : x[k] * __uint_as_float(q.x);
        y[1] = k ? y[1] + x[k] * __uint_as_float(q.y) : x[k] * __uint_as_float(q.y);
        y[2] = k ? y[2] + x[k] * __uint_as_float(q.z) : x[k] * __uint_as_float(q.z);
        y[3] = k ? y[3] + x[k] * __uint_as_float(q.w) : x[k] * __uint_as_float(q.w);
    }
    const uint32_t lo = pack_bf2(y[0], y[1]), hi = pack_bf2(y[2], y[3]);
    sg_add(out, c * bflo(lo), c * bfhi(lo), c * bflo(hi), c * bfhi(hi));
}

struct Mat4 { uint32_t b[4]; };
__device__ __forceinline__ Mat4 load_mat4(const __nv_bfloat16* w, int lane) {
    const unsigned short* u = (const unsigned short*)w + (lane >> 2 & 1);
    const bool on = lane >> 3 == (lane & 3);
    Mat4 m;
#pragma unroll
    for (int k = 0; k < 4; k++) m.b[k] = on ? u[(k & 1) * 8 + (k & 2)] | (uint32_t)u[(k & 1) * 8 + 4 + (k & 2)] << 16 : 0u;
    return m;
}
__device__ __forceinline__ void mul4(const uint4& x, const Mat4& m, float (&y)[8]) {
    asm("mma.sync.aligned.m16n8k16.row.col.f32.bf16.bf16.f32 {%0,%1,%2,%3}, {%8,%9,%10,%11}, {%12,%13}, {%16,%16,%16,%16};\n\t"
        "mma.sync.aligned.m16n8k16.row.col.f32.bf16.bf16.f32 {%4,%5,%6,%7}, {%8,%9,%10,%11}, {%14,%15}, {%16,%16,%16,%16};"
        : "=&f"(y[0]), "=&f"(y[1]), "=&f"(y[4]), "=&f"(y[5]), "=&f"(y[2]), "=&f"(y[3]), "=&f"(y[6]), "=&f"(y[7])
        : "r"(x.x), "r"(x.z), "r"(x.y), "r"(x.w), "r"(m.b[0]), "r"(m.b[1]), "r"(m.b[2]), "r"(m.b[3]), "f"(0.f));
}

struct Scale { uint32_t eb[4]; bool allslow; };
__device__ __forceinline__ void md_stats(const uint4& in, const Mat4& wd, int lane) {
    float y[8];
    mul4(in, wd, y);
    uint32_t mx[4], se[4];
#pragma unroll
    for (int c = 0; c < 4; c++) {
        uint32_t a = __float_as_uint(y[c]) & 0x7fffffffu, b = __float_as_uint(y[4 + c]) & 0x7fffffffu;
        if (a >= 0x7f800000u) a = 0;
        if (b >= 0x7f800000u) b = 0;
        mx[c] = __reduce_max_sync(0xffffffffu, max(a, b));
        se[c] = __reduce_add_sync(0xffffffffu, (a >> 23) + (b >> 23) + (a ? 1u << 20 : 0u) + (b ? 1u << 20 : 0u));
    }
    if (lane < 4) {
        asm volatile("red.shared.max.u32 [%0], %1;" ::"r"(SB + SM_STAT + lane * 4), "r"(lane == 0 ? mx[0] : lane == 1 ? mx[1] : lane == 2 ? mx[2] : mx[3]) : "memory");
        reds_add(SB + SM_STAT + 16 + lane * 4, lane == 0 ? se[0] : lane == 1 ? se[1] : lane == 2 ? se[2] : se[3]);
    }
}
__device__ __forceinline__ Scale get_scale(uint32_t sb) {
    Scale s;
    s.allslow = false;
#pragma unroll
    for (int k = 0; k < 4; k++) {
        const uint32_t mx = lds32(sb + SM_STAT + 4 * k), se = lds32(sb + SM_STAT + 16 + 4 * k);
        const uint32_t mean = (uint32_t)__fdividef((float)(se & 0xfffffu), (float)max(se >> 20, 1u));
        uint32_t eb = min(min((mx + 0x6e0000u) >> 23, mean + 5u), 227u);
        if (eb < 27u) { s.allslow = s.allslow || mx != 0; eb = 27u; }
        if (eb > 170u) s.allslow = true;
        s.eb[k] = eb;
    }
    return s;
}

__device__ __forceinline__ uint32_t probe_rt(uint32_t* p) {
    uint32_t best = 0xffffffffu;
#pragma unroll 1
    for (int r = 0; r < CFG_PROBES; r++) {
        const uint32_t t0 = clock();
        uint32_t v;
        asm volatile("atom.relaxed.gpu.global.add.u32 %0, [%1], 1;" : "=r"(v) : "l"(p) : "memory");
        if (v > 100000u) __trap();
        const uint32_t t1 = clock();
        best = min(best, t1 - t0);
    }
    return best;
}
__device__ __forceinline__ uint32_t* pub_ptr(const Params& p, int blk, uint32_t sel) {
    const int pr = blk / 44;
    return (uint32_t*)(p.ring + PROBE_OFF + (pr ? 4096u << pr : 0u) + (sel << 12) + 2176 + (blk - pr * 44) * 32);
}
__device__ __forceinline__ void probe(const Params& p, uint32_t sb, int w, int lane) {
    const int blk = blockIdx.x, pr = w >> 1;
    uint32_t off = PROBE_OFF + blk * 16 + (pr ? 4096u << pr : 0u);
    if (pr == 7) off = blk < NWIN ? blk * WIN + 4064 : PROBE_OFF + 3584 + blk % 16 * 32;
    off += (w & 1) * 4096;
    if (lane < 8) st_rlx((uint32_t*)(p.ring + (off & ~31u)) + lane, 0u);
    if (lane == 0) sts32(sb + SM_PROBE + w * 4, probe_rt((uint32_t*)(p.ring + off)));
}
__device__ __forceinline__ void assign_role(const Params& p, uint32_t sb, int lane) {
    {
        const bool x = lane < 8 && lds32(sb + SM_PROBE + lane * 8 + 4) < lds32(sb + SM_PROBE + lane * 8);
        const uint32_t near = __ballot_sync(0xffffffffu, x), bits = near & 1 ? ~near | 1u : near;
        const uint32_t tag = (lds32(sb + SM_MISC + 16) + 1) << 30;
        if (lane < 16) st_rlx(pub_ptr(p, blockIdx.x, lane >> 3) + (lane & 7), tag | (bits & 0xffu));
        constexpr int K = (NCTA + 31) / 32;
        __nanosleep(CFG_P0);
        uint32_t v[K], bad;
        int guard = 0;
        do {
            bad = 0;
#pragma unroll
            for (int k = 0; k < K; k++) {
                const int b = min(lane + 32 * k, NCTA - 1);
                v[k] = ld_rlx(pub_ptr(p, b, near >> (b / 44) & 1));
                bad |= v[k] ^ tag;
            }
            bad = __any_sync(0xffffffffu, bad >> 30);
            if (bad) __nanosleep(CFG_PSLEEP);
            if (++guard > GUARD) __trap();
        } while (bad);
#pragma unroll
        for (int k = 0; k < K; k++) sts32(sb + SM_PUB + (lane + 32 * k) * 4, v[k]);
    }
    __syncwarp();
    constexpr int NP = NCTA / 2, NTAB = H2 + H3;
    const int me = blockIdx.x >> 1, odd = blockIdx.x & 1;
    uint32_t pp[3], key[3];
    int n1 = 0;
#pragma unroll
    for (int k = 0; k < 3; k++) {
        const int i = lane + 32 * k;
        pp[k] = lds32(sb + SM_PUB + min(i, NP - 1) * 8) & 1;
        key[k] = (i * CFG_KM % CFG_KN) << 8 | i;
        n1 += 2 * __popc(__ballot_sync(0xffffffffu, i < NP && pp[k]));
    }
    bool fixed = n1 < NTAB || NCTA - n1 < NTAB;
    if (fixed) {
        n1 = NP / 2 * 2;
        pp[0] = pp[1] = pp[2] = lane & 1;
    }
    const uint32_t mine = __shfl_sync(0xffffffffu, (me < 32 ? key[0] : me < 64 ? key[1] : key[2]) * 2 + (me < 32 ? pp[0] : me < 64 ? pp[1] : pp[2]), me & 31);
    const int part = mine & 1;
    int pos = odd;
#pragma unroll
    for (int k = 0; k < 3; k++) pos += 2 * __popc(__ballot_sync(0xffffffffu, lane + 32 * k < NP && pp[k] == (uint32_t)part && key[k] < mine / 2));
    const int role = pos < H2 ? 1 : pos < NTAB ? 2 : 0;
    const int id = pos < H2 ? part * H2 + pos : pos < NTAB ? part * H3 + pos - H2 : (part ? NCTA - n1 - NTAB : 0) + pos - NTAB;
    const uint32_t v = lds32(sb + SM_PUB + lane * 4);
    uint32_t lin = 0;
#pragma unroll
    for (int b = 0; b < 6; b++) lin |= (__popc(__ballot_sync(0xffffffffu, (v >> (b + 1)) & 1)) > 16 ? 1u : 0u) << b;
    if (lane == 0) {
        sts32(sb + SM_MISC, role << 8 | id);
        sts32(sb + SM_MISC + 4, lin);
        sts32(sb + SM_MISC + 8, NCTA - n1 - NTAB);
        sts32(sb + SM_MISC + 20, part);
        sts32(sb + SM_MISC + 12, role == 0 ? id : role == 1 ? N1 + id : N1 + N2 + id);
    }
}
__device__ __forceinline__ uint32_t sel_of(uint32_t sb, int widx, uint32_t k, int part) {
    return (__popc(k & lds32(sb + SM_MISC + 4)) ^ (lds32(sb + SM_PUB + widx * 4) >> 7) ^ part) & 1;
}
__device__ __forceinline__ uint32_t gran_off(uint32_t sb, int widx, int k, int part) { return (2 * k + sel_of(sb, widx, k, part)) << 12; }
__device__ __forceinline__ uint32_t q1a_off(uint32_t sb, int src, int blk, int part) { return gran_off(sb, 2 * blk + part, src >> 1, part) + (src & 1) * 2048; }
__device__ __forceinline__ uint32_t q1h_off(uint32_t sb, int src, int blk, int part) { return gran_off(sb, 2 * blk + part, 32 + (src >> 2), part) + (src & 3) * 1024; }
__device__ __forceinline__ uint32_t* ctl_word(const Params& p, uint32_t sb, int k, int word, int part) {
    const int widx = CWIN + lds32(sb + SM_MISC + 16);
    return (uint32_t*)(p.ring + (widx * WIN + ((2 * k + sel_of(sb, widx, k, part)) << 12))) + word;
}
__device__ __forceinline__ uint32_t* cred1_of(const Params& p, uint32_t sb, int src) { return ctl_word(p, sb, src >> 3, (src & 7) * 128, src >= (int)lds32(sb + SM_MISC + 8)); }
__device__ __forceinline__ uint32_t* fin1_of(const Params& p, uint32_t sb, int dst) { return ctl_word(p, sb, 8 + (dst >> 3), (dst & 7) * 128, dst / H2); }
__device__ __forceinline__ uint32_t* cred2_of(const Params& p, uint32_t sb, int src) { return ctl_word(p, sb, 16 + (src >> 3), (src & 7) * 128, src / H2); }
__device__ __forceinline__ uint32_t* fin2_of(const Params& p, uint32_t sb, int dst) { return ctl_word(p, sb, 24 + (dst >> 3), (dst & 7) * 128, dst / H3); }
__device__ __forceinline__ uint32_t* rdy_of(const Params& p, uint32_t sb, int word, int part) { return ctl_word(p, sb, 28, word, part); }
__device__ __forceinline__ uint32_t q2_off(uint32_t sb, int blk, int dst) {
    return (N2 + dst) * WIN + gran_off(sb, N2 + dst, (blk >> 1) * 4 + (blk & 1), dst / H3);
}
template <bool IS1>
__device__ __forceinline__ void clear_queues(const Params& p, uint32_t sb, int id, int lane) {
    constexpr int NA = (N1 + 1) / 2, NG = NA + (N1 + 3) / 4, N = IS1 ? NG * N2 : NI * 2;
    if (IS1) {
#pragma unroll 1
        for (int k = 0; k < 8; k++) sts128(sb + SM_ZERO + (k * 32 + lane) * 16, make_uint4(0, 0, 0, 0));
        if (lane == 0) spin_ge(rdy_of(p, sb, 320, lds32(sb + SM_MISC + 20)), NTAIL);
    }
    __syncwarp();
    fence_async_smem();
    for (int k = IS1 ? id + lane * N1 : lane; k < N; k += IS1 ? 32 * N1 : 32) {
        const int wi = k / NG, g = k - wi * NG;
        const uint32_t off = IS1 ? wi * WIN + gran_off(sb, wi, g < NA ? g : 32 + g - NA, wi & 1) : q2_off(sb, k >> 1, id) + (k & 1) * 16384;
        bulk_store(p.ring + off, sb + SM_ZERO, 4096);
    }
    asm volatile("cp.async.bulk.commit_group;" ::: "memory");
    asm volatile("cp.async.bulk.wait_group 0;" ::: "memory");
    TR(21, IS1 && lane == 0);
    if (!IS1) {
        fence_async_all();
        __syncwarp();
        fence_gpu();
        if (lane < NI) red_rlx(rdy_of(p, sb, id / H3 * H2 + lane, id / H3), 1u);
    }
    __syncwarp();
}

struct In8 { uint4 a[2], o[2]; uint2 g[2]; };
__device__ __forceinline__ void p1_load(const Params& p, In8& r, int i4) {
#pragma unroll
    for (int u = 0; u < 2; u++) {
        [[maybe_unused]] uint32_t x, y;
        asm volatile("tex.1d.v4.u32.s32 {%0,%1,%2,%3}, [%4, {%5}];" : "=r"(r.a[u].x), "=r"(r.a[u].y), "=r"(r.a[u].z), "=r"(r.a[u].w) : "l"(p.t_in), "r"(i4 + u * 32));
        asm volatile("tex.1d.v4.u32.s32 {%0,%1,%2,%3}, [%4, {%5}];" : "=r"(r.o[u].x), "=r"(r.o[u].y), "=r"(r.o[u].z), "=r"(r.o[u].w) : "l"(p.t_out), "r"(i4 + u * 32));
        asm volatile("tex.1d.v4.u32.s32 {%0,%1,%2,%3}, [%4, {%5}];" : "=r"(r.g[u].x), "=r"(r.g[u].y), "=r"(x), "=r"(y) : "l"(p.t_ang), "r"(i4 + u * 32));
    }
}
__device__ __forceinline__ uint32_t imad(uint32_t a, uint32_t b, uint32_t c) {
    uint32_t r;
    asm("mad.lo.u32 %0, %1, %2, %3;" : "=r"(r) : "r"(a), "r"(b), "r"(c));
    return r;
}
__device__ __forceinline__ unsigned char* ring_ptr(const Params& p, uint32_t lo) {
    uint64_t r;
    asm("mov.b64 %0, {%1, %2};" : "=l"(r) : "r"(lo), "r"(p.ring_hi));
    return (unsigned char*)r;
}
__device__ __forceinline__ uint32_t keep32(uint32_t x) {
    return __shfl_sync(0xffffffffu, x, threadIdx.x & 31);
}
__device__ __forceinline__ uint32_t opaque32(uint32_t x) {
    asm volatile("" : "+r"(x));
    return x;
}
template <typename T> __device__ __forceinline__ T* opaque(T* p) {
    asm volatile("" : "+l"(p));
    return p;
}
template <int LUT> __device__ __forceinline__ uint32_t lop3(uint32_t a, uint32_t b, uint32_t c) {
    uint32_t r;
    asm("lop3.b32 %0, %1, %2, %3, %4;" : "=r"(r) : "r"(a), "r"(b), "r"(c), "n"(LUT));
    return r;
}
__device__ __forceinline__ uint32_t dp4(uint32_t a, uint32_t b, uint32_t c) {
    uint32_t r;
    asm("dp4a.u32.u32 %0, %1, %2, %3;" : "=r"(r) : "r"(a), "r"(b), "r"(c));
    return r;
}
__device__ __forceinline__ uint32_t dp2(uint32_t a, uint32_t b, uint32_t c) {
    uint32_t r;
    asm("dp2a.lo.u32.u32 %0, %1, %2, %3;" : "=r"(r) : "r"(a), "r"(b), "r"(c));
    return r;
}
__device__ __forceinline__ void p1_put(uint32_t sb, uint32_t wa, uint32_t wb, uint32_t old, bool on) {
    asm volatile("{.reg .pred q; setp.ne.u32 q, %3, 0; @q st.shared.v2.u32 [%0], {%1,%2};}"
                 ::"r"(sb + A_ST + prmt(old, wb, 0xf762)), "r"(wa), "r"(prmt(wb, old, 0x7210)), "r"((uint32_t)on) : "memory");
}
__device__ __forceinline__ void p1_slow_tile(const Params& p, uint32_t sb, int i4) {
    const float f = __bfloat162float(p.freq[0]);
#pragma unroll 1
    for (int u = 0; u < 8; u++) {
        const int k4 = i4 + (u >> 2) * 32;
        if (k4 < p.n4) {
            const size_t t = (size_t)k4 * 4 + (u & 3);
            const float x = __bfloat162float(__float2bfloat16(f * __bfloat162float(p.angle[t])));
            slow_add(p.m, sb, p.idx_in[t], p.idx_out[t], __bfloat162float(__float2bfloat16(cosf(x))));
        }
    }
}
__device__ __forceinline__ void role_p1(const Params& p, uint32_t sb, int id, int w, int lane) {
    lane = keep32(lane);
    const uint32_t f2 = (uint32_t)__bfloat16_as_ushort(p.freq[0]) * 0x10001u;
    constexpr int TG = CFG_TG, NTK = P1W;
    static_assert(NTK <= 16, "tickets");
    const int tc = (w + id) % NTK, first = (N1 * P1W + tc) * (TG * 64);
    uint32_t* const tickets = opaque(ctl_word(p, sb, 29 + tc / 8, tc % 8 * 128 + lane, tc & 1));
    auto draw = [&]() {
        uint32_t t = 0;
        asm volatile("{.reg .pred q; setp.eq.u32 q, %2, 0; @q atom.relaxed.gpu.global.add.u32 %0, [%1], 1;}" : "+r"(t) : "l"(tickets), "r"(lane) : "memory");
        return t;
    };
    int i4 = (id * P1W + w) * (TG * 64);
    In8 r;
    ACC_DECL
    uint32_t tk = draw();
    p1_load(p, r, i4 + lane);
    while (i4 < p.n4) {
        const int cur = i4;
        i4 += 64;
        if (i4 % (TG * 64) == 0) {
            i4 = min(__shfl_sync(0xffffffffu, tk, 0), 0x7fffffffu / (NTK * TG * 64) - N1 * P1W / NTK - 2) * (NTK * TG * 64) + first;
            tk = draw();
        }
        uint32_t wa[8], wb[8], x2[4];
        x2[0] = mul_bf2(r.g[0].x, f2); x2[1] = mul_bf2(r.g[0].y, f2);
        x2[2] = mul_bf2(r.g[1].x, f2); x2[3] = mul_bf2(r.g[1].y, f2);
        const uint32_t mx = maxabs_bf2(maxabs_bf2(x2[0], x2[1]), maxabs_bf2(x2[2], x2[3]));
        const bool fast = __all_sync(0xffffffffu, cur + 64 <= p.n4 && ((mx & 0x7fffu) <= 0x4300u) && ((mx & 0x7fff0000u) <= 0x43000000u));
        {
            const uint32_t in[8] = {r.a[0].x, r.a[0].y, r.a[0].z, r.a[0].w, r.a[1].x, r.a[1].y, r.a[1].z, r.a[1].w};
            const uint32_t ou[8] = {r.o[0].x, r.o[0].y, r.o[0].z, r.o[0].w, r.o[1].x, r.o[1].y, r.o[1].z, r.o[1].w};
#pragma unroll
            for (int j = 0; j < 8; j += 2) {
                const uint32_t ch = mul_h2(pack_h2(__cosf(bflo(x2[j >> 1])), __cosf(bfhi(x2[j >> 1]))), 0x24002400u);
#pragma unroll
                for (int k = j; k < j + 2; k++) {
                    const uint32_t blk = __umulhi(in[k], p.magic2), il = imad(blk, p.nrows2, in[k]);
                    wa[k] = k & 1 ? bitsel(ch, il, 0xffff0000u) : imad(ch, 65536u, il);
                    wb[k] = imad(blk, 1u << 21, imad(ou[k] >> 5, 1u - (1u << 21), ou[k] << 16));
                }
            }
        }
        p1_load(p, r, i4 + lane);
        if (fast) {
            uint32_t old[8], any = 0;
#pragma unroll
            for (int j = 0; j < 8; j++) old[j] = atoms_add(dp2(wb[j], 0x400u, 0u) + (sb + A_CNT), 0x80001u);
#pragma unroll
            for (int j = 0; j < 8; j++) any |= old[j];
            if (!__any_sync(0xffffffffu, any & 0xffe0u)) {
#pragma unroll
                for (int j = 0; j < 8; j++) p1_put(sb, wa[j], wb[j], old[j], true);
            } else {
                uint32_t pend = 0;
#pragma unroll
                for (int j = 0; j < 8; j++) { p1_put(sb, wa[j], wb[j], old[j], !(old[j] & 0xffe0u)); if (old[j] & 0xffe0u) pend |= 1u << j; }
                ACC(0, 1)
                for (int guard = 0; __any_sync(0xffffffffu, pend); guard++) {
                    __nanosleep(CFG_BSLEEP);
                    ACC(1, 1)
#pragma unroll
                    for (int j = 0; j < 8; j++) {
                        if (__any_sync(0xffffffffu, pend >> j & 1)) {
                            const uint32_t c = lds32v(sb + A_CNT + (pend >> j & 1 ? wb[j] >> 16 : 0) * 4);
                            const bool go = (pend >> j & 1) && (((old[j] >> 19) - (c >> 19) + c) & 8191u) < 32u;
                            p1_put(sb, wa[j], wb[j], old[j], go);
                            if (go) pend &= ~(1u << j);
                        }
                    }
                    if (guard > GUARD) __trap();
                }
            }
        } else {
            p1_slow_tile(p, sb, cur + lane);
            __syncwarp();
        }
    }
    __syncwarp();
    mbar_arrive_if(sb + SM_DONE, lane == 0);
    ACC_SAVE
}

__device__ __forceinline__ void role_flush(const Params& p, uint32_t sb, int id, int f, int lane) {
    lane = keep32(lane);
    const int half = lane >> 4, o = lane >> 2, q = lane & 3;
    const uint32_t hm = keep32(half ? 0xffff0000u : 0xffffu), lth = keep32(((1u << lane) - 1) & hm);
    const uint32_t list = sb + A_LIST + f * LISTB, cnt = keep32(sb + A_CNT + (f * GPW * 32 + lane) * 4);
    const uint32_t cred = opaque32(sb + SM_CRED + (half * 32 + f * GPW) * 4);
    const uint32_t pa = opaque32(p.ring_lo + (id >> 1) * 8192 + (id & 1) * 2048 + q * 16);
    const uint32_t ph = opaque32(p.ring_lo + (32 + (id >> 2)) * 8192 + (id & 3) * 1024 + q * 8 - 2048);
    const uint32_t sa = q * 16 + (o & 1) * 64;
    uint32_t qo[GPW], hs[GPW], cr[4] = {0, 0, 0, 0};
#pragma unroll
    for (int g = 0; g < GPW; g++) {
        const int blk = f * GPW + g;
        qo[g] = 32u << 25;
        const uint32_t sa = sel_of(sb, 2 * blk + half, id >> 1, half), sh = sel_of(sb, 2 * blk + half, 32 + (id >> 2), half);
        hs[g] = sa << 31 | (2 * sh + 1 - sa) << 22 | 1u << 24 | (lane & 15) << 15 | (blk * 32 + lane) * 2;
    }
    uint4 x[KR] = {}, y[KR] = {};
    uint32_t c[GPW] = {};
    auto scan = [&]() {
#pragma unroll
        for (int g = 0; g < GPW; g++) c[g] = lds32v(cnt + g * 128);
    };
    auto credits = [&]() {
        if (GPW == 4) { const uint4 v = lds128(cred); cr[0] = v.x; cr[1] = v.y; cr[2] = v.z; cr[3] = v.w; }
        else { const uint2 v = lds64v(cred); cr[0] = v.x; cr[1] = v.y; }
    };
    ACC_DECL
    int guard = 0;
    bool idle = false, done = false;
    while (true) {
        uint32_t fr[GPW], rank[GPW], num = 0, left = 0;
        bool ok[GPW];
        if (idle && !done && __all_sync(0xffffffffu, mbar_test(sb + SM_DONE, 0))) {
            done = true;
            TR(17, f == 0 && lane == 0);
#pragma unroll
            for (int g = 0; g < GPW; g++) {
                const uint32_t u = lds32v(cnt + g * 128) & 31u, hd = hs[g] ^ (u & 16u ? imad(hs[g], 1u << 24, 1u) & 0x01000001u : 0u);
#pragma unroll 2
                for (uint32_t j = 0, k; k = (j + lane) & 15u, j < 16; j++)
                    sts64_if(sb + A_ST + ((hd & 0x7ffu) << 7) + k * 8, p.rows2, (lane * 16 + k) | (hd & 0x1000000u), (u & 15u) && k >= (u & 15u));
                reds_add(cnt + g * 128, ((0u - u) & 15u) * 0x80001u);
            }
            __syncwarp();
            scan();
        }
#pragma unroll
        for (int g = 0; g < GPW; g++) {
            const bool isfull = c[g] & 0xfff0u;
            rank[g] = __popc(__ballot_sync(0xffffffffu, isfull) & lth);
            ok[g] = isfull && (int)(rank[g] << 25) < (int)(cr[g] - qo[g] + (63u << 25));
            ACC(2, __popc(__ballot_sync(0xffffffffu, isfull && !ok[g])))
        }
#pragma unroll
        for (int g = 0; g < GPW; g++) {
            const uint32_t m = __ballot_sync(0xffffffffu, ok[g]), n = __popc(m & hm), all = __popc(m), e = num + rank[g] + (half ? all - n : 0u);
            sts32_if(KR == 2 ? list + (e & 48u) * 4 + (e & 7u) * 8 + (e >> 1 & 4u) : imad(e, 4u, list), bitsel(imad(rank[g], 1u << 25, qo[g]), hs[g], 0x7e000000u), ok[g]);
            if (ok[g]) hs[g] ^= imad(hs[g], 1u << 24, 1u) & 0x01000001u;
            fr[g] = ok[g] ? 0u - 16u : 0u;
            left |= c[g] + fr[g];
            qo[g] = imad(n, 1u << 25, qo[g]);
            num += all;
        }
        __syncwarp();
        ACC(0, 1) ACC(1, num)
        if (num) {
            uint32_t la = list + o * (KR == 2 ? 8 : 4);
            int todo = (int)num - o, rest = num;
            do {
                uint32_t d[KR];
                if (KR == 2) { const uint2 v = lds64v(la); d[0] = v.x; d[KR - 1] = v.y; }
                else {
#pragma unroll
                    for (int k = 0; k < KR; k++) d[k] = lds32v(la + 32 * k);
                }
                while (true) {
                    uint32_t bad = 0;
#pragma unroll
                    for (int k = 0; k < KR; k++) {
                        const uint32_t m = d[k] & 0x7ffu;
                        lds128_keep(x[k], imad(m, 128u, sa) + (sb + A_ST), todo > 8 * k);
                        lds128_keep(y[k], imad(m, 128u, sa ^ 64) + (sb + A_ST), todo > 8 * k);
                    }
#pragma unroll
                    for (int k = 0; k < KR; k++)
                        or3_if(bad, lop3<0x7e>(x[k].y, x[k].w, d[k]), lop3<0x7e>(y[k].y, y[k].w, d[k]), todo > 8 * k);
                    if (!__any_sync(0xffffffffu, (int)imad(bad, 128u, 0u) < 0)) break;
                    if (++guard > GUARD) __trap();
                }
#pragma unroll
                for (int k = 0; k < KR; k++) {
                    const uint32_t mi = d[k] & 0x7e0u, dm = d[k] & 0xbec00000u;
                    x[k].x = bitsel(d[k], x[k].x, 0x40078000u);
                    x[k].y = prmt(x[k].y, x[k].w, 0x5410);
                    x[k].w = prmt(y[k].y, y[k].w, 0x5410);
                    y[k].x = bitsel(d[k], y[k].x, 0x40000000u);
                    y[k].y = y[k].z;
                    stg_q128(ring_ptr(p, dp4(dm, 0x20000000u, imad(mi, WIN / 32, pa))), x[k].x, x[k].y, x[k].z, x[k].w, todo > 8 * k);
                    stg_q64(ring_ptr(p, dp4(dm, 0x10200000u, imad(mi, WIN / 32, ph))), y[k].x, y[k].y, todo > 8 * k);
                }
                la += 32 * KR;
                todo -= 8 * KR;
                rest -= 8 * KR;
            } while (rest > 0);
#pragma unroll
            for (int g = 0; g < GPW; g++) c[g] = atoms_add(cnt + g * 128, fr[g]) + fr[g];
            credits();
            idle = num <= CFG_TH;
            if (done && !__any_sync(0xffffffffu, left & 0xffffu)) break;
            if (idle) { __nanosleep(CFG_TS); scan(); credits(); }
        } else {
            if (done && !__any_sync(0xffffffffu, left & 0xffffu)) break;
            idle = true;
            __nanosleep(CFG_FSLEEP);
            scan();
            credits();
            if (++guard > GUARD) __trap();
        }
    }
#pragma unroll
    for (int g = 0; g < GPW; g++) st_rlx_if(fin1_of(p, sb, half * H2 + f * GPW + g) + id, qo[g] - (32u << 25) + 1u, (lane & 15) == 0 && f * GPW + g < NI);
    mbar_arrive_if(sb + SM_DONE2, lane == 0);
    TR(18, f == 0 && lane == 0);
    ACC_SAVE
}
__device__ __forceinline__ void role_credit1(const Params& p, uint32_t sb, int id, int lane) {
    const uint32_t* const cred = cred1_of(p, sb, id) + lane * 2;
    for (int guard = 0; !__all_sync(0xffffffffu, mbar_test(sb + SM_DONE2, 0)); guard++) {
        const uint2 v = ldg_q64(cred);
        sts64(sb + SM_CRED + lane * 8, v.x, v.y);
        __nanosleep(CFG_C1SLEEP);
        if (guard > GUARD) __trap();
    }
}

__device__ __forceinline__ float h2f(uint32_t h) {
    float f;
    asm("{.reg .b16 t; cvt.u16.u32 t, %1; cvt.f32.f16 %0, t;}" : "=f"(f) : "r"(h));
    return f;
}
__device__ __forceinline__ void p2_slow(const Params& p, uint32_t sb, const uint32_t* tmp, int row0, uint32_t dst) {
#pragma unroll 1
    for (int j = 0; j < 4; j++)
        if (tmp[8 + j] & 0x40u) slow_add(p.m, sb, row0 + (tmp[j] & 0x7fffu), (tmp[4 + j] & 0x7fffu) * 32 + dst, h2f(tmp[j] >> 16) * 64.0f);
}
__device__ __forceinline__ uint32_t mul_h2_hi(uint32_t a, uint32_t b) {
    uint32_t r;
    asm("{.reg .b16 l, h; .reg .b32 t; mov.b32 {l, h}, %2; mov.b32 t, {h, h}; mul.rn.f16x2 %0, %1, t;}" : "=r"(r) : "r"(a), "r"(b));
    return r;
}
template <bool CHECK>
__device__ __forceinline__ void role_p2(const Params& p, uint32_t sb, int id, int w, int lane) {
    lane = keep32(lane);
    const int part = id / H2, blk = id - part * H2, row0 = blk * p.rows2;
    const int o = lane >> 2, q = lane & 3;
    uint32_t* const cbase = (uint32_t*)(p.ring + (CWIN + lds32(sb + SM_MISC + 16)) * WIN);
    const uint32_t cred = opaque32((uint32_t)(uintptr_t)(cbase + part * 32 + blk));
    const uint32_t pa = opaque32(p.ring_lo + (2 * blk + part) * WIN + q * 16), ph = opaque32(pa - q * 8);
    const uint32_t po = opaque32(p.ring_lo + (q2_off(sb, blk, part * H3) & ~4096u) + q * 16 + (o & 1) * 64);
    const uint32_t sel = __ballot_sync(0xffffffffu, q2_off(sb, blk, part * H3 + (lane & 15)) & 4096u) << 12;
    const uint32_t* const fins = fin1_of(p, sb, id);
    uint32_t st[QPW] = {}, sq[QPW] = {};
    uint4 qa[NBT];
    uint2 qh[NBT];
    auto load = [&](int k) {
        qa[k] = ldg_q128(ring_ptr(p, pa + (bitsel(sq[k], st[k] >> 19, 0x7f800u) & 0x7ffc0u)));
        qh[k] = ldg_q64(ring_ptr(p, ph + (bitsel(sq[k] >> 9, st[k] >> 20, 0x7fc00u) & 0x7ffe0u)));
    };
#pragma unroll
    for (int k = 0; k < QPW; k++) {
        const int src = w * QPW + k;
        st[k] = o << 25 | (src < N1 ? 1u : 5u);
        sq[k] = src < N1 ? q1h_off(sb, src, blk, part) << 9 | q1a_off(sb, src, blk, part) | (uint32_t)(cred1_of(p, sb, src) - cbase) / 8 : 0x7e000u * 513u;
    }
#pragma unroll
    for (int k = 0; k < NBT; k++) load(k);
    ACC_DECL
    int guard = 0;
    uint32_t streak = 0;
    while (true) {
        uint32_t nn[NBT], xx[NBT][4], hh[NBT][2], dd[NBT], any = 0;
        bool last = false;
#pragma unroll
        for (int k = 0; k < NBT; k++) {
            const uint4 a = qa[k];
            const uint2 h = qh[k];
            uint32_t n = 8;
            const uint32_t miss = __ballot_sync(0xffffffffu, (int)imad((a.x ^ st[k]) & (h.x ^ st[k]), 2u, 0u) >= 0);
            if (miss) {
                n = (__ffs(miss) - 1) >> 2;
                if (!__any_sync(0xffffffffu, st[k] & 8u)) { if (streak < CFG_PSTREAK) n &= CFG_PMASK; }
                else if (!__any_sync(0xffffffffu, ((st[k] >> 6) + ((n - o) << 19) ^ st[k]) & 0x1f80000u)) { st[k] |= 4u; last = true; }
            }
            ACC(1, n == 0) ACC(2, n != 0) ACC(3, n)
            st[k] = imad(n, 1u << 25, st[k]);
            st_rlx_if((uint32_t*)ring_ptr(p, imad(sq[k] & 0x7f0u, 32u, cred)), st[k], lane == 0 && n);
            xx[k][0] = bitsel(a.x, 0x00040000u, 0xbff87fffu); xx[k][1] = a.z; xx[k][2] = h.x & 0xbfffffffu; xx[k][3] = h.y;
            hh[k][0] = a.y; hh[k][1] = a.w; dd[k] = a.x >> 13 & 0x3cu; nn[k] = n;
            any |= n;
        }
        if (!any) {
#pragma unroll
            for (int k = 0; k < QPW; k++) {
                const uint32_t fin = ld_rlx(fins + ((sq[k] >> 12 & 62u) | (sq[k] >> 11 & 1u)));
                if (fin & 1u) st[k] |= (fin >> 6 & 0x1f80000u) | ((fin ^ (st[k] - (o << 25))) >> 25 ? 8u : 12u);
            }
            last = true;
            if (++guard > GUARD) __trap();
            streak++;
        } else streak = 0;
        if (last) {
            uint32_t all = 4u;
#pragma unroll
            for (int k = 0; k < QPW; k++) all &= st[k];
            last = __all_sync(0xffffffffu, all);
        }
        {
            uint32_t t[QPW], u[QPW];
#pragma unroll
            for (int k = 0; k < QPW; k++) { t[k] = st[(k + NBT) % QPW]; u[k] = sq[(k + NBT) % QPW]; }
#pragma unroll
            for (int k = 0; k < QPW; k++) { st[k] = t[k]; sq[k] = u[k]; }
        }
#pragma unroll
        for (int k = 0; k < NBT; k++) load(k);
#pragma unroll
      for (int k = 0; k < NBT; k++) {
        if (nn[k]) {
            const uint32_t* const x = xx[k];
            const uint32_t h0 = hh[k][0], h1 = hh[k][1], d4 = dd[k];
            const bool v = o < nn[k];
            uint32_t ta[4], tb[4], w0[4], w1[4];
            const uint32_t ca = imad(d4, 4u, sb + SM_CNT2 + q * 4), old = atoms_add(ca, v ? 0x10001u : 0u);
#pragma unroll
            for (int j = 0; j < 4; j++) {
                ta[j] = lds32nv(dp2(x[j], 4u, 0u) + (sb + B_TA));
                tb[j] = lds16nv(dp2(x[j], 2u, 0u) + (sb + B_TB));
            }
            const uint32_t tag = old << 8 & 0x40000000u;
#pragma unroll
            for (int j = 0; j < 4; j++) {
                const uint32_t z = prmt(j & 2 ? h1 : h0, 0, j & 1 ? 0x4342 : 0x4140);
                const uint32_t t23 = prmt((ta[j] & 0x60076007u) * 2050u, tb[j], 0x5341) & 0xfffcffffu;
                w0[j] = (imad(z, 128u, j & 1 ? 0u : tag) & 0x78007800u) | mul_h2_hi(ta[j] & 0x9ff89ff8u, x[j]);
                w1[j] = (imad(z, 2048u, 0u) & 0x78007800u) | mul_h2_hi(t23, x[j]);
            }
            if (CHECK && v && ((tb[0] | tb[1] | tb[2] | tb[3]) & 0x40u)) {
                uint32_t tmp[12];
#pragma unroll
                for (int j = 0; j < 4; j++) {
                    tmp[j] = x[j]; tmp[4 + j] = (j & 2 ? h1 : h0) >> (j & 1 ? 16 : 0); tmp[8 + j] = tb[j];
                    if (tb[j] & 0x40u) { w0[j] &= 0x78007800u; w1[j] &= 0x78007800u; }
                }
                p2_slow(p, sb, tmp, row0, part * H3 + d4 / 4);
            }
            const uint32_t off = (bitsel(old >> 9, old >> 7, 0x0f80u) & 0x4f80u) + imad(d4, WIN / 4, (sel >> (d4 / 4) & 4096u) + po);
            bool wait = v && (old & (0x10000u - NQ2));
            if (!__any_sync(0xffffffffu, wait)) {
                stg_q128(ring_ptr(p, off), w0[0], w1[0], w0[1], w1[1], v);
                stg_q128(ring_ptr(p, off ^ 64u), w0[2], w1[2], w0[3], w1[3], v);
            } else {
                bool pend = v;
                ACC(0, 1)
                for (int g2 = 0;; g2++) {
                    stg_q128(ring_ptr(p, off), w0[0], w1[0], w0[1], w1[1], pend && !wait);
                    stg_q128(ring_ptr(p, off ^ 64u), w0[2], w1[2], w0[3], w1[3], pend && !wait);
                    pend = wait;
                    if (!__any_sync(0xffffffffu, pend)) break;
                    __nanosleep(CFG_BSLEEP);
                    const uint32_t c = lds32v(ca);
                    wait = pend && (((old >> 16) - (c >> 16) + c) & 0xffffu) >= NQ2;
                    if (g2 > GUARD) __trap();
                }
            }
        }
      }
        if (last) break;
    }
    TR(17, w == 0 && lane == 0);
    __syncwarp();
    uint32_t rank = 0;
    if (lane == 0) { __threadfence_block(); rank = atoms_add(sb + SM_FIN, 1u); __threadfence_block(); }
    if (__shfl_sync(0xffffffffu, rank, 0) == P2W - 1 && lane < 16)
        st_rlx(fin2_of(p, sb, part * H3 + lane) + blk, FIN | (((lds32v(sb + SM_CNT2 + lane * 16) >> 16) - NQ2) & 0xffffu));
    __syncwarp();
    mbar_arrive_if(sb + SM_DONE, lane == 0);
    ACC_SAVE
}
__device__ __forceinline__ void role_credit(const Params& p, uint32_t sb, int id, int lane) {
    const uint32_t* const cred = cred2_of(p, sb, id) + (lane >> 2);
    uint32_t last = 0, last2 = 0;
    for (int guard = 0;; guard++) {
        if (__all_sync(0xffffffffu, mbar_test(sb + SM_DONE, 0))) break;
        const uint32_t c = ld_rlx(cred), c2 = ld_rlx(cred + 8);
        reds_add(sb + SM_CNT2 + lane * 4, 0u - ((c - last) & 0xffffu));
        reds_add(sb + SM_CNT2 + 128 + lane * 4, 0u - ((c2 - last2) & 0xffffu));
        last = c;
        last2 = c2;
        __nanosleep(CFG_CSLEEP);
        if (guard > GUARD) __trap();
    }
}

__device__ __forceinline__ void p3_wrap(uint32_t sb, int id, const uint32_t* tmp) {
    const Scale sc = get_scale(sb);
#pragma unroll 1
    for (int j = 0; j < 8; j++) {
        const uint32_t old = tmp[4 + j], v = tmp[12 + j], nw = old + v, t = (old ^ nw) & (v ^ nw);
        if (t & 0x80008000u) {
            const float k = (t & 0x8000u) ? ((v & 0x8000u) ? -1.0f : 1.0f) : 0.0f;
            const float q = (t & 0x80000000u) ? ((int)v < 0 ? -65536.0f : 65536.0f) : 0.0f;
            const uint32_t e0 = (j & 1) ? sc.eb[2] : sc.eb[0], e1 = (j & 1) ? sc.eb[3] : sc.eb[1];
            const float lo = k * 65536.0f * __uint_as_float((e0 - 10) << 23), hi = (q - k) * __uint_as_float((e1 - 10) << 23);
            if (j & 1) sg_add(tmp[j >> 1] * 32 + id, 0.f, 0.f, lo, hi);
            else sg_add(tmp[j >> 1] * 32 + id, lo, hi, 0.f, 0.f);
        }
    }
}
__device__ __forceinline__ uint32_t p3_val(uint32_t w) {
    const uint32_t mk = prmt(w, 0, 0xBB99);
    return ((w & 0x07ff07ffu) ^ mk) - mk;
}
__device__ __forceinline__ void role_p3(const Params& p, uint32_t sb, int id, int w, int lane) {
    lane = keep32(lane);
    uint32_t* const cred = opaque(cred2_of(p, sb, id / H3 * H2 + w) + id % H3);
    const uint32_t pq = opaque32(p.ring_lo + q2_off(sb, w, id) + lane * 16);
    auto off = [&](uint32_t n) { return (n & 1u) << 11 | (n & 2u) << 13; };
    const uint32_t pp = opaque32(pq - lane * 16 + 112);
    const uint32_t* const finp = opaque(fin2_of(p, sb, id) + w);
    auto tag_of = [&](uint32_t n) { return ~n << 28; };
    uint32_t n = 0, fin = 0, pr = 0, pk = 0;
    uint4 v[4] = {};
    bool have = false, last = false;
    ACC_DECL
    int guard = 0;
    while (true) {
        const uint32_t ex = tag_of(n);
        const bool ok = have && !__any_sync(0xffffffffu, ((v[0].x ^ ex) | (v[1].x ^ ex) | (v[2].x ^ ex) | (v[3].x ^ ex)) & 0x40000000u);
        if (ok) n++;
        const bool ready = (ok || !have) && __all_sync(0xffffffffu, !((pr ^ tag_of(n)) & 0x40000000u));
        st_rlx_if(cred, n * 16, lane == 0 && ok);
        if (!ok && !ready && __all_sync(0xffffffffu, fin & FIN)) {
            const uint32_t left = __shfl_sync(0xffffffffu, (fin - n * 16) & 0xffffu, 0);
            if (left - 1u > 0x8000u) break;
            if (left < 16u) {
#pragma unroll
                for (int u = 0; u < 4; u++) {
                    v[u] = make_uint4((ex & 0x40000000u) | (lane & 16) << 7, (lane & 15) << 11, (lane & 16) << 7, (lane & 15) << 11);
                    ldq128_keep(v[u], ring_ptr(p, pq + off(n)) + u * 512, u * 4 + (lane >> 3) < left);
                }
                have = last = !__any_sync(0xffffffffu, ((v[0].x ^ ex) | (v[1].x ^ ex) | (v[2].x ^ ex) | (v[3].x ^ ex)) & 0x40000000u);
                pr = ~tag_of(n + have);
                if (++guard > GUARD) __trap();
                continue;
            }
        }
        uint32_t row[8], val[16];
#pragma unroll
        for (int u = 0; u < 4; u++) {
            const uint4 x = v[u];
            row[2 * u] = prmt(bitsel(x.x << 1, x.y >> 3, 0x7000f000u), 0, 0x4431);
            row[2 * u + 1] = prmt(bitsel(x.z << 1, x.w >> 3, 0x7000f000u), 0, 0x4431);
            val[4 * u] = p3_val(x.x); val[4 * u + 1] = p3_val(x.y);
            val[4 * u + 2] = p3_val(x.z); val[4 * u + 3] = p3_val(x.w);
        }
#pragma unroll
        for (int u = 0; u < 4; u++) ldq128_keep(v[u], ring_ptr(p, pq + off(n)) + u * 512, ready);
        pk = ready ? CFG_PK1 * 128 : ok ? CFG_PK2 * 128 : have ? 15 * 128 : max(pk, CFG_PK3 * 128u);
        pr = ld_rlx((const uint32_t*)ring_ptr(p, pp + off(n + ready) + pk));
        ACC(2, have && !ok)
        have = ready;
        if (!ok) {
            ACC(1, 1)
            fin = ld_rlx(finp);
            if (++guard > GUARD) __trap();
        } else {
#pragma unroll
            for (int u = 0; u < 4; u += 2) {
                uint32_t old[8], chk = 0;
#pragma unroll
                for (int j = 0; j < 4; j++) {
                    old[2 * j] = atoms_add(sb + C_S + row[2 * u + j] * 4, val[4 * u + 2 * j]);
                    old[2 * j + 1] = atoms_add(sb + C_S + ROWS3_MAX * 4 + row[2 * u + j] * 4, val[4 * u + 2 * j + 1]);
                }
#pragma unroll
                for (int j = 0; j < 8; j++) {
                    const uint32_t nw = old[j] + val[4 * u + j];
                    chk |= (old[j] ^ nw) & (val[4 * u + j] ^ nw);
                }
                if (chk & 0x80008000u) {
                    uint32_t tmp[20];
#pragma unroll
                    for (int j = 0; j < 8; j++) { tmp[j >> 1] = row[2 * u + (j >> 1)]; tmp[4 + j] = old[j]; tmp[12 + j] = val[4 * u + j]; }
                    p3_wrap(sb, id, tmp);
                }
            }
            __syncwarp();
            if (last) break;
        }
    }
    ACC_SAVE
}

__device__ __forceinline__ void row_gates(const float* sw, const uint32_t* c2, uint32_t dbits, float4& gs, float4& gr) {
    const uint32_t d2 = dbits * 0x10001u;
    gs = gr = make_float4(0.f, 0.f, 0.f, 0.f);
#pragma unroll
    for (int r2 = 0; r2 < 4; r2++) {
        uint32_t df = sub_bf2(d2, c2[r2]);
        uint32_t ar = mul_bf2(mul_bf2(df, df), 0xC120C120u);
        uint32_t rb = pack_bf2(__expf(bflo(ar)), __expf(bfhi(ar)));
        const float r0 = bflo(rb), r1 = bfhi(rb);
        const float4 s0 = *(const float4*)(sw + r2 * 8), s1 = *(const float4*)(sw + r2 * 8 + 4);
        const float4 q0 = *(const float4*)(sw + 32 + r2 * 8), q1 = *(const float4*)(sw + 32 + r2 * 8 + 4);
        gs.x += r0 * s0.x + r1 * s1.x; gs.y += r0 * s0.y + r1 * s1.y;
        gs.z += r0 * s0.z + r1 * s1.z; gs.w += r0 * s0.w + r1 * s1.w;
        gr.x += r0 * q0.x + r1 * q1.x; gr.y += r0 * q0.y + r1 * q1.y;
        gr.z += r0 * q0.z + r1 * q1.z; gr.w += r0 * q0.w + r1 * q1.w;
    }
}
__device__ __forceinline__ uint2 finish_row(const float* wu, const float4& gs, const float4& gr, const float S[4], uint2 mrow) {
    const float a[4] = {S[0] * gs.x, S[1] * gs.y, S[2] * gs.z, S[3] * gs.w};
    float u[4] = {0, 0, 0, 0};
#pragma unroll
    for (int k = 0; k < 4; k++) {
        u[0] += a[k] * wu[4 * k]; u[1] += a[k] * wu[4 * k + 1]; u[2] += a[k] * wu[4 * k + 2]; u[3] += a[k] * wu[4 * k + 3];
    }
    return make_uint2(pack_bf2(bflo(mrow.x) + u[0] * gr.x, bfhi(mrow.x) + u[1] * gr.y),
                      pack_bf2(bflo(mrow.y) + u[2] * gr.z, bfhi(mrow.y) + u[3] * gr.w));
}
__device__ __forceinline__ void load_tail_weights(const Params& p, float* sw, int tid) {
    if (tid < 32) sw[tid] = __bfloat162float(p.w_sbf[tid]);
    else if (tid < 64) sw[tid] = __bfloat162float(p.w_rbf[tid - 32]);
    else if (tid < 80) sw[tid] = __bfloat162float(p.w_up[tid - 64]);
    else if (tid < 96) sw[tid] = __bfloat162float(p.w_down[tid - 80]);
}
__device__ __forceinline__ float exp_ftz(float x) {
    float r;
    asm("ex2.approx.ftz.f32 %0, %1;" : "=f"(r) : "f"(x * 1.4426950408889634f));
    return r;
}
__device__ __forceinline__ void tail_rows(const Params& p, int tidx, int w, int lane) {
    constexpr uint32_t sb = SB;
    if (w == NW - 1 && lane < 2) {
        fence_gpu();
        red_rlx(rdy_of(p, sb, 320, lane), 1u);
    }
    if (w > NPC * WPP) return;
    const bool dry = w == NPC * WPP;
    const int pc = w / WPP, r0 = pc * RPC + (tidx * WPP + w - pc * WPP) * 8, e0 = r0 * 32;
    const uint32_t G = sb + T_G + w * TWB, M = G + 4096, D = M + 2048;
    if (!dry) {
        cp16z(D + lane * 16, p.dist + e0 + lane * 8, min(max(p.E - e0 - lane * 8, 0), 8) * 2);
#pragma unroll
        for (int k = 0; k < 4; k++) cp16(M + (k * 32 + lane) * 16, p.m + e0 + (k * 32 + lane) * 2, e0 + (k * 32 + lane) * 2 < p.E);
        cp_commit();
    }
    const Scale sc = get_scale(sb);
    const float lsb[4] = {__uint_as_float((sc.eb[0] - 10) << 23), __uint_as_float((sc.eb[1] - 10) << 23),
                          __uint_as_float((sc.eb[2] - 10) << 23), __uint_as_float((sc.eb[3] - 10) << 23)};
    if (!dry) {
        const int g = lane >> 2, t = lane & 3;
        const uint32_t c2 = lds32(sb + SM_CEN + t * 4), wg = sb + SM_W + ((g >> 2) * 32 + t * 8 + (g & 3)) * 4;
        const uint32_t b = prmt(lds32(wg), lds32(wg + 16), 0x7632);
        cp_wait<0>();
        __syncwarp();
        TR(19, w == 0 && lane == 0 && b + c2 != 0x12345);
#pragma unroll 2
        for (int k = 0; k < 16; k++) {
            const uint32_t dv = lds32(D + (k * 8 + g) * 4);
            uint32_t a[2];
#pragma unroll
            for (int h = 0; h < 2; h++) {
                const uint32_t df = sub_bf2(prmt(dv, 0, h ? 0x3232 : 0x1010), c2);
                const uint32_t ar = mul_bf2(mul_bf2(df, df), 0xC120C120u);
                a[h] = pack_bf2(exp_ftz(bflo(ar)), exp_ftz(bfhi(ar)));
            }
            float d[4];
            asm("mma.sync.aligned.m16n8k8.row.col.f32.bf16.bf16.f32 {%0,%1,%2,%3}, {%4,%5}, {%6}, {%7,%7,%7,%7};"
                : "=f"(d[0]), "=f"(d[1]), "=f"(d[2]), "=f"(d[3]) : "r"(a[0]), "r"(a[1]), "r"(b), "f"(0.f));
            const uint32_t at = G + (k * 16 + g * 2) * 16 + t * 4;
            sts32(at, pack_bf2(d[0], d[1]));
            sts32(at + 16, pack_bf2(d[2], d[3]));
        }
    }
    __syncwarp();
    TR(2, w == 0 && lane == 0);
    float wu[16];
#pragma unroll
    for (int k = 0; k < 4; k++) *(uint4*)(wu + 4 * k) = lds128(sb + SM_W + 256 + 16 * k);
    uint32_t dirty = 0;
    {
        const bool pass = !dry;
        if (pass) {
            if (w == pc * WPP && lane < 2) spin_ge(rdy_of(p, sb, lane ? 320 : 160 + 32 * pc, lds32(sb + SM_MISC + 20)), lane ? NTAIL : N3);
            __syncwarp();
            bar_sync(1 + pc, WPP * 32);
            TR(3, w == 0 && lane == 0);
            TR(10, w == NPC * WPP - 1 && lane == 0);
            if (r0 >= (int)p.rows3) return;
        }
        uint4 sv[4] = {};
#pragma unroll
        for (int u = 0; u < 4; u++) ldq128_keep(sv[u], &g_S[0][u * 16 + (lane >> 1)][r0 + (lane & 1) * 4], pass);
        if (pass && lane < 8 && (r0 + lane) * 32 < p.E && (dirty = ld_rlx(g_dirty + r0 + lane))) st_rlx(g_dirty + r0 + lane, 0u);
        dirty = __ballot_sync(0xffffffffu, dirty != 0);
        uint32_t xs[8] = {sv[0].x, sv[0].y, sv[0].z, sv[0].w, sv[1].x, sv[1].y, sv[1].z, sv[1].w};
        uint32_t ys[8] = {sv[2].x, sv[2].y, sv[2].z, sv[2].w, sv[3].x, sv[3].y, sv[3].z, sv[3].w};
        auto finish = [&](int k, uint32_t x, uint32_t y, bool extra) {
            const int i = (lane & 1) * 128 + (lane >> 1) + (k & 3) * 32 + (k >> 2) * 16, e = e0 + i;
            float S[4];
            const uint32_t tx = x + 0x80008000u, ty = y + 0x80008000u;
            S[0] = (__uint_as_float(prmt(tx, 0x4b000000u, 0x7610)) - 8421376.0f) * lsb[0];
            S[1] = (__uint_as_float(prmt(tx, 0x4b000000u, 0x7632)) - 8421376.0f) * lsb[1];
            S[2] = (__uint_as_float(prmt(ty, 0x4b000000u, 0x7610)) - 8421376.0f) * lsb[2];
            S[3] = (__uint_as_float(prmt(ty, 0x4b000000u, 0x7632)) - 8421376.0f) * lsb[3];
            if (extra && e < p.E) {
                const float4 g = __ldcg(g_Sg + e);
                S[0] += g.x; S[1] += g.y; S[2] += g.z; S[3] += g.w;
                __stcg(g_Sg + e, make_float4(0.f, 0.f, 0.f, 0.f));
            }
            const uint4 g = lds128(G + i * 16);
            const uint2 o = finish_row(wu, make_float4(bflo(g.x), bfhi(g.x), bflo(g.y), bfhi(g.y)), make_float4(bflo(g.z), bfhi(g.z), bflo(g.w), bfhi(g.w)), S,
                                       lds64v(M + i * 8));
            asm volatile("{.reg .pred q; setp.ne.u32 q, %3, 0; @q st.global.v2.u32 [%0], {%1,%2};}"
                         ::"l"(p.out + e), "r"(o.x), "r"(o.y), "r"((uint32_t)(pass && e < p.E)));
        };
        if (!dirty) {
#pragma unroll
            for (int k = 0; k < 8; k++) finish(k, xs[k], ys[k], false);
        } else {
#pragma unroll 1
            for (int k = 0; k < 8; k++) {
                finish(k, xs[0], ys[0], dirty >> ((lane & 1) * 4 + (k & 3)) & 1);
#pragma unroll
                for (int j = 0; j < 7; j++) { xs[j] = xs[j + 1]; ys[j] = ys[j + 1]; }
            }
        }
    }
    TR(9, w == 0 && lane == 0);
    TR(11, w == NPC * WPP - 1 && lane == 0);
}

#define CFG_MAP1 1
__global__ void __launch_bounds__(NT, 1) k_main(const __grid_constant__ Params p) {
    extern __shared__ __align__(1024) unsigned char smem[];
    constexpr uint32_t sb = SB;
    if ((uint32_t)__cvta_generic_to_shared(smem) != SB) __trap();
    const int tid = threadIdx.x, w = __shfl_sync(0xffffffffu, tid >> 5, 0), lane = tid & 31;
    if (w < NPROBE) probe(p, sb, w, lane);
    else {
        if (tid == NT - 1) sts32(sb + SM_MISC + 16, ld_rlx(&g_epoch) & 1);
        if (tid >= NT - 32 && lane < 12) sts32(sb + SM_FIN + lane * 4, 0u);
        load_tail_weights(p, (float*)(smem + SM_W), tid - NPROBE * 32);
        if (w == NW - 3 && lane < 4) sts32(sb + SM_CEN + lane * 4, ((const uint32_t*)p.centers)[lane]);
        const int k = blockIdx.x % (NCTA / 2) * 14 + lane;
        if (w == NW - 2 && lane < 14 && k < NT - 32) asm volatile("prefetch.global.L2 [%0];" ::"l"((const uint4*)p.m + k * (p.E / 2 / (NT - 32))));
    }
    cta_sync();
    if (w) {
        const uint4 in = __ldg((const uint4*)p.m + (tid - 32) * (p.E / 2 / (NT - 32)));
        const Mat4 wd = load_mat4(p.w_down, lane);
        for (int i = SM_DATA / 16 + tid - 32; i < ZEND / 16; i += NT - 32) ((uint4*)smem)[i] = make_uint4(0, 0, 0, 0);
        if (tid - 32 < 256) ((uint4*)(smem + SM_ZERO))[tid - 32] = make_uint4(0, 0, 0, 0);
        if (tid < 96) sts32(sb + SM_CNT2 + (tid - 32) * 4, NQ2 << 16);
        __syncwarp();
        if (CFG_PFD && tid == NT - 1) {
            __nanosleep(CFG_PFD);
            const uint32_t n = (p.E / 2 + NCTA - 1) / NCTA, o = blockIdx.x * n;
            if (o < (uint32_t)p.E / 2) asm volatile("cp.async.bulk.prefetch.L2.global [%0], %1;" ::"l"((const uint4*)p.m + o), "r"(min(n, p.E / 2 - o) * 16) : "memory");
        }
        __syncwarp();
        md_stats(in, wd, lane);
    } else assign_role(p, sb, lane);
    if (tid == 0) {
        mbar_init(sb + SM_DONE, lds32(sb + SM_MISC) >> 8 ? P2W : P1W);
        mbar_init(sb + SM_DONE2, NF);
    }
    cta_sync();
    const uint32_t rid = __shfl_sync(0xffffffffu, lds32(sb + SM_MISC), 0);
    const int role = rid >> 8, id = rid & 255;
    TR(5, tid == 0);
    if (role == 0) {
        const int ww = CFG_MAP1 == 0 ? ((w & 3) == 3 ? NW : (w >> 2) * 3 + (w & 3)) : CFG_MAP1 == 1 ? (w & 2 ? NW : (w >> 2) * 2 + (w & 1)) : w;
        const int sw = CFG_MAP1 == 0 ? ((w & 3) == 3 ? w >> 2 : NW) : CFG_MAP1 == 1 ? (w & 2 ? (w >> 2) * 2 + (w & 1) : NW) : w - P1W;
        static_assert(CFG_MAP1 == 0 ? (P1W <= NW / 4 * 3 && NF + 2 <= NW / 4) : CFG_MAP1 == 1 ? (P1W <= NW / 2 && NF + 2 <= NW / 2) : true, "warp map");
        for (int i = tid; i < NF * GPW * 32; i += NT) sts32(sb + A_CNT + i * 4, 1u << 24);
        if (tid < 64) sts32(sb + SM_CRED + tid * 4, 0u);
        cta_sync();
        TR(1, tid == 0);
        if (ww < P1W) role_p1(p, sb, id, ww, lane);
        else if (sw < NF) role_flush(p, sb, id, sw, lane);
        else if (sw == NF) role_credit1(p, sb, id, lane);
        else if (w == NW - 1) {
            uint4* owin = (uint4*)(p.ring + (CWIN + (lds32(sb + SM_MISC + 16) ^ 1)) * WIN);
            for (int i = id * 32 + lane; i < CPAIRS * 512; i += N1 * 32) __stcg(owin + i, make_uint4(0, 0, 0, 0));
            __syncwarp();
        }
    } else if (role == 1) {
        const int row0 = id % H2 * p.rows2;
        const int nrows = min((int)p.rows2, p.E - row0);
        constexpr int NTB = NT - 32, TBD = CFG_TBD;
        bool flagged = false;
        if (w < NW - 1) {
            const uint4* const src = (const uint4*)(p.m + row0);
            uint4 r2[TBD], nx[TBD];
            auto fetch = [&](int i) {
#pragma unroll
                for (int k = 0; k < TBD; k++)
                    asm volatile("ld.global.nc.v4.u32 {%0,%1,%2,%3}, [%4];" : "=r"(nx[k].x), "=r"(nx[k].y), "=r"(nx[k].z), "=r"(nx[k].w) : "l"(src + min(i + k * NTB, nrows / 2 - 1)));
            };
            fetch(tid);
            const Scale sc = get_scale(sb);
            const Mat4 wd = load_mat4(p.w_down, lane);
            const uint32_t slow = sc.allslow ? 0x60006000u : 0u;
            Mat4 ws;
#pragma unroll
            for (int k = 0; k < 4; k++) ws.b[k] = mul_bf2(wd.b[k], ((246u - (lane & 4 ? sc.eb[(k & 2) + 1] : sc.eb[k & 2])) << 7) * 0x10001u);
#pragma unroll 1
            for (int i0 = tid; 2 * (i0 - lane) < nrows; i0 += TBD * NTB) {
#pragma unroll
                for (int k = 0; k < TBD; k++) r2[k] = make_uint4(nx[k].x, nx[k].z, nx[k].y, nx[k].w);
                fetch(i0 + TBD * NTB);
                uint32_t big[2 * TBD], any = slow;
#pragma unroll
                for (int k = 0; k < TBD; k++) {
                    const int i = i0 + k * NTB;
                    float y[8];
                    mul4(make_uint4(r2[k].x, r2[k].z, r2[k].y, r2[k].w), ws, y);
                    uint32_t a[4], h[4], ta[2];
#pragma unroll
                    for (int j = 0; j < 4; j++) { a[j] = pack_h2(y[2 * j], y[2 * j + 1]); h[j] = a[j] + 0x00040004u; }
#pragma unroll
                    for (int j = 0; j < 2; j++) {
                        ta[j] = bitsel(h[2 * j], bitsel(h[2 * j + 1] >> 3, h[2 * j + 1] << 7, 0x00070007u), 0x9ff89ff8u);
                        big[2 * k + j] = a[2 * j] | a[2 * j + 1] | h[2 * j] | h[2 * j + 1];
                    }
                    any |= big[2 * k] | big[2 * k + 1];
                    sts64_if(sb + B_TA + i * 8, ta[0], ta[1], 2 * i < nrows);
                    sts32_if(sb + B_TB + i * 4, prmt(h[1], h[3], 0x7531), 2 * i < nrows);
                }
                if (__any_sync(0xffffffffu, any & 0x60006000u)) {
#pragma unroll
                    for (int k = 0; k < 2 * TBD; k++) {
                        const int r = 2 * (i0 + (k >> 1) * NTB) + (k & 1);
                        if (((big[k] | slow) & 0x60006000u) && r < nrows) { sts32(sb + B_TA + r * 4, 0u); sts16(sb + B_TB + r * 2, 0x40u); }
                    }
                    flagged = true;
                }
            }
            if (tid == 0) {
                sts32(sb + B_TA + p.rows2 * 4, 0u);
                sts16(sb + B_TB + p.rows2 * 2, 0u);
            }
            TR(8, tid == 0);
        } else if (lane == 0) spin_ge(rdy_of(p, sb, id, id / H2), H3);
        __syncwarp();
        flagged = __any_sync(0xffffffffu, __syncthreads_or(flagged));
        TR(1, tid == 0);
        if (w < P2W) {
            if (flagged) role_p2<true>(p, sb, id, w, lane);
            else role_p2<false>(p, sb, id, w, lane);
        } else if (w == P2W) role_credit(p, sb, id, lane);
    } else {
        if (w == 0) clear_queues<false>(p, sb, id, lane);
        if (tid >= 32 && tid < 33 + NPC) mbar_init(sb + SM_DBAR + (tid - 32) * 8, 1);
        cta_sync();
        TR(1, tid == 0);
        if (w < P3W) role_p3(p, sb, id, w, lane);
        const int pc = w - P3W, n = min(((int)p.rows3 + 7) / 8 * 8 - pc * RPC, RPC);
        uint32_t *f0 = nullptr, *f1 = nullptr;
        if (pc >= 0) { f0 = opaque(rdy_of(p, sb, 160 + 32 * pc, 0)); f1 = opaque(rdy_of(p, sb, 160 + 32 * pc, 1)); }
        cta_sync();
        TR(2, tid == 0);
        if (pc >= 0 && pc < NPC && lane == 0) {
            fence_async_smem();
            if (pc >= CFG_DOUT) mbar_wait(sb + SM_DBAR + (pc + 1 - CFG_DOUT) * 8, 0);
            if (n > 0) {
                bulk_store(g_S[0][id] + pc * RPC, sb + C_S + pc * RPC * 4, n * 4);
                bulk_store(g_S[1][id] + pc * RPC, sb + C_S + (ROWS3_MAX + pc * RPC) * 4, n * 4);
            }
            asm volatile("cp.async.bulk.commit_group;" ::: "memory");
            asm volatile("cp.async.bulk.wait_group.read 0;" ::: "memory");
            mbar_arrive(sb + SM_DBAR + pc * 8 + 8);
            asm volatile("cp.async.bulk.wait_group 0;" ::: "memory");
            fence_gpu();
            red_rlx(f0, 1u);
            red_rlx(f1, 1u);
            if (id == 0 && pc == 0) red_rlx(&g_epoch, 1u);
            TR(12 + pc, true);
        }
        return;
    }
    cta_sync();
    TR(18, tid == 0 && role == 1);
    if (role == 0 && w == NW - 2) clear_queues<true>(p, sb, id, lane);
    tail_rows(p, role * N1 + id, w, lane);
}

__global__ void k_direct(const Params p, long long T) {
    float wd[16];
#pragma unroll
    for (int i = 0; i < 16; i++) wd[i] = __bfloat162float(p.w_down[i]);
    const float f = __bfloat162float(p.freq[0]);
    for (long long t = blockIdx.x * (long long)blockDim.x + threadIdx.x; t < T; t += (long long)gridDim.x * blockDim.x) {
        float x = __bfloat162float(__float2bfloat16(f * __bfloat162float(p.angle[t])));
        float c = __bfloat162float(__float2bfloat16(cosf(x)));
        uint2 md = down_row(__ldg(p.m + p.idx_in[t]), wd);
        red_v4(g_Sg + p.idx_out[t], c * bflo(md.x), c * bfhi(md.x), c * bflo(md.y), c * bfhi(md.y));
    }
}
__global__ void k_direct_tail(const Params p) {
    __shared__ __align__(16) float sw[96];
    load_tail_weights(p, sw, threadIdx.x);
    __syncthreads();
    uint32_t c2[4];
#pragma unroll
    for (int i = 0; i < 4; i++) c2[i] = ((const uint32_t*)p.centers)[i];
    for (int e = blockIdx.x * blockDim.x + threadIdx.x; e < p.E; e += gridDim.x * blockDim.x) {
        float4 g = __ldcg(g_Sg + e);
        __stcg(g_Sg + e, make_float4(0.f, 0.f, 0.f, 0.f));
        const float Sv[4] = {g.x, g.y, g.z, g.w};
        float4 gs, gr;
        row_gates(sw, c2, __bfloat16_as_ushort(p.dist[e]), gs, gr);
        p.out[e] = finish_row(sw + 64, gs, gr, Sv, __ldg(p.m + e));
    }
}

static bool pick_rows(int E, int n, int rows_max, int mult, uint32_t* rows, uint32_t* magic) {
    for (uint32_t r = (E + n - 1) / n; r <= (uint32_t)rows_max; r++) {
        if (r < 2 || r % mult) continue;
        uint64_t mg = ((1ull << 32) + r - 1) / r;
        uint64_t err = mg * r - (1ull << 32);
        if (err * (uint64_t)n < mg) { *rows = r; *magic = (uint32_t)mg; return true; }
    }
    return false;
}

}

extern "C" void kernel_launch(void* const* d_in, const int* in_sizes, int n_in, void* d_out, int out_size) {
    using namespace gs;
    (void)n_in; (void)out_size;
    Params p;
    p.m = (const uint2*)d_in[0];
    p.idx_in = (const int*)d_in[1];
    p.idx_out = (const int*)d_in[2];
    p.dist = (const __nv_bfloat16*)d_in[3];
    p.angle = (const __nv_bfloat16*)d_in[4];
    p.centers = (const __nv_bfloat16*)d_in[5];
    p.freq = (const __nv_bfloat16*)d_in[6];
    p.w_rbf = (const __nv_bfloat16*)d_in[7];
    p.w_sbf = (const __nv_bfloat16*)d_in[8];
    p.w_down = (const __nv_bfloat16*)d_in[9];
    p.w_up = (const __nv_bfloat16*)d_in[10];
    p.out = (uint2*)d_out;
    p.E = in_sizes[3];
    const long long T = in_sizes[1];
    p.n4 = (int)(T / 4);
    p.rows2 = p.magic2 = 0;
    p.ring = nullptr;

    static int sms = 0, rsv = 0;
    if (!sms) {
        int dev = 0;
        cudaGetDevice(&dev);
        cudaDeviceGetAttribute(&rsv, cudaDevAttrReservedSharedMemoryPerBlock, dev);
        cudaDeviceGetAttribute(&sms, cudaDevAttrMultiProcessorCount, dev);
        cudaFuncSetAttribute(k_main, cudaFuncAttributeMaxDynamicSharedMemorySize, SMEM_BYTES);
    }
    cudaStream_t st = cudaStreamPerThread;
    bool fast = (T % 4 == 0) && T > 0 && sms >= NCTA && rsv == (int)SB && p.E >= 65536 && p.E <= E_MAX &&
                p.E % 4 == 0 && (((uintptr_t)p.m | (uintptr_t)p.idx_in | (uintptr_t)p.idx_out | (uintptr_t)p.angle) & 15) == 0 &&
                pick_rows(p.E, NI, ROWS2_MAX, 2, &p.rows2, &p.magic2);
    p.nrows2 = 0u - p.rows2;
    p.rows3 = (p.E + 31) / 32;
    fast = fast && (p.rows2 * (NI - 1) + 2 <= (uint32_t)p.E);
    static const void* tkey[3] = {nullptr, nullptr, nullptr};
    static cudaTextureObject_t tex[3] = {0, 0, 0};
    static long long tlen = -1;
    const void* tptr[3] = {p.idx_in, p.idx_out, p.angle};
    for (int k = 0; fast && k < 3; k++) {
        if (tkey[k] == tptr[k] && tlen == T) continue;
        if (tkey[k]) cudaDestroyTextureObject(tex[k]);
        tkey[k] = nullptr;
        cudaResourceDesc rd = {};
        rd.resType = cudaResourceTypeLinear;
        rd.res.linear.devPtr = (void*)tptr[k];
        rd.res.linear.desc = cudaCreateChannelDesc(32, 32, k < 2 ? 32 : 0, k < 2 ? 32 : 0, cudaChannelFormatKindUnsigned);
        rd.res.linear.sizeInBytes = (size_t)T * (k < 2 ? 4 : 2);
        cudaTextureDesc td = {};
        td.readMode = cudaReadModeElementType;
        if (cudaCreateTextureObject(&tex[k], &rd, &td, nullptr) == cudaSuccess) tkey[k] = tptr[k];
        else { (void)cudaGetLastError(); fast = false; }
    }
    if (fast) tlen = T;
    p.t_in = tex[0]; p.t_out = tex[1]; p.t_ang = tex[2];
    if (fast) {
        void* ring = nullptr;
        cudaGetSymbolAddress(&ring, g_ring);
        uintptr_t a = ((uintptr_t)ring + WIN - 1) & ~(uintptr_t)(WIN - 1);
        if (a >> 32 != (a + RING_BYTES - 1) >> 32) a += RING_BYTES;
        p.ring = (unsigned char*)a;
        p.ring_lo = (uint32_t)a;
        p.ring_hi = (uint32_t)(a >> 32);
        k_main<<<NCTA, NT, SMEM_BYTES, st>>>(p);
    } else {
        k_direct<<<sms * 8, 256, 0, st>>>(p, T);
        k_direct_tail<<<sms * 4, 256, 0, st>>>(p);
    }
}
```

```cpp
#include <cuda_runtime.h>
#include <cuda_bf16.h>
#include <stdint.h>

#define CFG_N1 56
#define CFG_NI 22
#define CFG_NW 28
#define CFG_P1W 14
#define CFG_GPW 2
#define CFG_KR 1
#define CFG_QPW 3
#define CFG_TG 2
#define CFG_PMASK 8
#define CFG_PSTREAK 1
#define CFG_NBT 1
#define CFG_KM 5
#define CFG_KN 9
#define CFG_TBD 3
#define CFG_P0 500
#define CFG_PFD 200
#define CFG_C1SLEEP 200
#define CFG_PK1 6
#define CFG_PK2 8
#define CFG_PK3 11
#define CFG_DOUT 2
#define CFG_TH 14
#define CFG_TS 200
#define CFG_POLL 64
#define CFG_HINT 20000
#define CFG_BSLEEP 100
#define CFG_CSLEEP 400
#define CFG_FSLEEP 100
#define CFG_PSLEEP 100
#define CFG_PROBES 4

namespace gs {

constexpr int E_MAX = 640000;
constexpr int N1 = CFG_N1, NI = CFG_NI, N2 = 2 * NI, N3 = 32, NCTA = N1 + N2 + N3;
constexpr int H2 = NI, H3 = N3 / 2;
constexpr int NB = NI * N3;
constexpr int NW = CFG_NW, NT = NW * 32;
constexpr int GPW = CFG_GPW, NF = (NI + GPW - 1) / GPW;
constexpr int QPW = CFG_QPW, NBT = CFG_NBT;
constexpr int P1W = CFG_P1W, P2W = (N1 + QPW - 1) / QPW, P3W = NI;
constexpr int NQ2 = 64;
constexpr int ROWS2_MAX = ((E_MAX + NI - 1) / NI + 31) / 8 * 8;
constexpr int ROWS3_MAX = (E_MAX / 32 + 31) / 32 * 32;
constexpr int NTAIL = N1 + N2;
constexpr int NPC = 5, WPP = 5, RPC = NTAIL * WPP * 8;
constexpr int GUARD = 1 << 26;
static_assert(NCTA % 4 == 0 && NCTA <= 192, "roles come in CTA pairs, per partition");
static_assert((GPW == 2 || GPW == 4) && QPW >= NBT && QPW <= 4 && NI <= 32 && N1 <= 62, "queue ownership");
static_assert(P1W + NF + 2 <= NW && P2W + 2 <= NW && P3W + 5 <= NW && P1W * 256 + 64 < 8192, "warp roles");
static_assert(ROWS2_MAX + 8 <= 32768 && ROWS3_MAX <= 32768, "index bits");

constexpr uint32_t SB = 1024;
constexpr int SM_DONE = 0, SM_DONE2 = 8;
constexpr int SM_MISC = 16;
constexpr int SM_FIN = 48;
constexpr int SM_STAT = 64;
constexpr int SM_CEN = 112;
constexpr int SM_DBAR = 128;
constexpr int SM_W = 256;
constexpr int SM_PUB = SM_W + 384;
constexpr int SM_PROBE = SM_PUB + 768;
constexpr int SM_CRED = 1792;
constexpr int SM_CNT2 = SM_CRED;
constexpr int SM_DATA = 2048;
constexpr int cmax(int a, int b) { return a > b ? a : b; }
constexpr int A_CNT = SM_DATA;
constexpr int KR = CFG_KR, LISTB = (GPW * 32 + 8 * KR) * 4;
constexpr int A_LIST = A_CNT + NF * GPW * 128;
constexpr int A_ST = (A_LIST + NF * LISTB + 127) / 128 * 128;
constexpr int A_END = A_ST + NB * 256;
constexpr int B_TB = SM_DATA;
constexpr int B_TA = SM_DATA + (ROWS2_MAX + 8) * 2;
constexpr int B_END = SM_DATA + (ROWS2_MAX + 8) * 6;
constexpr int C_S = SM_DATA;
constexpr int C_END = C_S + ROWS3_MAX * 8;
constexpr int T_G = SM_DATA, TWB = 4096 + 2048 + 512, T_END = T_G + NPC * WPP * TWB;
constexpr int ZEND = cmax(A_END, C_END);
constexpr int SM_ZERO = (cmax(C_END, T_END) + 127) / 128 * 128;
constexpr int SMEM_BYTES = cmax(cmax(A_END, B_END), SM_ZERO + 4096);
static_assert(SMEM_BYTES <= 232448 && SM_PROBE + 128 <= SM_CRED, "shared memory");
static_assert(NPC * RPC >= ROWS3_MAX && NPC * WPP + 3 <= NW, "tail");

constexpr uint32_t FIN = 0x80000000u;

constexpr uint32_t WIN = 524288;
constexpr int CWIN = N2 + N3, NWIN = CWIN + 2, CPAIRS = 31;
constexpr uint32_t PROBE_OFF = (uint32_t)NWIN * WIN;
constexpr int NPROBE = 16;
static_assert(NWIN <= NCTA && NPROBE <= NW, "windows");
constexpr size_t RING_BYTES = (size_t)PROBE_OFF + WIN;
__device__ __align__(128) unsigned char g_ring[2 * RING_BYTES + WIN];
__device__ __align__(128) uint32_t g_S[2][32][ROWS3_MAX];
__device__ __align__(128) float4 g_Sg[E_MAX];
__device__ uint32_t g_dirty[E_MAX / 32];
__device__ uint32_t g_epoch;

#define TR(ev, on)
#define ACC_DECL
#define ACC(i, n)
#define ACC_SAVE

struct Params {
    const uint2* m;
    const int* idx_in;
    const int* idx_out;
    const __nv_bfloat16* dist;
    const __nv_bfloat16* angle;
    const __nv_bfloat16* centers;
    const __nv_bfloat16* freq;
    const __nv_bfloat16* w_rbf;
    const __nv_bfloat16* w_sbf;
    const __nv_bfloat16* w_down;
    const __nv_bfloat16* w_up;
    uint2* out;
    unsigned char* ring;
    cudaTextureObject_t t_in, t_out, t_ang;
    int E, n4;
    uint32_t rows2, nrows2, magic2, rows3;
    uint32_t ring_lo, ring_hi;
};

__device__ __forceinline__ float bflo(uint32_t w) { return __uint_as_float(w << 16); }
__device__ __forceinline__ float bfhi(uint32_t w) { return __uint_as_float(w & 0xffff0000u); }
__device__ __forceinline__ uint32_t pack_bf2(float lo, float hi) {
    uint32_t r;
    asm("cvt.rn.bf16x2.f32 %0, %1, %2;" : "=r"(r) : "f"(hi), "f"(lo));
    return r;
}
__device__ __forceinline__ uint32_t mul_bf2(uint32_t a, uint32_t b) {
    uint32_t r;
    asm("mul.rn.bf16x2 %0, %1, %2;" : "=r"(r) : "r"(a), "r"(b));
    return r;
}
__device__ __forceinline__ uint32_t sub_bf2(uint32_t a, uint32_t b) {
    uint32_t r;
    asm("sub.rn.bf16x2 %0, %1, %2;" : "=r"(r) : "r"(a), "r"(b));
    return r;
}
__device__ __forceinline__ uint32_t maxabs_bf2(uint32_t a, uint32_t b) {
    uint32_t r;
    asm("max.NaN.xorsign.abs.bf16x2 %0, %1, %2;" : "=r"(r) : "r"(a), "r"(b));
    return r;
}
__device__ __forceinline__ void mbar_init(uint32_t a, uint32_t n) {
    asm volatile("mbarrier.init.shared::cta.b64 [%0], %1;" ::"r"(a), "r"(n) : "memory");
}
__device__ __forceinline__ void mbar_arrive(uint32_t a) {
    asm volatile("mbarrier.arrive.shared::cta.b64 _, [%0];" ::"r"(a) : "memory");
}
__device__ __forceinline__ void mbar_arrive_if(uint32_t a, bool on) {
    asm volatile("{.reg .pred q; setp.ne.u32 q, %1, 0; @q mbarrier.arrive.shared::cta.b64 _, [%0];}" ::"r"(a), "r"((uint32_t)on) : "memory");
}
__device__ __forceinline__ void mbar_wait(uint32_t a, uint32_t parity) {
    uint32_t ok;
    int guard = 0;
    do {
        asm volatile("{.reg .pred p; mbarrier.try_wait.parity.shared::cta.b64 p, [%1], %2, %3; selp.u32 %0, 1, 0, p;}"
                     : "=r"(ok) : "r"(a), "r"(parity), "r"(CFG_HINT) : "memory");
        if (!ok) {
            if (++guard > GUARD) __trap();
        }
    } while (!ok);
}
__device__ __forceinline__ void cta_sync() { __syncwarp(); __syncthreads(); }
__device__ __forceinline__ void bar_sync(int id, int n) { asm volatile("bar.sync %0, %1;" ::"r"(id), "r"(n) : "memory"); }
__device__ __forceinline__ bool mbar_test(uint32_t a, uint32_t parity) {
    uint32_t ok;
    asm volatile("{.reg .pred p; mbarrier.test_wait.parity.shared::cta.b64 p, [%1], %2; selp.u32 %0, 1, 0, p;}"
                 : "=r"(ok) : "r"(a), "r"(parity) : "memory");
    return ok;
}
__device__ __forceinline__ uint32_t ld_acq(const uint32_t* p) {
    uint32_t v;
    asm volatile("ld.acquire.gpu.global.u32 %0, [%1];" : "=r"(v) : "l"(p) : "memory");
    return v;
}
__device__ __forceinline__ uint32_t ld_rlx(const uint32_t* p) {
    uint32_t v;
    asm volatile("ld.relaxed.gpu.global.u32 %0, [%1];" : "=r"(v) : "l"(p) : "memory");
    return v;
}
__device__ __forceinline__ void st_rlx(uint32_t* p, uint32_t v) {
    asm volatile("st.relaxed.gpu.global.u32 [%0], %1;" ::"l"(p), "r"(v) : "memory");
}
__device__ __forceinline__ void red_rlx(uint32_t* p, uint32_t v) {
    asm volatile("red.relaxed.gpu.global.add.u32 [%0], %1;" ::"l"(p), "r"(v) : "memory");
}
__device__ __forceinline__ uint32_t spin_ge(const uint32_t* p, uint32_t target) {
    int guard = 0;
    while (ld_rlx(p) < target) {
        __nanosleep(CFG_POLL);
        if (++guard > GUARD) __trap();
    }
    return ld_acq(p);
}
__device__ __forceinline__ void fence_gpu() { asm volatile("fence.acq_rel.gpu;" ::: "memory"); }
__device__ __forceinline__ void fence_async_smem() { asm volatile("fence.proxy.async.shared::cta;" ::: "memory"); }
__device__ __forceinline__ void fence_async_all() { asm volatile("fence.proxy.async;" ::: "memory"); }
__device__ __forceinline__ void bulk_store(void* g, uint32_t s, uint32_t bytes) {
    asm volatile("cp.async.bulk.global.shared::cta.bulk_group [%0], [%1], %2;" ::"l"(g), "r"(s), "r"(bytes) : "memory");
}
__device__ __forceinline__ void cp16(uint32_t s, const void* g, bool on) {
    asm volatile("{.reg .pred q; setp.ne.u32 q, %2, 0; @q cp.async.cg.shared.global [%0], [%1], 16;}" ::"r"(s), "l"(g), "r"((uint32_t)on) : "memory");
}
__device__ __forceinline__ void cp16z(uint32_t s, const void* g, int bytes) {
    asm volatile("cp.async.cg.shared.global [%0], [%1], 16, %2;" ::"r"(s), "l"(g), "r"(bytes) : "memory");
}
__device__ __forceinline__ void cp_commit() { asm volatile("cp.async.commit_group;" ::: "memory"); }
template <int N> __device__ __forceinline__ void cp_wait() { asm volatile("cp.async.wait_group %0;" ::"n"(N) : "memory"); }
__device__ __forceinline__ uint32_t atoms_add(uint32_t a, uint32_t v) {
    uint32_t o;
    asm volatile("atom.shared.add.u32 %0, [%1], %2;" : "=r"(o) : "r"(a), "r"(v) : "memory");
    return o;
}
__device__ __forceinline__ void sts32(uint32_t a, uint32_t v) { asm volatile("st.shared.u32 [%0], %1;" ::"r"(a), "r"(v) : "memory"); }
__device__ __forceinline__ void sts16(uint32_t a, uint32_t v) { asm volatile("st.shared.u16 [%0], %1;" ::"r"(a), "h"((uint16_t)v) : "memory"); }
__device__ __forceinline__ void sts64(uint32_t a, uint32_t x, uint32_t y) { asm volatile("st.shared.v2.u32 [%0], {%1,%2};" ::"r"(a), "r"(x), "r"(y) : "memory"); }
__device__ __forceinline__ uint32_t lds32(uint32_t a) {
    uint32_t v;
    asm volatile("ld.shared.u32 %0, [%1];" : "=r"(v) : "r"(a) : "memory");
    return v;
}
__device__ __forceinline__ uint2 lds64v(uint32_t a) {
    uint2 v;
    asm volatile("ld.volatile.shared.v2.u32 {%0,%1}, [%2];" : "=r"(v.x), "=r"(v.y) : "r"(a) : "memory");
    return v;
}
__device__ __forceinline__ uint32_t lds32v(uint32_t a) {
    uint32_t v;
    asm volatile("ld.volatile.shared.u32 %0, [%1];" : "=r"(v) : "r"(a) : "memory");
    return v;
}
__device__ __forceinline__ uint4 lds128(uint32_t a) {
    uint4 v;
    asm volatile("ld.shared.v4.u32 {%0,%1,%2,%3}, [%4];" : "=r"(v.x), "=r"(v.y), "=r"(v.z), "=r"(v.w) : "r"(a) : "memory");
    return v;
}
__device__ __forceinline__ void sts128(uint32_t a, uint4 v) {
    asm volatile("st.shared.v4.u32 [%0], {%1,%2,%3,%4};" ::"r"(a), "r"(v.x), "r"(v.y), "r"(v.z), "r"(v.w) : "memory");
}
#define LD_Q "ld.relaxed.gpu.global"
__device__ __forceinline__ uint4 ldg_q128(const void* p) {
    uint4 v;
    asm volatile(LD_Q ".v4.u32 {%0,%1,%2,%3}, [%4];"
                 : "=r"(v.x), "=r"(v.y), "=r"(v.z), "=r"(v.w) : "l"(p) : "memory");
    return v;
}
__device__ __forceinline__ uint2 ldg_q64(const void* p) {
    uint2 v;
    asm volatile(LD_Q ".v2.u32 {%0,%1}, [%2];" : "=r"(v.x), "=r"(v.y) : "l"(p) : "memory");
    return v;
}
__device__ __forceinline__ void red_v4(float4* p, float a, float b, float c, float d) {
    asm volatile("red.global.add.v4.f32 [%0], {%1,%2,%3,%4};" ::"l"(p), "f"(a), "f"(b), "f"(c), "f"(d) : "memory");
}
__device__ __forceinline__ uint2 down_row(uint2 r, const float* wd) {
    float x0 = bflo(r.x), x1 = bfhi(r.x), x2 = bflo(r.y), x3 = bfhi(r.y);
    float y[4];
#pragma unroll
    for (int j = 0; j < 4; j++) y[j] = x0 * wd[j] + x1 * wd[4 + j] + x2 * wd[8 + j] + x3 * wd[12 + j];
    return make_uint2(pack_bf2(y[0], y[1]), pack_bf2(y[2], y[3]));
}
__device__ __forceinline__ uint32_t prmt(uint32_t a, uint32_t b, uint32_t s) {
    uint32_t r;
    asm("prmt.b32 %0, %1, %2, %3;" : "=r"(r) : "r"(a), "r"(b), "r"(s));
    return r;
}
__device__ __forceinline__ uint32_t bitsel(uint32_t a, uint32_t b, uint32_t m) {
    uint32_t r;
    asm("lop3.b32 %0, %1, %2, %3, 0xE4;" : "=r"(r) : "r"(a), "r"(b), "r"(m));
    return r;
}
__device__ __forceinline__ uint32_t pack_h2(float lo, float hi) {
    uint32_t r;
    asm("cvt.rn.f16x2.f32 %0, %1, %2;" : "=r"(r) : "f"(hi), "f"(lo));
    return r;
}
__device__ __forceinline__ uint32_t mul_h2(uint32_t a, uint32_t b) {
    uint32_t r;
    asm("mul.rn.f16x2 %0, %1, %2;" : "=r"(r) : "r"(a), "r"(b));
    return r;
}
__device__ __forceinline__ uint32_t lds32nv(uint32_t a) {
    uint32_t v;
    asm volatile("ld.shared.u32 %0, [%1];" : "=r"(v) : "r"(a));
    return v;
}
__device__ __forceinline__ uint32_t lds16nv(uint32_t a) {
    uint32_t v;
    asm volatile("ld.shared.u16 %0, [%1];" : "=r"(v) : "r"(a));
    return v;
}
#define ST_Q "st.relaxed.gpu.global"
__device__ __forceinline__ void stg_q128(void* p, uint32_t a, uint32_t b, uint32_t c, uint32_t d, bool on) {
    asm volatile("{.reg .pred q; setp.ne.u32 q, %5, 0; @q " ST_Q ".v4.u32 [%0], {%1,%2,%3,%4};}"
                 ::"l"(p), "r"(a), "r"(b), "r"(c), "r"(d), "r"((uint32_t)on) : "memory");
}
__device__ __forceinline__ void stg_q64(void* p, uint32_t a, uint32_t b, bool on) {
    asm volatile("{.reg .pred q; setp.ne.u32 q, %3, 0; @q " ST_Q ".v2.u32 [%0], {%1,%2};}"
                 ::"l"(p), "r"(a), "r"(b), "r"((uint32_t)on) : "memory");
}
__device__ __forceinline__ void st_rlx_if(uint32_t* p, uint32_t v, bool on) {
    asm volatile("{.reg .pred q; setp.ne.u32 q, %2, 0; @q st.relaxed.gpu.global.u32 [%0], %1;}" ::"l"(p), "r"(v), "r"((uint32_t)on) : "memory");
}
__device__ __forceinline__ void ldq128_keep(uint4& v, const void* p, bool on) {
    asm volatile("{.reg .pred q; setp.ne.u32 q, %5, 0; @q ld.relaxed.gpu.global.v4.u32 {%0,%1,%2,%3}, [%4];}"
                 : "+r"(v.x), "+r"(v.y), "+r"(v.z), "+r"(v.w) : "l"(p), "r"((uint32_t)on) : "memory");
}
__device__ __forceinline__ void reds_add(uint32_t a, uint32_t v) { asm volatile("red.shared.add.u32 [%0], %1;" ::"r"(a), "r"(v) : "memory"); }
__device__ __forceinline__ void sts32_if(uint32_t a, uint32_t v, bool on) {
    asm volatile("{.reg .pred q; setp.ne.u32 q, %2, 0; @q st.shared.u32 [%0], %1;}" ::"r"(a), "r"(v), "r"((uint32_t)on) : "memory");
}
__device__ __forceinline__ void sts64_if(uint32_t a, uint32_t x, uint32_t y, bool on) {
    asm volatile("{.reg .pred q; setp.ne.u32 q, %3, 0; @q st.shared.v2.u32 [%0], {%1,%2};}" ::"r"(a), "r"(x), "r"(y), "r"((uint32_t)on) : "memory");
}
__device__ __forceinline__ void lds128_keep(uint4& v, uint32_t a, bool on) {
    asm volatile("{.reg .pred q; setp.ne.u32 q, %5, 0; @q ld.volatile.shared.v4.u32 {%0,%1,%2,%3}, [%4];}"
                 : "+r"(v.x), "+r"(v.y), "+r"(v.z), "+r"(v.w) : "r"(a), "r"((uint32_t)on) : "memory");
}
__device__ __forceinline__ void or3_if(uint32_t& x, uint32_t a, uint32_t b, bool on) {
    asm("{.reg .pred q; setp.ne.u32 q, %3, 0; @q lop3.b32 %0, %0, %1, %2, 0xfe;}" : "+r"(x) : "r"(a), "r"(b), "r"((uint32_t)on));
}
__device__ __forceinline__ uint32_t clk() {
    uint32_t t;
    asm volatile("mov.u32 %0, %%clock;" : "=r"(t) :: "memory");
    return t;
}
__device__ __forceinline__ void sg_add(int row, float a, float b, float c, float d) {
    red_v4(g_Sg + row, a, b, c, d);
    st_rlx(g_dirty + (row >> 5), 1u);
}
__device__ __forceinline__ void slow_add(const uint2* m, uint32_t sb, int in, int out, float c) {
    const uint2 r = __ldg(m + in);
    const float x[4] = {bflo(r.x), bfhi(r.x), bflo(r.y), bfhi(r.y)};
    float y[4] = {0.f, 0.f, 0.f, 0.f};
#pragma unroll
    for (int k = 0; k < 4; k++) {
        const uint4 q = lds128(sb + SM_W + 320 + k * 16);
        y[0] = k ? y[0] + x[k] * __uint_as_float(q.x) : x[k] * __uint_as_float(q.x);
        y[1] = k ? y[1] + x[k] * __uint_as_float(q.y) : x[k] * __uint_as_float(q.y);
        y[2] = k ? y[2] + x[k] * __uint_as_float(q.z) : x[k] * __uint_as_float(q.z);
        y[3] = k ? y[3] + x[k] * __uint_as_float(q.w) : x[k] * __uint_as_float(q.w);
    }
    const uint32_t lo = pack_bf2(y[0], y[1]), hi = pack_bf2(y[2], y[3]);
    sg_add(out, c * bflo(lo), c * bfhi(lo), c * bflo(hi), c * bfhi(hi));
}

struct Mat4 { uint32_t b[4]; };
__device__ __forceinline__ Mat4 load_mat4(const __nv_bfloat16* w, int lane) {
    const unsigned short* u = (const unsigned short*)w + (lane >> 2 & 1);
    const bool on = lane >> 3 == (lane & 3);
    Mat4 m;
#pragma unroll
    for (int k = 0; k < 4; k++) m.b[k] = on ? u[(k & 1) * 8 + (k & 2)] | (uint32_t)u[(k & 1) * 8 + 4 + (k & 2)] << 16 : 0u;
    return m;
}
__device__ __forceinline__ void mul4(const uint4& x, const Mat4& m, float (&y)[8]) {
    asm("mma.sync.aligned.m16n8k16.row.col.f32.bf16.bf16.f32 {%0,%1,%2,%3}, {%8,%9,%10,%11}, {%12,%13}, {%16,%16,%16,%16};\n\t"
        "mma.sync.aligned.m16n8k16.row.col.f32.bf16.bf16.f32 {%4,%5,%6,%7}, {%8,%9,%10,%11}, {%14,%15}, {%16,%16,%16,%16};"
        : "=&f"(y[0]), "=&f"(y[1]), "=&f"(y[4]), "=&f"(y[5]), "=&f"(y[2]), "=&f"(y[3]), "=&f"(y[6]), "=&f"(y[7])
        : "r"(x.x), "r"(x.z), "r"(x.y), "r"(x.w), "r"(m.b[0]), "r"(m.b[1]), "r"(m.b[2]), "r"(m.b[3]), "f"(0.f));
}

struct Scale { uint32_t eb[4]; bool allslow; };
__device__ __forceinline__ void md_stats(const uint4& in, const Mat4& wd, int lane) {
    float y[8];
    mul4(in, wd, y);
    uint32_t mx[4], se[4];
#pragma unroll
    for (int c = 0; c < 4; c++) {
        uint32_t a = __float_as_uint(y[c]) & 0x7fffffffu, b = __float_as_uint(y[4 + c]) & 0x7fffffffu;
        if (a >= 0x7f800000u) a = 0;
        if (b >= 0x7f800000u) b = 0;
        mx[c] = __reduce_max_sync(0xffffffffu, max(a, b));
        se[c] = __reduce_add_sync(0xffffffffu, (a >> 23) + (b >> 23) + (a ? 1u << 20 : 0u) + (b ? 1u << 20 : 0u));
    }
    if (lane < 4) {
        asm volatile("red.shared.max.u32 [%0], %1;" ::"r"(SB + SM_STAT + lane * 4), "r"(lane == 0 ? mx[0] : lane == 1 ? mx[1] : lane == 2 ? mx[2] : mx[3]) : "memory");
        reds_add(SB + SM_STAT + 16 + lane * 4, lane == 0 ? se[0] : lane == 1 ? se[1] : lane == 2 ? se[2] : se[3]);
    }
}
__device__ __forceinline__ Scale get_scale(uint32_t sb) {
    Scale s;
    s.allslow = false;
#pragma unroll
    for (int k = 0; k < 4; k++) {
        const uint32_t mx = lds32(sb + SM_STAT + 4 * k), se = lds32(sb + SM_STAT + 16 + 4 * k);
        const uint32_t mean = (uint32_t)__fdividef((float)(se & 0xfffffu), (float)max(se >> 20, 1u));
        uint32_t eb = min(min((mx + 0x6e0000u) >> 23, mean + 5u), 227u);
        if (eb < 27u) { s.allslow = s.allslow || mx != 0; eb = 27u; }
        if (eb > 170u) s.allslow = true;
        s.eb[k] = eb;
    }
    return s;
}

__device__ __forceinline__ uint32_t probe_rt(uint32_t* p) {
    uint32_t best = 0xffffffffu;
#pragma unroll 1
    for (int r = 0; r < CFG_PROBES; r++) {
        const uint32_t t0 = clock();
        uint32_t v;
        asm volatile("atom.relaxed.gpu.global.add.u32 %0, [%1], 1;" : "=r"(v) : "l"(p) : "memory");
        if (v > 100000u) __trap();
        const uint32_t t1 = clock();
        best = min(best, t1 - t0);
    }
    return best;
}
__device__ __forceinline__ uint32_t* pub_ptr(const Params& p, int blk, uint32_t sel) {
    const int pr = blk / 44;
    return (uint32_t*)(p.ring + PROBE_OFF + (pr ? 4096u << pr : 0u) + (sel << 12) + 2176 + (blk - pr * 44) * 32);
}
__device__ __forceinline__ void probe(const Params& p, uint32_t sb, int w, int lane) {
    const int blk = blockIdx.x, pr = w >> 1;
    uint32_t off = PROBE_OFF + blk * 16 + (pr ? 4096u << pr : 0u);
    if (pr == 7) off = blk < NWIN ? blk * WIN + 4064 : PROBE_OFF + 3584 + blk % 16 * 32;
    off += (w & 1) * 4096;
    if (lane < 8) st_rlx((uint32_t*)(p.ring + (off & ~31u)) + lane, 0u);
    if (lane == 0) sts32(sb + SM_PROBE + w * 4, probe_rt((uint32_t*)(p.ring + off)));
}
__device__ __forceinline__ void assign_role(const Params& p, uint32_t sb, int lane) {
    {
        const bool x = lane < 8 && lds32(sb + SM_PROBE + lane * 8 + 4) < lds32(sb + SM_PROBE + lane * 8);
        const uint32_t near = __ballot_sync(0xffffffffu, x), bits = near & 1 ? ~near | 1u : near;
        const uint32_t tag = (lds32(sb + SM_MISC + 16) + 1) << 30;
        if (lane < 16) st_rlx(pub_ptr(p, blockIdx.x, lane >> 3) + (lane & 7), tag | (bits & 0xffu));
        constexpr int K = (NCTA + 31) / 32;
        __nanosleep(CFG_P0);
        uint32_t v[K], bad;
        int guard = 0;
        do {
            bad = 0;
#pragma unroll
            for (int k = 0; k < K; k++) {
                const int b = min(lane + 32 * k, NCTA - 1);
                v[k] = ld_rlx(pub_ptr(p, b, near >> (b / 44) & 1));
                bad |= v[k] ^ tag;
            }
            bad = __any_sync(0xffffffffu, bad >> 30);
            if (bad) __nanosleep(CFG_PSLEEP);
            if (++guard > GUARD) __trap();
        } while (bad);
#pragma unroll
        for (int k = 0; k < K; k++) sts32(sb + SM_PUB + (lane + 32 * k) * 4, v[k]);
    }
    __syncwarp();
    constexpr int NP = NCTA / 2, NTAB = H2 + H3;
    const int me = blockIdx.x >> 1, odd = blockIdx.x & 1;
    uint32_t pp[3], key[3];
    int n1 = 0;
#pragma unroll
    for (int k = 0; k < 3; k++) {
        const int i = lane + 32 * k;
        pp[k] = lds32(sb + SM_PUB + min(i, NP - 1) * 8) & 1;
        key[k] = (i * CFG_KM % CFG_KN) << 8 | i;
        n1 += 2 * __popc(__ballot_sync(0xffffffffu, i < NP && pp[k]));
    }
    bool fixed = n1 < NTAB || NCTA - n1 < NTAB;
    if (fixed) {
        n1 = NP / 2 * 2;
        pp[0] = pp[1] = pp[2] = lane & 1;
    }
    const uint32_t mine = __shfl_sync(0xffffffffu, (me < 32 ? key[0] : me < 64 ? key[1] : key[2]) * 2 + (me < 32 ? pp[0] : me < 64 ? pp[1] : pp[2]), me & 31);
    const int part = mine & 1;
    int pos = odd;
#pragma unroll
    for (int k = 0; k < 3; k++) pos += 2 * __popc(__ballot_sync(0xffffffffu, lane + 32 * k < NP && pp[k] == (uint32_t)part && key[k] < mine / 2));
    const int role = pos < H2 ? 1 : pos < NTAB ? 2 : 0;
    const int id = pos < H2 ? part * H2 + pos : pos < NTAB ? part * H3 + pos - H2 : (part ? NCTA - n1 - NTAB : 0) + pos - NTAB;
    const uint32_t v = lds32(sb + SM_PUB + lane * 4);
    uint32_t lin = 0;
#pragma unroll
    for (int b = 0; b < 6; b++) lin |= (__popc(__ballot_sync(0xffffffffu, (v >> (b + 1)) & 1)) > 16 ? 1u : 0u) << b;
    if (lane == 0) {
        sts32(sb + SM_MISC, role << 8 | id);
        sts32(sb + SM_MISC + 4, lin);
        sts32(sb + SM_MISC + 8, NCTA - n1 - NTAB);
        sts32(sb + SM_MISC + 20, part);
        sts32(sb + SM_MISC + 12, role == 0 ? id : role == 1 ? N1 + id : N1 + N2 + id);
    }
}
__device__ __forceinline__ uint32_t sel_of(uint32_t sb, int widx, uint32_t k, int part) {
    return (__popc(k & lds32(sb + SM_MISC + 4)) ^ (lds32(sb + SM_PUB + widx * 4) >> 7) ^ part) & 1;
}
__device__ __forceinline__ uint32_t gran_off(uint32_t sb, int widx, int k, int part) { return (2 * k + sel_of(sb, widx, k, part)) << 12; }
__device__ __forceinline__ uint32_t q1a_off(uint32_t sb, int src, int blk, int part) { return gran_off(sb, 2 * blk + part, src >> 1, part) + (src & 1) * 2048; }
__device__ __forceinline__ uint32_t q1h_off(uint32_t sb, int src, int blk, int part) { return gran_off(sb, 2 * blk + part, 32 + (src >> 2), part) + (src & 3) * 1024; }
__device__ __forceinline__ uint32_t* ctl_word(const Params& p, uint32_t sb, int k, int word, int part) {
    const int widx = CWIN + lds32(sb + SM_MISC + 16);
    return (uint32_t*)(p.ring + (widx * WIN + ((2 * k + sel_of(sb, widx, k, part)) << 12))) + word;
}
__device__ __forceinline__ uint32_t* cred1_of(const Params& p, uint32_t sb, int src) { return ctl_word(p, sb, src >> 3, (src & 7) * 128, src >= (int)lds32(sb + SM_MISC + 8)); }
__device__ __forceinline__ uint32_t* fin1_of(const Params& p, uint32_t sb, int dst) { return ctl_word(p, sb, 8 + (dst >> 3), (dst & 7) * 128, dst / H2); }
__device__ __forceinline__ uint32_t* cred2_of(const Params& p, uint32_t sb, int src) { return ctl_word(p, sb, 16 + (src >> 3), (src & 7) * 128, src / H2); }
__device__ __forceinline__ uint32_t* fin2_of(const Params& p, uint32_t sb, int dst) { return ctl_word(p, sb, 24 + (dst >> 3), (dst & 7) * 128, dst / H3); }
__device__ __forceinline__ uint32_t* rdy_of(const Params& p, uint32_t sb, int word, int part) { return ctl_word(p, sb, 28, word, part); }
__device__ __forceinline__ uint32_t q2_off(uint32_t sb, int blk, int dst) {
    return (N2 + dst) * WIN + gran_off(sb, N2 + dst, (blk >> 1) * 4 + (blk & 1), dst / H3);
}
template <bool IS1>
__device__ __forceinline__ void clear_queues(const Params& p, uint32_t sb, int id, int lane) {
    constexpr int NA = (N1 + 1) / 2, NG = NA + (N1 + 3) / 4, N = IS1 ? NG * N2 : NI * 2;
    if (IS1) {
#pragma unroll 1
        for (int k = 0; k < 8; k++) sts128(sb + SM_ZERO + (k * 32 + lane) * 16, make_uint4(0, 0, 0, 0));
        if (lane == 0) spin_ge(rdy_of(p, sb, 320, lds32(sb + SM_MISC + 20)), NTAIL);
    }
    __syncwarp();
    fence_async_smem();
    for (int k = IS1 ? id + lane * N1 : lane; k < N; k += IS1 ? 32 * N1 : 32) {
        const int wi = k / NG, g = k - wi * NG;
        const uint32_t off = IS1 ? wi * WIN + gran_off(sb, wi, g < NA ? g : 32 + g - NA, wi & 1) : q2_off(sb, k >> 1, id) + (k & 1) * 16384;
        bulk_store(p.ring + off, sb + SM_ZERO, 4096);
    }
    asm volatile("cp.async.bulk.commit_group;" ::: "memory");
    asm volatile("cp.async.bulk.wait_group 0;" ::: "memory");
    TR(21, IS1 && lane == 0);
    if (!IS1) {
        fence_async_all();
        __syncwarp();
        fence_gpu();
        if (lane < NI) red_rlx(rdy_of(p, sb, id / H3 * H2 + lane, id / H3), 1u);
    }
    __syncwarp();
}

struct In8 { uint4 a[2], o[2]; uint2 g[2]; };
__device__ __forceinline__ void p1_load(const Params& p, In8& r, int i4) {
#pragma unroll
    for (int u = 0; u < 2; u++) {
        [[maybe_unused]] uint32_t x, y;
        asm volatile("tex.1d.v4.u32.s32 {%0,%1,%2,%3}, [%4, {%5}];" : "=r"(r.a[u].x), "=r"(r.a[u].y), "=r"(r.a[u].z), "=r"(r.a[u].w) : "l"(p.t_in), "r"(i4 + u * 32));
        asm volatile("tex.1d.v4.u32.s32 {%0,%1,%2,%3}, [%4, {%5}];" : "=r"(r.o[u].x), "=r"(r.o[u].y), "=r"(r.o[u].z), "=r"(r.o[u].w) : "l"(p.t_out), "r"(i4 + u * 32));
        asm volatile("tex.1d.v4.u32.s32 {%0,%1,%2,%3}, [%4, {%5}];" : "=r"(r.g[u].x), "=r"(r.g[u].y), "=r"(x), "=r"(y) : "l"(p.t_ang), "r"(i4 + u * 32));
    }
}
__device__ __forceinline__ uint32_t imad(uint32_t a, uint32_t b, uint32_t c) {
    uint32_t r;
    asm("mad.lo.u32 %0, %1, %2, %3;" : "=r"(r) : "r"(a), "r"(b), "r"(c));
    return r;
}
__device__ __forceinline__ unsigned char* ring_ptr(const Params& p, uint32_t lo) {
    uint64_t r;
    asm("mov.b64 %0, {%1, %2};" : "=l"(r) : "r"(lo), "r"(p.ring_hi));
    return (unsigned char*)r;
}
__device__ __forceinline__ uint32_t keep32(uint32_t x) {
    return __shfl_sync(0xffffffffu, x, threadIdx.x & 31);
}
__device__ __forceinline__ uint32_t opaque32(uint32_t x) {
    asm volatile("" : "+r"(x));
    return x;
}
template <typename T> __device__ __forceinline__ T* opaque(T* p) {
    asm volatile("" : "+l"(p));
    return p;
}
template <int LUT> __device__ __forceinline__ uint32_t lop3(uint32_t a, uint32_t b, uint32_t c) {
    uint32_t r;
    asm("lop3.b32 %0, %1, %2, %3, %4;" : "=r"(r) : "r"(a), "r"(b), "r"(c), "n"(LUT));
    return r;
}
__device__ __forceinline__ uint32_t dp4(uint32_t a, uint32_t b, uint32_t c) {
    uint32_t r;
    asm("dp4a.u32.u32 %0, %1, %2, %3;" : "=r"(r) : "r"(a), "r"(b), "r"(c));
    return r;
}
__device__ __forceinline__ uint32_t dp2(uint32_t a, uint32_t b, uint32_t c) {
    uint32_t r;
    asm("dp2a.lo.u32.u32 %0, %1, %2, %3;" : "=r"(r) : "r"(a), "r"(b), "r"(c));
    return r;
}
__device__ __forceinline__ void p1_put(uint32_t sb, uint32_t wa, uint32_t wb, uint32_t old, bool on) {
    asm volatile("{.reg .pred q; setp.ne.u32 q, %3, 0; @q st.shared.v2.u32 [%0], {%1,%2};}"
                 ::"r"(sb + A_ST + prmt(old, wb, 0xf762)), "r"(wa), "r"(prmt(wb, old, 0x7210)), "r"((uint32_t)on) : "memory");
}
__device__ __forceinline__ void p1_slow_tile(const Params& p, uint32_t sb, int i4) {
    const float f = __bfloat162float(p.freq[0]);
#pragma unroll 1
    for (int u = 0; u < 8; u++) {
        const int k4 = i4 + (u >> 2) * 32;
        if (k4 < p.n4) {
            const size_t t = (size_t)k4 * 4 + (u & 3);
            const float x = __bfloat162float(__float2bfloat16(f * __bfloat162float(p.angle[t])));
            slow_add(p.m, sb, p.idx_in[t], p.idx_out[t], __bfloat162float(__float2bfloat16(cosf(x))));
        }
    }
}
__device__ __forceinline__ void role_p1(const Params& p, uint32_t sb, int id, int w, int lane) {
    lane = keep32(lane);
    const uint32_t f2 = (uint32_t)__bfloat16_as_ushort(p.freq[0]) * 0x10001u;
    constexpr int TG = CFG_TG, NTK = P1W;
    static_assert(NTK <= 16, "tickets");
    const int tc = (w + id) % NTK, first = (N1 * P1W + tc) * (TG * 64);
    uint32_t* const tickets = opaque(ctl_word(p, sb, 29 + tc / 8, tc % 8 * 128 + lane, tc & 1));
    auto draw = [&]() {
        uint32_t t = 0;
        asm volatile("{.reg .pred q; setp.eq.u32 q, %2, 0; @q atom.relaxed.gpu.global.add.u32 %0, [%1], 1;}" : "+r"(t) : "l"(tickets), "r"(lane) : "memory");
        return t;
    };
    int i4 = (id * P1W + w) * (TG * 64);
    In8 r;
    ACC_DECL
    uint32_t tk = draw();
    p1_load(p, r, i4 + lane);
    while (i4 < p.n4) {
        const int cur = i4;
        i4 += 64;
        if (i4 % (TG * 64) == 0) {
            i4 = min(__shfl_sync(0xffffffffu, tk, 0), 0x7fffffffu / (NTK * TG * 64) - N1 * P1W / NTK - 2) * (NTK * TG * 64) + first;
            tk = draw();
        }
        uint32_t wa[8], wb[8], x2[4];
        x2[0] = mul_bf2(r.g[0].x, f2); x2[1] = mul_bf2(r.g[0].y, f2);
        x2[2] = mul_bf2(r.g[1].x, f2); x2[3] = mul_bf2(r.g[1].y, f2);
        const uint32_t mx = maxabs_bf2(maxabs_bf2(x2[0], x2[1]), maxabs_bf2(x2[2], x2[3]));
        const bool fast = __all_sync(0xffffffffu, cur + 64 <= p.n4 && ((mx & 0x7fffu) <= 0x4300u) && ((mx & 0x7fff0000u) <= 0x43000000u));
        {
            const uint32_t in[8] = {r.a[0].x, r.a[0].y, r.a[0].z, r.a[0].w, r.a[1].x, r.a[1].y, r.a[1].z, r.a[1].w};
            const uint32_t ou[8] = {r.o[0].x, r.o[0].y, r.o[0].z, r.o[0].w, r.o[1].x, r.o[1].y, r.o[1].z, r.o[1].w};
#pragma unroll
            for (int j = 0; j < 8; j += 2) {
                const uint32_t ch = mul_h2(pack_h2(__cosf(bflo(x2[j >> 1])), __cosf(bfhi(x2[j >> 1]))), 0x24002400u);
#pragma unroll
                for (int k = j; k < j + 2; k++) {
                    const uint32_t blk = __umulhi(in[k], p.magic2), il = imad(blk, p.nrows2, in[k]);
                    wa[k] = k & 1 ? bitsel(ch, il, 0xffff0000u) : imad(ch, 65536u, il);
                    wb[k] = imad(blk, 1u << 21, imad(ou[k] >> 5, 1u - (1u << 21), ou[k] << 16));
                }
            }
        }
        p1_load(p, r, i4 + lane);
        if (fast) {
            uint32_t old[8], any = 0;
#pragma unroll
            for (int j = 0; j < 8; j++) old[j] = atoms_add(dp2(wb[j], 0x400u, 0u) + (sb + A_CNT), 0x80001u);
#pragma unroll
            for (int j = 0; j < 8; j++) any |= old[j];
            if (!__any_sync(0xffffffffu, any & 0xffe0u)) {
#pragma unroll
                for (int j = 0; j < 8; j++) p1_put(sb, wa[j], wb[j], old[j], true);
            } else {
                uint32_t pend = 0;
#pragma unroll
                for (int j = 0; j < 8; j++) { p1_put(sb, wa[j], wb[j], old[j], !(old[j] & 0xffe0u)); if (old[j] & 0xffe0u) pend |= 1u << j; }
                ACC(0, 1)
                for (int guard = 0; __any_sync(0xffffffffu, pend); guard++) {
                    __nanosleep(CFG_BSLEEP);
                    ACC(1, 1)
#pragma unroll
                    for (int j = 0; j < 8; j++) {
                        if (__any_sync(0xffffffffu, pend >> j & 1)) {
                            const uint32_t c = lds32v(sb + A_CNT + (pend >> j & 1 ? wb[j] >> 16 : 0) * 4);
                            const bool go = (pend >> j & 1) && (((old[j] >> 19) - (c >> 19) + c) & 8191u) < 32u;
                            p1_put(sb, wa[j], wb[j], old[j], go);
                            if (go) pend &= ~(1u << j);
                        }
                    }
                    if (guard > GUARD) __trap();
                }
            }
        } else {
            p1_slow_tile(p, sb, cur + lane);
            __syncwarp();
        }
    }
    __syncwarp();
    mbar_arrive_if(sb + SM_DONE, lane == 0);
    ACC_SAVE
}

__device__ __forceinline__ void role_flush(const Params& p, uint32_t sb, int id, int f, int lane) {
    lane = keep32(lane);
    const int half = lane >> 4, o = lane >> 2, q = lane & 3;
    const uint32_t hm = keep32(half ? 0xffff0000u : 0xffffu), lth = keep32(((1u << lane) - 1) & hm);
    const uint32_t list = sb + A_LIST + f * LISTB, cnt = keep32(sb + A_CNT + (f * GPW * 32 + lane) * 4);
    const uint32_t cred = opaque32(sb + SM_CRED + (half * 32 + f * GPW) * 4);
    const uint32_t pa = opaque32(p.ring_lo + (id >> 1) * 8192 + (id & 1) * 2048 + q * 16);
    const uint32_t ph = opaque32(p.ring_lo + (32 + (id >> 2)) * 8192 + (id & 3) * 1024 + q * 8 - 2048);
    const uint32_t sa = q * 16 + (o & 1) * 64;
    uint32_t qo[GPW], hs[GPW], cr[4] = {0, 0, 0, 0};
#pragma unroll
    for (int g = 0; g < GPW; g++) {
        const int blk = f * GPW + g;
        qo[g] = 32u << 25;
        const uint32_t sa = sel_of(sb, 2 * blk + half, id >> 1, half), sh = sel_of(sb, 2 * blk + half, 32 + (id >> 2), half);
        hs[g] = sa << 31 | (2 * sh + 1 - sa) << 22 | 1u << 24 | (lane & 15) << 15 | (blk * 32 + lane) * 2;
    }
    uint4 x[KR] = {}, y[KR] = {};
    uint32_t c[GPW] = {};
    auto scan = [&]() {
#pragma unroll
        for (int g = 0; g < GPW; g++) c[g] = lds32v(cnt + g * 128);
    };
    auto credits = [&]() {
        if (GPW == 4) { const uint4 v = lds128(cred); cr[0] = v.x; cr[1] = v.y; cr[2] = v.z; cr[3] = v.w; }
        else { const uint2 v = lds64v(cred); cr[0] = v.x; cr[1] = v.y; }
    };
    ACC_DECL
    int guard = 0;
    bool idle = false, done = false;
    while (true) {
        uint32_t fr[GPW], rank[GPW], num = 0, left = 0;
        bool ok[GPW];
        if (idle && !done && __all_sync(0xffffffffu, mbar_test(sb + SM_DONE, 0))) {
            done = true;
            TR(17, f == 0 && lane == 0);
#pragma unroll
            for (int g = 0; g < GPW; g++) {
                const uint32_t u = lds32v(cnt + g * 128) & 31u, hd = hs[g] ^ (u & 16u ? imad(hs[g], 1u << 24, 1u) & 0x01000001u : 0u);
#pragma unroll 2
                for (uint32_t j = 0, k; k = (j + lane) & 15u, j < 16; j++)
                    sts64_if(sb + A_ST + ((hd & 0x7ffu) << 7) + k * 8, p.rows2, (lane * 16 + k) | (hd & 0x1000000u), (u & 15u) && k >= (u & 15u));
                reds_add(cnt + g * 128, ((0u - u) & 15u) * 0x80001u);
            }
            __syncwarp();
            scan();
        }
#pragma unroll
        for (int g = 0; g < GPW; g++) {
            const bool isfull = c[g] & 0xfff0u;
            rank[g] = __popc(__ballot_sync(0xffffffffu, isfull) & lth);
            ok[g] = isfull && (int)(rank[g] << 25) < (int)(cr[g] - qo[g] + (63u << 25));
            ACC(2, __popc(__ballot_sync(0xffffffffu, isfull && !ok[g])))
        }
#pragma unroll
        for (int g = 0; g < GPW; g++) {
            const uint32_t m = __ballot_sync(0xffffffffu, ok[g]), n = __popc(m & hm), all = __popc(m), e = num + rank[g] + (half ? all - n : 0u);
            sts32_if(KR == 2 ? list + (e & 48u) * 4 + (e & 7u) * 8 + (e >> 1 & 4u) : imad(e, 4u, list), bitsel(imad(rank[g], 1u << 25, qo[g]), hs[g], 0x7e000000u), ok[g]);
            if (ok[g]) hs[g] ^= imad(hs[g], 1u << 24, 1u) & 0x01000001u;
            fr[g] = ok[g] ? 0u - 16u : 0u;
            left |= c[g] + fr[g];
            qo[g] = imad(n, 1u << 25, qo[g]);
            num += all;
        }
        __syncwarp();
        ACC(0, 1) ACC(1, num)
        if (num) {
            uint32_t la = list + o * (KR == 2 ? 8 : 4);
            int todo = (int)num - o, rest = num;
            do {
                uint32_t d[KR];
                if (KR == 2) { const uint2 v = lds64v(la); d[0] = v.x; d[KR - 1] = v.y; }
                else {
#pragma unroll
                    for (int k = 0; k < KR; k++) d[k] = lds32v(la + 32 * k);
                }
                while (true) {
                    uint32_t bad = 0;
#pragma unroll
                    for (int k = 0; k < KR; k++) {
                        const uint32_t m = d[k] & 0x7ffu;
                        lds128_keep(x[k], imad(m, 128u, sa) + (sb + A_ST), todo > 8 * k);
                        lds128_keep(y[k], imad(m, 128u, sa ^ 64) + (sb + A_ST), todo > 8 * k);
                    }
#pragma unroll
                    for (int k = 0; k < KR; k++)
                        or3_if(bad, lop3<0x7e>(x[k].y, x[k].w, d[k]), lop3<0x7e>(y[k].y, y[k].w, d[k]), todo > 8 * k);
                    if (!__any_sync(0xffffffffu, (int)imad(bad, 128u, 0u) < 0)) break;
                    if (++guard > GUARD) __trap();
                }
#pragma unroll
                for (int k = 0; k < KR; k++) {
                    const uint32_t mi = d[k] & 0x7e0u, dm = d[k] & 0xbec00000u;
                    x[k].x = bitsel(d[k], x[k].x, 0x40078000u);
                    x[k].y = prmt(x[k].y, x[k].w, 0x5410);
                    x[k].w = prmt(y[k].y, y[k].w, 0x5410);
                    y[k].x = bitsel(d[k], y[k].x, 0x40000000u);
                    y[k].y = y[k].z;
                    stg_q128(ring_ptr(p, dp4(dm, 0x20000000u, imad(mi, WIN / 32, pa))), x[k].x, x[k].y, x[k].z, x[k].w, todo > 8 * k);
                    stg_q64(ring_ptr(p, dp4(dm, 0x10200000u, imad(mi, WIN / 32, ph))), y[k].x, y[k].y, todo > 8 * k);
                }
                la += 32 * KR;
                todo -= 8 * KR;
                rest -= 8 * KR;
            } while (rest > 0);
#pragma unroll
            for (int g = 0; g < GPW; g++) c[g] = atoms_add(cnt + g * 128, fr[g]) + fr[g];
            credits();
            idle = num <= CFG_TH;
            if (done && !__any_sync(0xffffffffu, left & 0xffffu)) break;
            if (idle) { __nanosleep(CFG_TS); scan(); credits(); }
        } else {
            if (done && !__any_sync(0xffffffffu, left & 0xffffu)) break;
            idle = true;
            __nanosleep(CFG_FSLEEP);
            scan();
            credits();
            if (++guard > GUARD) __trap();
        }
    }
#pragma unroll
    for (int g = 0; g < GPW; g++) st_rlx_if(fin1_of(p, sb, half * H2 + f * GPW + g) + id, qo[g] - (32u << 25) + 1u, (lane & 15) == 0 && f * GPW + g < NI);
    mbar_arrive_if(sb + SM_DONE2, lane == 0);
    TR(18, f == 0 && lane == 0);
    ACC_SAVE
}
__device__ __forceinline__ void role_credit1(const Params& p, uint32_t sb, int id, int lane) {
    const uint32_t* const cred = cred1_of(p, sb, id) + lane * 2;
    for (int guard = 0; !__all_sync(0xffffffffu, mbar_test(sb + SM_DONE2, 0)); guard++) {
        const uint2 v = ldg_q64(cred);
        sts64(sb + SM_CRED + lane * 8, v.x, v.y);
        __nanosleep(CFG_C1SLEEP);
        if (guard > GUARD) __trap();
    }
}

__device__ __forceinline__ float h2f(uint32_t h) {
    float f;
    asm("{.reg .b16 t; cvt.u16.u32 t, %1; cvt.f32.f16 %0, t;}" : "=f"(f) : "r"(h));
    return f;
}
__device__ __forceinline__ void p2_slow(const Params& p, uint32_t sb, const uint32_t* tmp, int row0, uint32_t dst) {
#pragma unroll 1
    for (int j = 0; j < 4; j++)
        if (tmp[8 + j] & 0x40u) slow_add(p.m, sb, row0 + (tmp[j] & 0x7fffu), (tmp[4 + j] & 0x7fffu) * 32 + dst, h2f(tmp[j] >> 16) * 64.0f);
}
__device__ __forceinline__ uint32_t mul_h2_hi(uint32_t a, uint32_t b) {
    uint32_t r;
    asm("{.reg .b16 l, h; .reg .b32 t; mov.b32 {l, h}, %2; mov.b32 t, {h, h}; mul.rn.f16x2 %0, %1, t;}" : "=r"(r) : "r"(a), "r"(b));
    return r;
}
template <bool CHECK>
__device__ __forceinline__ void role_p2(const Params& p, uint32_t sb, int id, int w, int lane) {
    lane = keep32(lane);
    const int part = id / H2, blk = id - part * H2, row0 = blk * p.rows2;
    const int o = lane >> 2, q = lane & 3;
    uint32_t* const cbase = (uint32_t*)(p.ring + (CWIN + lds32(sb + SM_MISC + 16)) * WIN);
    const uint32_t cred = opaque32((uint32_t)(uintptr_t)(cbase + part * 32 + blk));
    const uint32_t pa = opaque32(p.ring_lo + (2 * blk + part) * WIN + q * 16), ph = opaque32(pa - q * 8);
    const uint32_t po = opaque32(p.ring_lo + (q2_off(sb, blk, part * H3) & ~4096u) + q * 16 + (o & 1) * 64);
    const uint32_t sel = __ballot_sync(0xffffffffu, q2_off(sb, blk, part * H3 + (lane & 15)) & 4096u) << 12;
    const uint32_t* const fins = fin1_of(p, sb, id);
    uint32_t st[QPW] = {}, sq[QPW] = {};
    uint4 qa[NBT];
    uint2 qh[NBT];
    auto load = [&](int k) {
        qa[k] = ldg_q128(ring_ptr(p, pa + (bitsel(sq[k], st[k] >> 19, 0x7f800u) & 0x7ffc0u)));
        qh[k] = ldg_q64(ring_ptr(p, ph + (bitsel(sq[k] >> 9, st[k] >> 20, 0x7fc00u) & 0x7ffe0u)));
    };
#pragma unroll
    for (int k = 0; k < QPW; k++) {
        const int src = w * QPW + k;
        st[k] = o << 25 | (src < N1 ? 1u : 5u);
        sq[k] = src < N1 ? q1h_off(sb, src, blk, part) << 9 | q1a_off(sb, src, blk, part) | (uint32_t)(cred1_of(p, sb, src) - cbase) / 8 : 0x7e000u * 513u;
    }
#pragma unroll
    for (int k = 0; k < NBT; k++) load(k);
    ACC_DECL
    int guard = 0;
    uint32_t streak = 0;
    while (true) {
        uint32_t nn[NBT], xx[NBT][4], hh[NBT][2], dd[NBT], any = 0;
        bool last = false;
#pragma unroll
        for (int k = 0; k < NBT; k++) {
            const uint4 a = qa[k];
            const uint2 h = qh[k];
            uint32_t n = 8;
            const uint32_t miss = __ballot_sync(0xffffffffu, (int)imad((a.x ^ st[k]) & (h.x ^ st[k]), 2u, 0u) >= 0);
            if (miss) {
                n = (__ffs(miss) - 1) >> 2;
                if (!__any_sync(0xffffffffu, st[k] & 8u)) { if (streak < CFG_PSTREAK) n &= CFG_PMASK; }
                else if (!__any_sync(0xffffffffu, ((st[k] >> 6) + ((n - o) << 19) ^ st[k]) & 0x1f80000u)) { st[k] |= 4u; last = true; }
            }
            ACC(1, n == 0) ACC(2, n != 0) ACC(3, n)
            st[k] = imad(n, 1u << 25, st[k]);
            st_rlx_if((uint32_t*)ring_ptr(p, imad(sq[k] & 0x7f0u, 32u, cred)), st[k], lane == 0 && n);
            xx[k][0] = bitsel(a.x, 0x00040000u, 0xbff87fffu); xx[k][1] = a.z; xx[k][2] = h.x & 0xbfffffffu; xx[k][3] = h.y;
            hh[k][0] = a.y; hh[k][1] = a.w; dd[k] = a.x >> 13 & 0x3cu; nn[k] = n;
            any |= n;
        }
        if (!any) {
            if (!__any_sync(0xffffffffu, st[0] & 4u)) {
#pragma unroll
                for (int k = 0; k < QPW; k++) {
                    const uint32_t fin = ld_rlx(fins + ((sq[k] >> 12 & 62u) | (sq[k] >> 11 & 1u)));
                    if (fin & 1u) st[k] |= (fin >> 6 & 0x1f80000u) | ((fin ^ (st[k] - (o << 25))) >> 25 ? 8u : 12u);
                }
                streak++;
            }
            last = true;
            if (++guard > GUARD) __trap();
        } else streak = 0;
        if (last) {
            uint32_t all = 4u;
#pragma unroll
            for (int k = 0; k < QPW; k++) all &= st[k];
            last = __all_sync(0xffffffffu, all);
        }
        {
            uint32_t t[QPW], u[QPW];
#pragma unroll
            for (int k = 0; k < QPW; k++) { t[k] = st[(k + NBT) % QPW]; u[k] = sq[(k + NBT) % QPW]; }
#pragma unroll
            for (int k = 0; k < QPW; k++) { st[k] = t[k]; sq[k] = u[k]; }
        }
#pragma unroll
        for (int k = 0; k < NBT; k++) load(k);
#pragma unroll
      for (int k = 0; k < NBT; k++) {
        if (nn[k]) {
            const uint32_t* const x = xx[k];
            const uint32_t h0 = hh[k][0], h1 = hh[k][1], d4 = dd[k];
            const bool v = o < nn[k];
            uint32_t ta[4], tb[4], w0[4], w1[4];
            const uint32_t ca = imad(d4, 4u, sb + SM_CNT2 + q * 4), old = atoms_add(ca, v ? 0x10001u : 0u);
#pragma unroll
            for (int j = 0; j < 4; j++) {
                ta[j] = lds32nv(dp2(x[j], 4u, 0u) + (sb + B_TA));
                tb[j] = lds16nv(dp2(x[j], 2u, 0u) + (sb + B_TB));
            }
            const uint32_t tag = old << 8 & 0x40000000u;
#pragma unroll
            for (int j = 0; j < 4; j++) {
                const uint32_t z = prmt(j & 2 ? h1 : h0, 0, j & 1 ? 0x4342 : 0x4140);
                const uint32_t t23 = prmt((ta[j] & 0x60076007u) * 2050u, tb[j], 0x5341) & 0xfffcffffu;
                w0[j] = (imad(z, 128u, j & 1 ? 0u : tag) & 0x78007800u) | mul_h2_hi(ta[j] & 0x9ff89ff8u, x[j]);
                w1[j] = (imad(z, 2048u, 0u) & 0x78007800u) | mul_h2_hi(t23, x[j]);
            }
            if (CHECK && v && ((tb[0] | tb[1] | tb[2] | tb[3]) & 0x40u)) {
                uint32_t tmp[12];
#pragma unroll
                for (int j = 0; j < 4; j++) {
                    tmp[j] = x[j]; tmp[4 + j] = (j & 2 ? h1 : h0) >> (j & 1 ? 16 : 0); tmp[8 + j] = tb[j];
                    if (tb[j] & 0x40u) { w0[j] &= 0x78007800u; w1[j] &= 0x78007800u; }
                }
                p2_slow(p, sb, tmp, row0, part * H3 + d4 / 4);
            }
            const uint32_t off = (bitsel(old >> 9, old >> 7, 0x0f80u) & 0x4f80u) + imad(d4, WIN / 4, (sel >> (d4 / 4) & 4096u) + po);
            bool wait = v && (old & (0x10000u - NQ2));
            if (!__any_sync(0xffffffffu, wait)) {
                stg_q128(ring_ptr(p, off), w0[0], w1[0], w0[1], w1[1], v);
                stg_q128(ring_ptr(p, off ^ 64u), w0[2], w1[2], w0[3], w1[3], v);
            } else {
                bool pend = v;
                ACC(0, 1)
                for (int g2 = 0;; g2++) {
                    stg_q128(ring_ptr(p, off), w0[0], w1[0], w0[1], w1[1], pend && !wait);
                    stg_q128(ring_ptr(p, off ^ 64u), w0[2], w1[2], w0[3], w1[3], pend && !wait);
                    pend = wait;
                    if (!__any_sync(0xffffffffu, pend)) break;
                    __nanosleep(CFG_BSLEEP);
                    const uint32_t c = lds32v(ca);
                    wait = pend && (((old >> 16) - (c >> 16) + c) & 0xffffu) >= NQ2;
                    if (g2 > GUARD) __trap();
                }
            }
        }
      }
        if (last) break;
    }
    TR(17, w == 0 && lane == 0);
    __syncwarp();
    uint32_t rank = 0;
    if (lane == 0) { __threadfence_block(); rank = atoms_add(sb + SM_FIN, 1u); __threadfence_block(); }
    if (__shfl_sync(0xffffffffu, rank, 0) == P2W - 1 && lane < 16)
        st_rlx(fin2_of(p, sb, part * H3 + lane) + blk, FIN | (((lds32v(sb + SM_CNT2 + lane * 16) >> 16) - NQ2) & 0xffffu));
    __syncwarp();
    mbar_arrive_if(sb + SM_DONE, lane == 0);
    ACC_SAVE
}
__device__ __forceinline__ void role_credit(const Params& p, uint32_t sb, int id, int lane) {
    const uint32_t* const cred = cred2_of(p, sb, id) + (lane >> 2);
    uint32_t last = 0, last2 = 0;
    for (int guard = 0;; guard++) {
        if (__all_sync(0xffffffffu, mbar_test(sb + SM_DONE, 0))) break;
        const uint32_t c = ld_rlx(cred), c2 = ld_rlx(cred + 8);
        reds_add(sb + SM_CNT2 + lane * 4, 0u - ((c - last) & 0xffffu));
        reds_add(sb + SM_CNT2 + 128 + lane * 4, 0u - ((c2 - last2) & 0xffffu));
        last = c;
        last2 = c2;
        __nanosleep(CFG_CSLEEP);
        if (guard > GUARD) __trap();
    }
}

__device__ __forceinline__ void p3_wrap(uint32_t sb, int id, const uint32_t* tmp) {
    const Scale sc = get_scale(sb);
#pragma unroll 1
    for (int j = 0; j < 8; j++) {
        const uint32_t old = tmp[4 + j], v = tmp[12 + j], nw = old + v, t = (old ^ nw) & (v ^ nw);
        if (t & 0x80008000u) {
            const float k = (t & 0x8000u) ? ((v & 0x8000u) ? -1.0f : 1.0f) : 0.0f;
            const float q = (t & 0x80000000u) ? ((int)v < 0 ? -65536.0f : 65536.0f) : 0.0f;
            const uint32_t e0 = (j & 1) ? sc.eb[2] : sc.eb[0], e1 = (j & 1) ? sc.eb[3] : sc.eb[1];
            const float lo = k * 65536.0f * __uint_as_float((e0 - 10) << 23), hi = (q - k) * __uint_as_float((e1 - 10) << 23);
            if (j & 1) sg_add(tmp[j >> 1] * 32 + id, 0.f, 0.f, lo, hi);
            else sg_add(tmp[j >> 1] * 32 + id, lo, hi, 0.f, 0.f);
        }
    }
}
__device__ __forceinline__ uint32_t p3_val(uint32_t w) {
    const uint32_t mk = prmt(w, 0, 0xBB99);
    return ((w & 0x07ff07ffu) ^ mk) - mk;
}
__device__ __forceinline__ void role_p3(const Params& p, uint32_t sb, int id, int w, int lane) {
    lane = keep32(lane);
    uint32_t* const cred = opaque(cred2_of(p, sb, id / H3 * H2 + w) + id % H3);
    const uint32_t pq = opaque32(p.ring_lo + q2_off(sb, w, id) + lane * 16);
    auto off = [&](uint32_t n) { return (n & 1u) << 11 | (n & 2u) << 13; };
    const uint32_t pp = opaque32(pq - lane * 16 + 112);
    const uint32_t* const finp = opaque(fin2_of(p, sb, id) + w);
    auto tag_of = [&](uint32_t n) { return ~n << 28; };
    uint32_t n = 0, fin = 0, pr = 0, pk = 0;
    uint4 v[4] = {};
    bool have = false, last = false;
    ACC_DECL
    int guard = 0;
    while (true) {
        const uint32_t ex = tag_of(n);
        const bool ok = have && !__any_sync(0xffffffffu, ((v[0].x ^ ex) | (v[1].x ^ ex) | (v[2].x ^ ex) | (v[3].x ^ ex)) & 0x40000000u);
        if (ok) n++;
        const bool ready = (ok || !have) && __all_sync(0xffffffffu, !((pr ^ tag_of(n)) & 0x40000000u));
        st_rlx_if(cred, n * 16, lane == 0 && ok);
        if (!ok && !ready && __all_sync(0xffffffffu, fin & FIN)) {
            const uint32_t left = __shfl_sync(0xffffffffu, (fin - n * 16) & 0xffffu, 0);
            if (left - 1u > 0x8000u) break;
            if (left < 16u) {
#pragma unroll
                for (int u = 0; u < 4; u++) {
                    v[u] = make_uint4((ex & 0x40000000u) | (lane & 16) << 7, (lane & 15) << 11, (lane & 16) << 7, (lane & 15) << 11);
                    ldq128_keep(v[u], ring_ptr(p, pq + off(n)) + u * 512, u * 4 + (lane >> 3) < left);
                }
                have = last = !__any_sync(0xffffffffu, ((v[0].x ^ ex) | (v[1].x ^ ex) | (v[2].x ^ ex) | (v[3].x ^ ex)) & 0x40000000u);
                pr = ~tag_of(n + have);
                if (++guard > GUARD) __trap();
                continue;
            }
        }
        uint32_t row[8], val[16];
#pragma unroll
        for (int u = 0; u < 4; u++) {
            const uint4 x = v[u];
            row[2 * u] = prmt(bitsel(x.x << 1, x.y >> 3, 0x7000f000u), 0, 0x4431);
            row[2 * u + 1] = prmt(bitsel(x.z << 1, x.w >> 3, 0x7000f000u), 0, 0x4431);
            val[4 * u] = p3_val(x.x); val[4 * u + 1] = p3_val(x.y);
            val[4 * u + 2] = p3_val(x.z); val[4 * u + 3] = p3_val(x.w);
        }
#pragma unroll
        for (int u = 0; u < 4; u++) ldq128_keep(v[u], ring_ptr(p, pq + off(n)) + u * 512, ready);
        pk = ready ? CFG_PK1 * 128 : ok ? CFG_PK2 * 128 : have ? 15 * 128 : max(pk, CFG_PK3 * 128u);
        pr = ld_rlx((const uint32_t*)ring_ptr(p, pp + off(n + ready) + pk));
        ACC(2, have && !ok)
        have = ready;
        if (!ok) {
            ACC(1, 1)
            fin = ld_rlx(finp);
            if (++guard > GUARD) __trap();
        } else {
#pragma unroll
            for (int u = 0; u < 4; u += 2) {
                uint32_t old[8], chk = 0;
#pragma unroll
                for (int j = 0; j < 4; j++) {
                    old[2 * j] = atoms_add(sb + C_S + row[2 * u + j] * 4, val[4 * u + 2 * j]);
                    old[2 * j + 1] = atoms_add(sb + C_S + ROWS3_MAX * 4 + row[2 * u + j] * 4, val[4 * u + 2 * j + 1]);
                }
#pragma unroll
                for (int j = 0; j < 8; j++) {
                    const uint32_t nw = old[j] + val[4 * u + j];
                    chk |= (old[j] ^ nw) & (val[4 * u + j] ^ nw);
                }
                if (chk & 0x80008000u) {
                    uint32_t tmp[20];
#pragma unroll
                    for (int j = 0; j < 8; j++) { tmp[j >> 1] = row[2 * u + (j >> 1)]; tmp[4 + j] = old[j]; tmp[12 + j] = val[4 * u + j]; }
                    p3_wrap(sb, id, tmp);
                }
            }
            __syncwarp();
            if (last) break;
        }
    }
    ACC_SAVE
}

__device__ __forceinline__ void row_gates(const float* sw, const uint32_t* c2, uint32_t dbits, float4& gs, float4& gr) {
    const uint32_t d2 = dbits * 0x10001u;
    gs = gr = make_float4(0.f, 0.f, 0.f, 0.f);
#pragma unroll
    for (int r2 = 0; r2 < 4; r2++) {
        uint32_t df = sub_bf2(d2, c2[r2]);
        uint32_t ar = mul_bf2(mul_bf2(df, df), 0xC120C120u);
        uint32_t rb = pack_bf2(__expf(bflo(ar)), __expf(bfhi(ar)));
        const float r0 = bflo(rb), r1 = bfhi(rb);
        const float4 s0 = *(const float4*)(sw + r2 * 8), s1 = *(const float4*)(sw + r2 * 8 + 4);
        const float4 q0 = *(const float4*)(sw + 32 + r2 * 8), q1 = *(const float4*)(sw + 32 + r2 * 8 + 4);
        gs.x += r0 * s0.x + r1 * s1.x; gs.y += r0 * s0.y + r1 * s1.y;
        gs.z += r0 * s0.z + r1 * s1.z; gs.w += r0 * s0.w + r1 * s1.w;
        gr.x += r0 * q0.x + r1 * q1.x; gr.y += r0 * q0.y + r1 * q1.y;
        gr.z += r0 * q0.z + r1 * q1.z; gr.w += r0 * q0.w + r1 * q1.w;
    }
}
__device__ __forceinline__ uint2 finish_row(const float* wu, const float4& gs, const float4& gr, const float S[4], uint2 mrow) {
    const float a[4] = {S[0] * gs.x, S[1] * gs.y, S[2] * gs.z, S[3] * gs.w};
    float u[4] = {0, 0, 0, 0};
#pragma unroll
    for (int k = 0; k < 4; k++) {
        u[0] += a[k] * wu[4 * k]; u[1] += a[k] * wu[4 * k + 1]; u[2] += a[k] * wu[4 * k + 2]; u[3] += a[k] * wu[4 * k + 3];
    }
    return make_uint2(pack_bf2(bflo(mrow.x) + u[0] * gr.x, bfhi(mrow.x) + u[1] * gr.y),
                      pack_bf2(bflo(mrow.y) + u[2] * gr.z, bfhi(mrow.y) + u[3] * gr.w));
}
__device__ __forceinline__ void load_tail_weights(const Params& p, float* sw, int tid) {
    if (tid < 32) sw[tid] = __bfloat162float(p.w_sbf[tid]);
    else if (tid < 64) sw[tid] = __bfloat162float(p.w_rbf[tid - 32]);
    else if (tid < 80) sw[tid] = __bfloat162float(p.w_up[tid - 64]);
    else if (tid < 96) sw[tid] = __bfloat162float(p.w_down[tid - 80]);
}
__device__ __forceinline__ float exp_ftz(float x) {
    float r;
    asm("ex2.approx.ftz.f32 %0, %1;" : "=f"(r) : "f"(x * 1.4426950408889634f));
    return r;
}
__device__ __forceinline__ void tail_rows(const Params& p, int tidx, int w, int lane) {
    constexpr uint32_t sb = SB;
    if (w == NW - 1 && lane < 2) {
        fence_gpu();
        red_rlx(rdy_of(p, sb, 320, lane), 1u);
    }
    if (w > NPC * WPP) return;
    const bool dry = w == NPC * WPP;
    const int pc = w / WPP, r0 = pc * RPC + (tidx * WPP + w - pc * WPP) * 8, e0 = r0 * 32;
    const uint32_t G = sb + T_G + w * TWB, M = G + 4096, D = M + 2048;
    if (!dry) {
        cp16z(D + lane * 16, p.dist + e0 + lane * 8, min(max(p.E - e0 - lane * 8, 0), 8) * 2);
#pragma unroll
        for (int k = 0; k < 4; k++) cp16(M + (k * 32 + lane) * 16, p.m + e0 + (k * 32 + lane) * 2, e0 + (k * 32 + lane) * 2 < p.E);
        cp_commit();
    }
    const Scale sc = get_scale(sb);
    const float lsb[4] = {__uint_as_float((sc.eb[0] - 10) << 23), __uint_as_float((sc.eb[1] - 10) << 23),
                          __uint_as_float((sc.eb[2] - 10) << 23), __uint_as_float((sc.eb[3] - 10) << 23)};
    if (!dry) {
        const int g = lane >> 2, t = lane & 3;
        const uint32_t c2 = lds32(sb + SM_CEN + t * 4), wg = sb + SM_W + ((g >> 2) * 32 + t * 8 + (g & 3)) * 4;
        const uint32_t b = prmt(lds32(wg), lds32(wg + 16), 0x7632);
        cp_wait<0>();
        __syncwarp();
        TR(19, w == 0 && lane == 0 && b + c2 != 0x12345);
#pragma unroll 2
        for (int k = 0; k < 16; k++) {
            const uint32_t dv = lds32(D + (k * 8 + g) * 4);
            uint32_t a[2];
#pragma unroll
            for (int h = 0; h < 2; h++) {
                const uint32_t df = sub_bf2(prmt(dv, 0, h ? 0x3232 : 0x1010), c2);
                const uint32_t ar = mul_bf2(mul_bf2(df, df), 0xC120C120u);
                a[h] = pack_bf2(exp_ftz(bflo(ar)), exp_ftz(bfhi(ar)));
            }
            float d[4];
            asm("mma.sync.aligned.m16n8k8.row.col.f32.bf16.bf16.f32 {%0,%1,%2,%3}, {%4,%5}, {%6}, {%7,%7,%7,%7};"
                : "=f"(d[0]), "=f"(d[1]), "=f"(d[2]), "=f"(d[3]) : "r"(a[0]), "r"(a[1]), "r"(b), "f"(0.f));
            const uint32_t at = G + (k * 16 + g * 2) * 16 + t * 4;
            sts32(at, pack_bf2(d[0], d[1]));
            sts32(at + 16, pack_bf2(d[2], d[3]));
        }
    }
    __syncwarp();
    TR(2, w == 0 && lane == 0);
    float wu[16];
#pragma unroll
    for (int k = 0; k < 4; k++) *(uint4*)(wu + 4 * k) = lds128(sb + SM_W + 256 + 16 * k);
    uint32_t dirty = 0;
    {
        const bool pass = !dry;
        if (pass) {
            if (w == pc * WPP && lane < 2) spin_ge(rdy_of(p, sb, lane ? 320 : 160 + 32 * pc, lds32(sb + SM_MISC + 20)), lane ? NTAIL : N3);
            __syncwarp();
            bar_sync(1 + pc, WPP * 32);
            TR(3, w == 0 && lane == 0);
            TR(10, w == NPC * WPP - 1 && lane == 0);
            if (r0 >= (int)p.rows3) return;
        }
        uint4 sv[4] = {};
#pragma unroll
        for (int u = 0; u < 4; u++) ldq128_keep(sv[u], &g_S[0][u * 16 + (lane >> 1)][r0 + (lane & 1) * 4], pass);
        if (pass && lane < 8 && (r0 + lane) * 32 < p.E && (dirty = ld_rlx(g_dirty + r0 + lane))) st_rlx(g_dirty + r0 + lane, 0u);
        dirty = __ballot_sync(0xffffffffu, dirty != 0);
        uint32_t xs[8] = {sv[0].x, sv[0].y, sv[0].z, sv[0].w, sv[1].x, sv[1].y, sv[1].z, sv[1].w};
        uint32_t ys[8] = {sv[2].x, sv[2].y, sv[2].z, sv[2].w, sv[3].x, sv[3].y, sv[3].z, sv[3].w};
        auto finish = [&](int k, uint32_t x, uint32_t y, bool extra) {
            const int i = (lane & 1) * 128 + (lane >> 1) + (k & 3) * 32 + (k >> 2) * 16, e = e0 + i;
            float S[4];
            const uint32_t tx = x + 0x80008000u, ty = y + 0x80008000u;
            S[0] = (__uint_as_float(prmt(tx, 0x4b000000u, 0x7610)) - 8421376.0f) * lsb[0];
            S[1] = (__uint_as_float(prmt(tx, 0x4b000000u, 0x7632)) - 8421376.0f) * lsb[1];
            S[2] = (__uint_as_float(prmt(ty, 0x4b000000u, 0x7610)) - 8421376.0f) * lsb[2];
            S[3] = (__uint_as_float(prmt(ty, 0x4b000000u, 0x7632)) - 8421376.0f) * lsb[3];
            if (extra && e < p.E) {
                const float4 g = __ldcg(g_Sg + e);
                S[0] += g.x; S[1] += g.y; S[2] += g.z; S[3] += g.w;
                __stcg(g_Sg + e, make_float4(0.f, 0.f, 0.f, 0.f));
            }
            const uint4 g = lds128(G + i * 16);
            const uint2 o = finish_row(wu, make_float4(bflo(g.x), bfhi(g.x), bflo(g.y), bfhi(g.y)), make_float4(bflo(g.z), bfhi(g.z), bflo(g.w), bfhi(g.w)), S,
                                       lds64v(M + i * 8));
            asm volatile("{.reg .pred q; setp.ne.u32 q, %3, 0; @q st.global.v2.u32 [%0], {%1,%2};}"
                         ::"l"(p.out + e), "r"(o.x), "r"(o.y), "r"((uint32_t)(pass && e < p.E)));
        };
        if (!dirty) {
#pragma unroll
            for (int k = 0; k < 8; k++) finish(k, xs[k], ys[k], false);
        } else {
#pragma unroll 1
            for (int k = 0; k < 8; k++) {
                finish(k, xs[0], ys[0], dirty >> ((lane & 1) * 4 + (k & 3)) & 1);
#pragma unroll
                for (int j = 0; j < 7; j++) { xs[j] = xs[j + 1]; ys[j] = ys[j + 1]; }
            }
        }
    }
    TR(9, w == 0 && lane == 0);
    TR(11, w == NPC * WPP - 1 && lane == 0);
}

#define CFG_MAP1 1
__global__ void __launch_bounds__(NT, 1) k_main(const __grid_constant__ Params p) {
    extern __shared__ __align__(1024) unsigned char smem[];
    constexpr uint32_t sb = SB;
    if ((uint32_t)__cvta_generic_to_shared(smem) != SB) __trap();
    const int tid = threadIdx.x, w = __shfl_sync(0xffffffffu, tid >> 5, 0), lane = tid & 31;
    if (w < NPROBE) probe(p, sb, w, lane);
    else {
        if (tid == NT - 1) sts32(sb + SM_MISC + 16, ld_rlx(&g_epoch) & 1);
        if (tid >= NT - 32 && lane < 12) sts32(sb + SM_FIN + lane * 4, 0u);
        load_tail_weights(p, (float*)(smem + SM_W), tid - NPROBE * 32);
        if (w == NW - 3 && lane < 4) sts32(sb + SM_CEN + lane * 4, ((const uint32_t*)p.centers)[lane]);
        const int k = blockIdx.x % (NCTA / 2) * 14 + lane;
        if (w == NW - 2 && lane < 14 && k < NT - 32) asm volatile("prefetch.global.L2 [%0];" ::"l"((const uint4*)p.m + k * (p.E / 2 / (NT - 32))));
    }
    cta_sync();
    if (w) {
        const uint4 in = __ldg((const uint4*)p.m + (tid - 32) * (p.E / 2 / (NT - 32)));
        const Mat4 wd = load_mat4(p.w_down, lane);
        for (int i = SM_DATA / 16 + tid - 32; i < ZEND / 16; i += NT - 32) ((uint4*)smem)[i] = make_uint4(0, 0, 0, 0);
        if (tid - 32 < 256) ((uint4*)(smem + SM_ZERO))[tid - 32] = make_uint4(0, 0, 0, 0);
        if (tid < 96) sts32(sb + SM_CNT2 + (tid - 32) * 4, NQ2 << 16);
        __syncwarp();
        if (CFG_PFD && tid == NT - 1) {
            __nanosleep(CFG_PFD);
            const uint32_t n = (p.E / 2 + NCTA - 1) / NCTA, o = blockIdx.x * n;
            if (o < (uint32_t)p.E / 2) asm volatile("cp.async.bulk.prefetch.L2.global [%0], %1;" ::"l"((const uint4*)p.m + o), "r"(min(n, p.E / 2 - o) * 16) : "memory");
        }
        __syncwarp();
        md_stats(in, wd, lane);
    } else assign_role(p, sb, lane);
    if (tid == 0) {
        mbar_init(sb + SM_DONE, lds32(sb + SM_MISC) >> 8 ? P2W : P1W);
        mbar_init(sb + SM_DONE2, NF);
    }
    cta_sync();
    const uint32_t rid = __shfl_sync(0xffffffffu, lds32(sb + SM_MISC), 0);
    const int role = rid >> 8, id = rid & 255;
    TR(5, tid == 0);
    if (role == 0) {
        const int ww = CFG_MAP1 == 0 ? ((w & 3) == 3 ? NW : (w >> 2) * 3 + (w & 3)) : CFG_MAP1 == 1 ? (w & 2 ? NW : (w >> 2) * 2 + (w & 1)) : w;
        const int sw = CFG_MAP1 == 0 ? ((w & 3) == 3 ? w >> 2 : NW) : CFG_MAP1 == 1 ? (w & 2 ? (w >> 2) * 2 + (w & 1) : NW) : w - P1W;
        static_assert(CFG_MAP1 == 0 ? (P1W <= NW / 4 * 3 && NF + 2 <= NW / 4) : CFG_MAP1 == 1 ? (P1W <= NW / 2 && NF + 2 <= NW / 2) : true, "warp map");
        for (int i = tid; i < NF * GPW * 32; i += NT) sts32(sb + A_CNT + i * 4, 1u << 24);
        if (tid < 64) sts32(sb + SM_CRED + tid * 4, 0u);
        cta_sync();
        TR(1, tid == 0);
        if (ww < P1W) role_p1(p, sb, id, ww, lane);
        else if (sw < NF) role_flush(p, sb, id, sw, lane);
        else if (sw == NF) role_credit1(p, sb, id, lane);
        else if (w == NW - 1) {
            uint4* owin = (uint4*)(p.ring + (CWIN + (lds32(sb + SM_MISC + 16) ^ 1)) * WIN);
            for (int i = id * 32 + lane; i < CPAIRS * 512; i += N1 * 32) __stcg(owin + i, make_uint4(0, 0, 0, 0));
            __syncwarp();
        }
    } else if (role == 1) {
        const int row0 = id % H2 * p.rows2;
        const int nrows = min((int)p.rows2, p.E - row0);
        constexpr int NTB = NT - 32, TBD = CFG_TBD;
        bool flagged = false;
        if (w < NW - 1) {
            const uint4* const src = (const uint4*)(p.m + row0);
            uint4 r2[TBD], nx[TBD];
            auto fetch = [&](int i) {
#pragma unroll
                for (int k = 0; k < TBD; k++)
                    asm volatile("ld.global.nc.v4.u32 {%0,%1,%2,%3}, [%4];" : "=r"(nx[k].x), "=r"(nx[k].y), "=r"(nx[k].z), "=r"(nx[k].w) : "l"(src + min(i + k * NTB, nrows / 2 - 1)));
            };
            fetch(tid);
            const Scale sc = get_scale(sb);
            const Mat4 wd = load_mat4(p.w_down, lane);
            const uint32_t slow = sc.allslow ? 0x60006000u : 0u;
            Mat4 ws;
#pragma unroll
            for (int k = 0; k < 4; k++) ws.b[k] = mul_bf2(wd.b[k], ((246u - (lane & 4 ? sc.eb[(k & 2) + 1] : sc.eb[k & 2])) << 7) * 0x10001u);
#pragma unroll 1
            for (int i0 = tid; 2 * (i0 - lane) < nrows; i0 += TBD * NTB) {
#pragma unroll
                for (int k = 0; k < TBD; k++) r2[k] = make_uint4(nx[k].x, nx[k].z, nx[k].y, nx[k].w);
                fetch(i0 + TBD * NTB);
                uint32_t big[2 * TBD], any = slow;
#pragma unroll
                for (int k = 0; k < TBD; k++) {
                    const int i = i0 + k * NTB;
                    float y[8];
                    mul4(make_uint4(r2[k].x, r2[k].z, r2[k].y, r2[k].w), ws, y);
                    uint32_t a[4], h[4], ta[2];
#pragma unroll
                    for (int j = 0; j < 4; j++) { a[j] = pack_h2(y[2 * j], y[2 * j + 1]); h[j] = a[j] + 0x00040004u; }
#pragma unroll
                    for (int j = 0; j < 2; j++) {
                        ta[j] = bitsel(h[2 * j], bitsel(h[2 * j + 1] >> 3, h[2 * j + 1] << 7, 0x00070007u), 0x9ff89ff8u);
                        big[2 * k + j] = a[2 * j] | a[2 * j + 1] | h[2 * j] | h[2 * j + 1];
                    }
                    any |= big[2 * k] | big[2 * k + 1];
                    sts64_if(sb + B_TA + i * 8, ta[0], ta[1], 2 * i < nrows);
                    sts32_if(sb + B_TB + i * 4, prmt(h[1], h[3], 0x7531), 2 * i < nrows);
                }
                if (__any_sync(0xffffffffu, any & 0x60006000u)) {
#pragma unroll
                    for (int k = 0; k < 2 * TBD; k++) {
                        const int r = 2 * (i0 + (k >> 1) * NTB) + (k & 1);
                        if (((big[k] | slow) & 0x60006000u) && r < nrows) { sts32(sb + B_TA + r * 4, 0u); sts16(sb + B_TB + r * 2, 0x40u); }
                    }
                    flagged = true;
                }
            }
            if (tid == 0) {
                sts32(sb + B_TA + p.rows2 * 4, 0u);
                sts16(sb + B_TB + p.rows2 * 2, 0u);
            }
            TR(8, tid == 0);
        } else if (lane == 0) spin_ge(rdy_of(p, sb, id, id / H2), H3);
        __syncwarp();
        flagged = __any_sync(0xffffffffu, __syncthreads_or(flagged));
        TR(1, tid == 0);
        if (w < P2W) {
            if (flagged) role_p2<true>(p, sb, id, w, lane);
            else role_p2<false>(p, sb, id, w, lane);
        } else if (w == P2W) role_credit(p, sb, id, lane);
    } else {
        if (w == 0) clear_queues<false>(p, sb, id, lane);
        if (tid >= 32 && tid < 33 + NPC) mbar_init(sb + SM_DBAR + (tid - 32) * 8, 1);
        cta_sync();
        TR(1, tid == 0);
        if (w < P3W) role_p3(p, sb, id, w, lane);
        const int pc = w - P3W, n = min(((int)p.rows3 + 7) / 8 * 8 - pc * RPC, RPC);
        uint32_t *f0 = nullptr, *f1 = nullptr;
        if (pc >= 0) { f0 = opaque(rdy_of(p, sb, 160 + 32 * pc, 0)); f1 = opaque(rdy_of(p, sb, 160 + 32 * pc, 1)); }
        cta_sync();
        TR(2, tid == 0);
        if (pc >= 0 && pc < NPC && lane == 0) {
            fence_async_smem();
            if (pc >= CFG_DOUT) mbar_wait(sb + SM_DBAR + (pc + 1 - CFG_DOUT) * 8, 0);
            if (n > 0) {
                bulk_store(g_S[0][id] + pc * RPC, sb + C_S + pc * RPC * 4, n * 4);
                bulk_store(g_S[1][id] + pc * RPC, sb + C_S + (ROWS3_MAX + pc * RPC) * 4, n * 4);
            }
            asm volatile("cp.async.bulk.commit_group;" ::: "memory");
            asm volatile("cp.async.bulk.wait_group.read 0;" ::: "memory");
            mbar_arrive(sb + SM_DBAR + pc * 8 + 8);
            asm volatile("cp.async.bulk.wait_group 0;" ::: "memory");
            fence_gpu();
            red_rlx(f0, 1u);
            red_rlx(f1, 1u);
            if (id == 0 && pc == 0) red_rlx(&g_epoch, 1u);
            TR(12 + pc, true);
        }
        return;
    }
    cta_sync();
    TR(18, tid == 0 && role == 1);
    if (role == 0 && w == NW - 2) clear_queues<true>(p, sb, id, lane);
    tail_rows(p, role * N1 + id, w, lane);
}

__global__ void k_direct(const Params p, long long T) {
    float wd[16];
#pragma unroll
    for (int i = 0; i < 16; i++) wd[i] = __bfloat162float(p.w_down[i]);
    const float f = __bfloat162float(p.freq[0]);
    for (long long t = blockIdx.x * (long long)blockDim.x + threadIdx.x; t < T; t += (long long)gridDim.x * blockDim.x) {
        float x = __bfloat162float(__float2bfloat16(f * __bfloat162float(p.angle[t])));
        float c = __bfloat162float(__float2bfloat16(cosf(x)));
        uint2 md = down_row(__ldg(p.m + p.idx_in[t]), wd);
        red_v4(g_Sg + p.idx_out[t], c * bflo(md.x), c * bfhi(md.x), c * bflo(md.y), c * bfhi(md.y));
    }
}
__global__ void k_direct_tail(const Params p) {
    __shared__ __align__(16) float sw[96];
    load_tail_weights(p, sw, threadIdx.x);
    __syncthreads();
    uint32_t c2[4];
#pragma unroll
    for (int i = 0; i < 4; i++) c2[i] = ((const uint32_t*)p.centers)[i];
    for (int e = blockIdx.x * blockDim.x + threadIdx.x; e < p.E; e += gridDim.x * blockDim.x) {
        float4 g = __ldcg(g_Sg + e);
        __stcg(g_Sg + e, make_float4(0.f, 0.f, 0.f, 0.f));
        const float Sv[4] = {g.x, g.y, g.z, g.w};
        float4 gs, gr;
        row_gates(sw, c2, __bfloat16_as_ushort(p.dist[e]), gs, gr);
        p.out[e] = finish_row(sw + 64, gs, gr, Sv, __ldg(p.m + e));
    }
}

static bool pick_rows(int E, int n, int rows_max, int mult, uint32_t* rows, uint32_t* magic) {
    for (uint32_t r = (E + n - 1) / n; r <= (uint32_t)rows_max; r++) {
        if (r < 2 || r % mult) continue;
        uint64_t mg = ((1ull << 32) + r - 1) / r;
        uint64_t err = mg * r - (1ull << 32);
        if (err * (uint64_t)n < mg) { *rows = r; *magic = (uint32_t)mg; return true; }
    }
    return false;
}

}

extern "C" void kernel_launch(void* const* d_in, const int* in_sizes, int n_in, void* d_out, int out_size) {
    using namespace gs;
    (void)n_in; (void)out_size;
    Params p;
    p.m = (const uint2*)d_in[0];
    p.idx_in = (const int*)d_in[1];
    p.idx_out = (const int*)d_in[2];
    p.dist = (const __nv_bfloat16*)d_in[3];
    p.angle = (const __nv_bfloat16*)d_in[4];
    p.centers = (const __nv_bfloat16*)d_in[5];
    p.freq = (const __nv_bfloat16*)d_in[6];
    p.w_rbf = (const __nv_bfloat16*)d_in[7];
    p.w_sbf = (const __nv_bfloat16*)d_in[8];
    p.w_down = (const __nv_bfloat16*)d_in[9];
    p.w_up = (const __nv_bfloat16*)d_in[10];
    p.out = (uint2*)d_out;
    p.E = in_sizes[3];
    const long long T = in_sizes[1];
    p.n4 = (int)(T / 4);
    p.rows2 = p.magic2 = 0;
    p.ring = nullptr;

    static int sms = 0, rsv = 0;
    if (!sms) {
        int dev = 0;
        cudaGetDevice(&dev);
        cudaDeviceGetAttribute(&rsv, cudaDevAttrReservedSharedMemoryPerBlock, dev);
        cudaDeviceGetAttribute(&sms, cudaDevAttrMultiProcessorCount, dev);
        cudaFuncSetAttribute(k_main, cudaFuncAttributeMaxDynamicSharedMemorySize, SMEM_BYTES);
    }
    cudaStream_t st = cudaStreamPerThread;
    bool fast = (T % 4 == 0) && T > 0 && sms >= NCTA && rsv == (int)SB && p.E >= 65536 && p.E <= E_MAX &&
                p.E % 4 == 0 && (((uintptr_t)p.m | (uintptr_t)p.idx_in | (uintptr_t)p.idx_out | (uintptr_t)p.angle) & 15) == 0 &&
                pick_rows(p.E, NI, ROWS2_MAX, 2, &p.rows2, &p.magic2);
    p.nrows2 = 0u - p.rows2;
    p.rows3 = (p.E + 31) / 32;
    fast = fast && (p.rows2 * (NI - 1) + 2 <= (uint32_t)p.E);
    static const void* tkey[3] = {nullptr, nullptr, nullptr};
    static cudaTextureObject_t tex[3] = {0, 0, 0};
    static long long tlen = -1;
    const void* tptr[3] = {p.idx_in, p.idx_out, p.angle};
    for (int k = 0; fast && k < 3; k++) {
        if (tkey[k] == tptr[k] && tlen == T) continue;
        if (tkey[k]) cudaDestroyTextureObject(tex[k]);
        tkey[k] = nullptr;
        cudaResourceDesc rd = {};
        rd.resType = cudaResourceTypeLinear;
        rd.res.linear.devPtr = (void*)tptr[k];
        rd.res.linear.desc = cudaCreateChannelDesc(32, 32, k < 2 ? 32 : 0, k < 2 ? 32 : 0, cudaChannelFormatKindUnsigned);
        rd.res.linear.sizeInBytes = (size_t)T * (k < 2 ? 4 : 2);
        cudaTextureDesc td = {};
        td.readMode = cudaReadModeElementType;
        if (cudaCreateTextureObject(&tex[k], &rd, &td, nullptr) == cudaSuccess) tkey[k] = tptr[k];
        else { (void)cudaGetLastError(); fast = false; }
    }
    if (fast) tlen = T;
    p.t_in = tex[0]; p.t_out = tex[1]; p.t_ang = tex[2];
    if (fast) {
        void* ring = nullptr;
        cudaGetSymbolAddress(&ring, g_ring);
        uintptr_t a = ((uintptr_t)ring + WIN - 1) & ~(uintptr_t)(WIN - 1);
        if (a >> 32 != (a + RING_BYTES - 1) >> 32) a += RING_BYTES;
        p.ring = (unsigned char*)a;
        p.ring_lo = (uint32_t)a;
        p.ring_hi = (uint32_t)(a >> 32);
        k_main<<<NCTA, NT, SMEM_BYTES, st>>>(p);
    } else {
        k_direct<<<sms * 8, 256, 0, st>>>(p, T);
        k_direct_tail<<<sms * 4, 256, 0, st>>>(p);
    }
}
```
